```python
import torch

def _softmax(x, axis=-1):
    return torch.softmax(x, dim=axis)
def _gelu(x):
    return torch.nn.functional.gelu(x, approximate="tanh")
def _silu(x):
    return torch.nn.functional.silu(x)
def _sigmoid(x):
    return torch.sigmoid(x)
def _layernorm(x, axis=-1, eps=1e-5):
    m = x.mean(dim=axis, keepdim=True)
    v = x.var(dim=axis, keepdim=True, unbiased=False)
    return (x - m) / torch.sqrt(v + eps)
def _scatter_add(tgt, idx, src, axis=0):
    return tgt.clone().index_add_(axis, idx, src)
def _segment_sum(src, seg, n):
    out = torch.zeros((n,) + src.shape[1:], dtype=src.dtype)
    return out.index_add_(0, seg, src)
def _pad(x, pw):
    flat = tuple(v for pair in reversed(pw) for v in pair)
    return torch.nn.functional.pad(x, flat)

kernel_name = 'concat_heads__linear_attn_block__mha_block__prompt'

def setup_inputs():

    _w = (lambda a: (lambda t: t.to(torch.bfloat16) if t.is_floating_point() else t)(torch.as_tensor(a)))
    def _A_setup():
        B, S, D = 1, 2048, 512
        return {
            "x": _w((lambda *s: torch.randn(*s, dtype=torch.bfloat16) * 0.05)(B, S, D)),
            "wqkv": _w((lambda *s: torch.randn(*s, dtype=torch.bfloat16) * 1.6)(D, 3 * D)),
            "wo": _w((lambda *s: torch.randn(*s, dtype=torch.bfloat16) * 0.05)(D, D)),
        }
    _A_in = _A_setup()

    def _B_setup():
        B, S, D, H = 1, 2048, 512, 32
        return {
            "x": _w((lambda *s: torch.randn(*s, dtype=torch.bfloat16) * 0.2)(B, S, D)),
            "wqkv": _w((lambda *s: torch.randn(*s, dtype=torch.bfloat16) * 0.2)(D, 3 * D)),
            "wo": _w((lambda *s: torch.randn(*s, dtype=torch.bfloat16) * 0.05)(D, D)),
        }
    _B_in = _B_setup()

    return {
        "A_x": _A_in["x"],
        "A_wqkv": _A_in["wqkv"],
        "A_wo": _A_in["wo"],
        "B_x": _B_in["x"],
        "B_wqkv": _B_in["wqkv"],
        "B_wo": _B_in["wo"],
    }

def reference(A_x, A_wqkv, A_wo, B_x, B_wqkv, B_wo):
    def _A_ref(x, wqkv, wo):
        B, S, D = x.shape
        H = 32; Dh = D // H
        qkv = (lambda x, *d: x.permute(*d))((x @ wqkv).reshape(B, S, 3, H, Dh), 2, 0, 3, 1, 4)
        q, k, v = qkv[0], qkv[1], qkv[2]
        phi = lambda t: torch.where(t > 0, t + 1, torch.exp(t)) + 1e-6
        pq, pk = phi(q), phi(k)
        kv = torch.einsum("bhsd,bhse->bhde", pk, v)
        z = torch.einsum("bhsd->bhd", pk)
        num = torch.einsum("bhqd,bhde->bhqe", pq, kv)
        den = torch.einsum("bhqd,bhd->bhq", pq, z)[..., None] + 1e-6
        o = num / den
        return (lambda x, *d: x.permute(*d))(o, 0, 2, 1, 3).reshape(B, S, D) @ wo

    def _B_ref(x, wqkv, wo):
        B, S, D = x.shape
        H = 32
        Dh = D // H
        qkv = (lambda x, *d: x.permute(*d))((x @ wqkv).reshape(B, S, 3, H, Dh), 2, 0, 3, 1, 4)
        q, k, v = qkv[0], qkv[1], qkv[2]
        scores = torch.einsum("bhqd,bhkd->bhqk", q, k) * (Dh ** -0.5)
        p = _softmax(scores, axis=-1)
        o = torch.einsum("bhqk,bhkd->bhqd", p, v)
        return (lambda x, *d: x.permute(*d))(o, 0, 2, 1, 3).reshape(B, S, D) @ wo

    a = _A_ref(A_x, A_wqkv, A_wo)
    b = _B_ref(B_x, B_wqkv, B_wo)
    return torch.concatenate([a, b], axis=-1)
```

```cpp
#include <cuda_runtime.h>
#include <cuda_bf16.h>
#include <cuda.h>
#include <stdint.h>

namespace {

constexpr int S_LEN = 2048;
constexpr int DM = 512;
constexpr int NH = 32;

constexpr int KV_CHUNK_BYTES = 16384 + 24576;
constexpr int KV_HEAD_BYTES = 4 * KV_CHUNK_BYTES;
__device__ uint4 g_qfrag[2 * NH * 32 * 128];
__device__ uint4 g_kv[2 * NH * KV_HEAD_BYTES / 16];
__device__ float g_nrm[NH * 16 * 4];
__device__ __nv_bfloat16 g_o[2 * S_LEN * DM];

__device__ __forceinline__ uint32_t smem_u32(const void* p) { return (uint32_t)__cvta_generic_to_shared(p); }
__device__ __forceinline__ void mbar_init(uint32_t bar, int cnt) {
  asm volatile("mbarrier.init.shared::cta.b64 [%0], %1;" ::"r"(bar), "r"(cnt) : "memory");
}
__device__ __forceinline__ void mbar_expect_tx(uint32_t bar, uint32_t bytes) {
  asm volatile("mbarrier.arrive.expect_tx.shared::cta.b64 _, [%0], %1;" ::"r"(bar), "r"(bytes) : "memory");
}
__device__ __forceinline__ void mbar_arrive(uint32_t bar) {
  asm volatile("mbarrier.arrive.shared::cta.b64 _, [%0];" ::"r"(bar) : "memory");
}
__device__ __forceinline__ void mbar_arrive_cluster(uint32_t bar, uint32_t cta) {
  asm volatile(
      "{\n.reg .b32 ra;\nmapa.shared::cluster.u32 ra, %0, %1;\n"
      "mbarrier.arrive.release.cluster.shared::cluster.b64 _, [ra];\n}" ::"r"(bar), "r"(cta) : "memory");
}
__device__ __forceinline__ void mbar_wait(uint32_t bar, uint32_t parity) {
  asm volatile(
      "{\n.reg .pred p;\n"
      "WAIT_LOOP:\n"
      "mbarrier.try_wait.parity.shared::cta.b64 p, [%0], %1, 0x989680;\n"
      "@p bra WAIT_DONE;\n"
      "bra WAIT_LOOP;\n"
      "WAIT_DONE:\n}" ::"r"(bar), "r"(parity) : "memory");
}
__device__ __forceinline__ void mbar_wait_cluster(uint32_t bar, uint32_t parity) {
  asm volatile(
      "{\n.reg .pred p;\n"
      "WAIT_LOOP:\n"
      "mbarrier.try_wait.parity.acquire.cluster.shared::cta.b64 p, [%0], %1, 0x989680;\n"
      "@p bra WAIT_DONE;\n"
      "bra WAIT_LOOP;\n"
      "WAIT_DONE:\n}" ::"r"(bar), "r"(parity) : "memory");
}
__device__ __forceinline__ void fence_barrier_init() {
  asm volatile("fence.mbarrier_init.release.cluster;" ::: "memory");
}
__device__ __forceinline__ void fence_proxy_async() { asm volatile("fence.proxy.async.shared::cta;" ::: "memory"); }
__device__ __forceinline__ void cluster_sync() {
  asm volatile("barrier.cluster.arrive.release.aligned;\nbarrier.cluster.wait.acquire.aligned;" ::: "memory");
}
__device__ __forceinline__ void tma_load_2d(uint32_t dst, const CUtensorMap* m, int x, int y, uint32_t bar) {
  asm volatile(
      "cp.async.bulk.tensor.2d.shared::cluster.global.mbarrier::complete_tx::bytes [%0], [%1, {%3, %4}], [%2];" ::"r"(dst),
      "l"(m), "r"(bar), "r"(x), "r"(y)
      : "memory");
}
__device__ __forceinline__ void tma_load_2d_mc(uint32_t dst, const CUtensorMap* m, int x, int y, uint32_t bar, uint16_t mask) {
  asm volatile(
      "cp.async.bulk.tensor.2d.shared::cluster.global.mbarrier::complete_tx::bytes.multicast::cluster [%0], [%1, {%3, %4}], "
      "[%2], %5;" ::"r"(dst),
      "l"(m), "r"(bar), "r"(x), "r"(y), "h"(mask)
      : "memory");
}
__device__ __forceinline__ void tma_store_2d(const CUtensorMap* m, uint32_t src, int x, int y) {
  asm volatile("cp.async.bulk.tensor.2d.global.shared::cta.bulk_group [%0, {%2, %3}], [%1];" ::"l"(m), "r"(src), "r"(x),
               "r"(y)
               : "memory");
}
__device__ __forceinline__ void bulk_load(uint32_t dst, const void* src, uint32_t bytes, uint32_t bar) {
  asm volatile("cp.async.bulk.shared::cluster.global.mbarrier::complete_tx::bytes [%0], [%1], %2, [%3];" ::"r"(dst),
               "l"(src), "r"(bytes), "r"(bar)
               : "memory");
}
__device__ __forceinline__ void wg_fence() { asm volatile("wgmma.fence.sync.aligned;" ::: "memory"); }
__device__ __forceinline__ void wg_commit() { asm volatile("wgmma.commit_group.sync.aligned;" ::: "memory"); }
template <int N>
__device__ __forceinline__ void wg_wait() {
  asm volatile("wgmma.wait_group.sync.aligned %0;" ::"n"(N) : "memory");
}
template <int M>
__device__ __forceinline__ void fence_regs(float (&r)[M]) {
#pragma unroll
  for (int i = 0; i < M; i++) asm volatile("" : "+f"(r[i])::"memory");
}
__device__ __forceinline__ uint64_t mkdesc(uint32_t addr, uint32_t lbo, uint32_t sbo, uint32_t layout) {
  return (uint64_t)((addr & 0x3FFFF) >> 4) | ((uint64_t)(lbo >> 4) << 16) | ((uint64_t)(sbo >> 4) << 32) |
         ((uint64_t)layout << 62);
}
__device__ __forceinline__ uint32_t pack_bf16(float lo, float hi) {
  uint32_t r;
  asm("cvt.rn.bf16x2.f32 %0, %1, %2;" : "=r"(r) : "f"(hi), "f"(lo));
  return r;
}
__device__ __forceinline__ float bf_lo(uint32_t v) { return __uint_as_float(v << 16); }
__device__ __forceinline__ float bf_hi(uint32_t v) { return __uint_as_float(v & 0xFFFF0000u); }
__device__ __forceinline__ float round_bf16(float x) { return bf_lo(pack_bf16(x, 0.f)); }
__device__ __forceinline__ float ex2f(float x) {
  float y;
  asm("ex2.approx.ftz.f32 %0, %1;" : "=f"(y) : "f"(x));
  return y;
}

__device__ __forceinline__ void wgmma_rs_n24_tb(float (&d)[12], uint32_t a0, uint32_t a1, uint32_t a2, uint32_t a3, uint64_t descB, int scaleD) {
  asm volatile("{\n.reg .pred p;\nsetp.ne.b32 p, %17, 0;\n"
    "wgmma.mma_async.sync.aligned.m64n24k16.f32.bf16.bf16 "
    "{%0, %1, %2, %3, %4, %5, %6, %7, %8, %9, %10, %11}, {%12, %13, %14, %15}, %16, p, 1, 1, 1;\n}\n"
    : "+f"(d[0]), "+f"(d[1]), "+f"(d[2]), "+f"(d[3]), "+f"(d[4]), "+f"(d[5]), "+f"(d[6]), "+f"(d[7]),
      "+f"(d[8]), "+f"(d[9]), "+f"(d[10]), "+f"(d[11])
    : "r"(a0), "r"(a1), "r"(a2), "r"(a3), "l"(descB), "r"(scaleD));
}
__device__ __forceinline__ void wgmma_rs_n64_z(float (&d)[32], uint32_t a0, uint32_t a1, uint32_t a2, uint32_t a3, uint64_t descB) {
  asm volatile("{\n.reg .pred p;\nsetp.ne.b32 p, %37, 0;\n"
    "wgmma.mma_async.sync.aligned.m64n64k16.f32.bf16.bf16 "
    "{%0, %1, %2, %3, %4, %5, %6, %7, %8, %9, %10, %11, %12, %13, %14, %15, %16, %17, %18, %19, %20, %21, %22, %23, %24, %25, %26, %27, %28, %29, %30, %31}, {%32, %33, %34, %35}, %36, p, 1, 1, 0;\n}\n"
    : "=f"(d[0]), "=f"(d[1]), "=f"(d[2]), "=f"(d[3]), "=f"(d[4]), "=f"(d[5]), "=f"(d[6]), "=f"(d[7]),
      "=f"(d[8]), "=f"(d[9]), "=f"(d[10]), "=f"(d[11]), "=f"(d[12]), "=f"(d[13]), "=f"(d[14]), "=f"(d[15]),
      "=f"(d[16]), "=f"(d[17]), "=f"(d[18]), "=f"(d[19]), "=f"(d[20]), "=f"(d[21]), "=f"(d[22]), "=f"(d[23]),
      "=f"(d[24]), "=f"(d[25]), "=f"(d[26]), "=f"(d[27]), "=f"(d[28]), "=f"(d[29]), "=f"(d[30]), "=f"(d[31])
    : "r"(a0), "r"(a1), "r"(a2), "r"(a3), "l"(descB), "n"(0));
}
__device__ __forceinline__ void wgmma_ss_n128_tb(float (&d)[64], uint64_t descA, uint64_t descB, int scaleD) {
  asm volatile("{\n.reg .pred p;\nsetp.ne.b32 p, %66, 0;\n"
    "wgmma.mma_async.sync.aligned.m64n128k16.f32.bf16.bf16 "
    "{%0, %1, %2, %3, %4, %5, %6, %7, %8, %9, %10, %11, %12, %13, %14, %15, %16, %17, %18, %19, %20, %21, %22, %23, %24, %25, %26, %27, %28, %29, %30, %31, %32, %33, %34, %35, %36, %37, %38, %39, %40, %41, %42, %43, %44, %45, %46, %47, %48, %49, %50, %51, %52, %53, %54, %55, %56, %57, %58, %59, %60, %61, %62, %63}, %64, %65, p, 1, 1, 0, 1;\n}\n"
    : "+f"(d[0]), "+f"(d[1]), "+f"(d[2]), "+f"(d[3]), "+f"(d[4]), "+f"(d[5]), "+f"(d[6]), "+f"(d[7]),
      "+f"(d[8]), "+f"(d[9]), "+f"(d[10]), "+f"(d[11]), "+f"(d[12]), "+f"(d[13]), "+f"(d[14]), "+f"(d[15]),
      "+f"(d[16]), "+f"(d[17]), "+f"(d[18]), "+f"(d[19]), "+f"(d[20]), "+f"(d[21]), "+f"(d[22]), "+f"(d[23]),
      "+f"(d[24]), "+f"(d[25]), "+f"(d[26]), "+f"(d[27]), "+f"(d[28]), "+f"(d[29]), "+f"(d[30]), "+f"(d[31]),
      "+f"(d[32]), "+f"(d[33]), "+f"(d[34]), "+f"(d[35]), "+f"(d[36]), "+f"(d[37]), "+f"(d[38]), "+f"(d[39]),
      "+f"(d[40]), "+f"(d[41]), "+f"(d[42]), "+f"(d[43]), "+f"(d[44]), "+f"(d[45]), "+f"(d[46]), "+f"(d[47]),
      "+f"(d[48]), "+f"(d[49]), "+f"(d[50]), "+f"(d[51]), "+f"(d[52]), "+f"(d[53]), "+f"(d[54]), "+f"(d[55]),
      "+f"(d[56]), "+f"(d[57]), "+f"(d[58]), "+f"(d[59]), "+f"(d[60]), "+f"(d[61]), "+f"(d[62]), "+f"(d[63])
    : "l"(descA), "l"(descB), "r"(scaleD));
}
__device__ __forceinline__ void wgmma_ss_n192_tb(float (&d)[96], uint64_t descA, uint64_t descB, int scaleD) {
  asm volatile("{\n.reg .pred p;\nsetp.ne.b32 p, %98, 0;\n"
    "wgmma.mma_async.sync.aligned.m64n192k16.f32.bf16.bf16 "
    "{%0, %1, %2, %3, %4, %5, %6, %7, %8, %9, %10, %11, %12, %13, %14, %15, %16, %17, %18, %19, %20, %21, %22, %23, %24, %25, %26, %27, %28, %29, %30, %31, %32, %33, %34, %35, %36, %37, %38, %39, %40, %41, %42, %43, %44, %45, %46, %47, %48, %49, %50, %51, %52, %53, %54, %55, %56, %57, %58, %59, %60, %61, %62, %63, %64, %65, %66, %67, %68, %69, %70, %71, %72, %73, %74, %75, %76, %77, %78, %79, %80, %81, %82, %83, %84, %85, %86, %87, %88, %89, %90, %91, %92, %93, %94, %95}, %96, %97, p, 1, 1, 0, 1;\n}\n"
    : "+f"(d[0]), "+f"(d[1]), "+f"(d[2]), "+f"(d[3]), "+f"(d[4]), "+f"(d[5]), "+f"(d[6]), "+f"(d[7]),
      "+f"(d[8]), "+f"(d[9]), "+f"(d[10]), "+f"(d[11]), "+f"(d[12]), "+f"(d[13]), "+f"(d[14]), "+f"(d[15]),
      "+f"(d[16]), "+f"(d[17]), "+f"(d[18]), "+f"(d[19]), "+f"(d[20]), "+f"(d[21]), "+f"(d[22]), "+f"(d[23]),
      "+f"(d[24]), "+f"(d[25]), "+f"(d[26]), "+f"(d[27]), "+f"(d[28]), "+f"(d[29]), "+f"(d[30]), "+f"(d[31]),
      "+f"(d[32]), "+f"(d[33]), "+f"(d[34]), "+f"(d[35]), "+f"(d[36]), "+f"(d[37]), "+f"(d[38]), "+f"(d[39]),
      "+f"(d[40]), "+f"(d[41]), "+f"(d[42]), "+f"(d[43]), "+f"(d[44]), "+f"(d[45]), "+f"(d[46]), "+f"(d[47]),
      "+f"(d[48]), "+f"(d[49]), "+f"(d[50]), "+f"(d[51]), "+f"(d[52]), "+f"(d[53]), "+f"(d[54]), "+f"(d[55]),
      "+f"(d[56]), "+f"(d[57]), "+f"(d[58]), "+f"(d[59]), "+f"(d[60]), "+f"(d[61]), "+f"(d[62]), "+f"(d[63]),
      "+f"(d[64]), "+f"(d[65]), "+f"(d[66]), "+f"(d[67]), "+f"(d[68]), "+f"(d[69]), "+f"(d[70]), "+f"(d[71]),
      "+f"(d[72]), "+f"(d[73]), "+f"(d[74]), "+f"(d[75]), "+f"(d[76]), "+f"(d[77]), "+f"(d[78]), "+f"(d[79]),
      "+f"(d[80]), "+f"(d[81]), "+f"(d[82]), "+f"(d[83]), "+f"(d[84]), "+f"(d[85]), "+f"(d[86]), "+f"(d[87]),
      "+f"(d[88]), "+f"(d[89]), "+f"(d[90]), "+f"(d[91]), "+f"(d[92]), "+f"(d[93]), "+f"(d[94]), "+f"(d[95])
    : "l"(descA), "l"(descB), "r"(scaleD));
}


constexpr int K1_STAGES = 3;
constexpr int K1_STAGE_BYTES = 16384 + 6 * 8192;
constexpr int K1_SMEM = K1_STAGES * K1_STAGE_BYTES + 1024 + 256;
constexpr float QSCALE = 0.25f * 1.4426950408889634f;

__device__ __forceinline__ float phi_fn(float acc) {
  float t = round_bf16(acc);
  float a = round_bf16(t + 1.0f);
  float e = round_bf16(ex2f(t * 1.4426950408889634f));
  float r = t > 0.f ? a : e;
  return r + 1e-6f;
}

__global__ void __launch_bounds__(384, 1)
qkv_gemm_kernel(const __grid_constant__ CUtensorMap mxA, const __grid_constant__ CUtensorMap mxB,
                const __grid_constant__ CUtensorMap mwA, const __grid_constant__ CUtensorMap mwB) {
  extern __shared__ uint8_t smem_raw[];
  const uint32_t sbase = (smem_u32(smem_raw) + 1023) & ~1023u;
  const uint32_t bar_full = sbase + K1_STAGES * K1_STAGE_BYTES;
  const uint32_t bar_empty = bar_full + 8 * K1_STAGES;
  __shared__ uint32_t s_red[8 * 3];

  const int rank = blockIdx.x & 1;
  const int pair = blockIdx.x >> 1;
  const int branch = pair >> 5;
  const int rp = (pair & 31) >> 2;
  const int cp = pair & 3;
  const int rt = rp * 2 + rank;
  const int warp = threadIdx.x >> 5;

  if (threadIdx.x == 0) {
    for (int i = 0; i < K1_STAGES; i++) {
      mbar_init(bar_full + 8 * i, 1);
      mbar_init(bar_empty + 8 * i, 4);
    }
    fence_barrier_init();
  }
  if (threadIdx.x < 24) s_red[threadIdx.x] = 0;
  __syncthreads();
  cluster_sync();

  if (warp >= 8) {
    asm volatile("setmaxnreg.dec.sync.aligned.u32 40;");
    if (threadIdx.x == 256) {
      const CUtensorMap* mx = branch ? &mxA : &mxB;
      const CUtensorMap* mw = branch ? &mwA : &mwB;
      const int h0 = cp * 8 + rank * 4;
      for (int kb = 0; kb < 8; kb++) {
        const int s = kb % K1_STAGES;
        if (kb >= K1_STAGES) mbar_wait_cluster(bar_empty + 8 * s, ((kb / K1_STAGES) - 1) & 1);
        const uint32_t st = sbase + s * K1_STAGE_BYTES;
        mbar_expect_tx(bar_full + 8 * s, K1_STAGE_BYTES);
        tma_load_2d(st, mx, kb * 64, rt * 128, bar_full + 8 * s);
#pragma unroll
        for (int p = 0; p < 3; p++)
          tma_load_2d_mc(st + 16384 + (rank * 3 + p) * 8192, mw, p * 512 + h0 * 16, kb * 64, bar_full + 8 * s, (uint16_t)3);
      }
    }
    __syncwarp();
    cluster_sync();
  } else {
    asm volatile("setmaxnreg.inc.sync.aligned.u32 232;");
    const int wg = warp >> 2;
    float acc0[96], acc1[96];
    for (int kb = 0; kb < 8; kb++) {
      const int s = kb % K1_STAGES;
      mbar_wait(bar_full + 8 * s, (kb / K1_STAGES) & 1);
      const uint32_t st = sbase + s * K1_STAGE_BYTES;
      const uint64_t dA = mkdesc(st + wg * 8192, 16, 1024, 1);
      const uint64_t dB = mkdesc(st + 16384, 8192, 1024, 1);
      wg_fence();
#pragma unroll
      for (int k = 0; k < 4; k++) {
        wgmma_ss_n192_tb(acc0, dA + k * 2, dB + k * 128, (kb | k) != 0);
        wgmma_ss_n192_tb(acc1, dA + k * 2, dB + k * 128 + 3 * 512, (kb | k) != 0);
      }
      wg_commit();
      if (kb > 0) {
        wg_wait<1>();
        if ((threadIdx.x & 127) == 0) {
          const int sp = (kb - 1) % K1_STAGES;
          mbar_arrive_cluster(bar_empty + 8 * sp, 0);
          mbar_arrive_cluster(bar_empty + 8 * sp, 1);
        }
      }
    }
    wg_wait<0>();
    fence_regs(acc0);
    fence_regs(acc1);

    const int lane = threadIdx.x & 31;
    const int tid = threadIdx.x & 127;
    const int row0 = rt * 128 + wg * 64 + (warp & 3) * 16;
    const int tile64 = rt * 2 + wg;
    const int obr = branch;
    const int chunk = row0 >> 9;
    const int grp = (row0 & 511) >> 3;
#pragma unroll
    for (int j = 0; j < 2; j++) {
      float(&acc)[96] = j ? acc1 : acc0;
#pragma unroll
      for (int hh = 0; hh < 4; hh++) {
        const int head = cp * 8 + j * 4 + hh;
        uint8_t* img = reinterpret_cast<uint8_t*>(g_kv) + (size_t)(obr * NH + head) * KV_HEAD_BYTES + chunk * KV_CHUNK_BYTES;
        uint32_t r[4];
        {
          const float* a = &acc[hh * 8];
          if (branch == 0) {
#pragma unroll
            for (int i = 0; i < 4; i++) r[i] = pack_bf16(a[(i & 1) * 2 + (i >> 1) * 4] * QSCALE, a[(i & 1) * 2 + (i >> 1) * 4 + 1] * QSCALE);
          } else {
#pragma unroll
            for (int i = 0; i < 4; i++) r[i] = pack_bf16(phi_fn(a[(i & 1) * 2 + (i >> 1) * 4]), phi_fn(a[(i & 1) * 2 + (i >> 1) * 4 + 1]));
          }
          g_qfrag[((obr * NH + head) * 32 + tile64) * 128 + tid] = make_uint4(r[0], r[1], r[2], r[3]);
          if (branch == 0) {
            float n0 = bf_lo(r[0]) * bf_lo(r[0]) + bf_hi(r[0]) * bf_hi(r[0]) + bf_lo(r[2]) * bf_lo(r[2]) + bf_hi(r[2]) * bf_hi(r[2]);
            float n1 = bf_lo(r[1]) * bf_lo(r[1]) + bf_hi(r[1]) * bf_hi(r[1]) + bf_lo(r[3]) * bf_lo(r[3]) + bf_hi(r[3]) * bf_hi(r[3]);
            n0 += __shfl_xor_sync(0xffffffffu, n0, 1);
            n1 += __shfl_xor_sync(0xffffffffu, n1, 1);
            n0 += __shfl_xor_sync(0xffffffffu, n0, 2);
            n1 += __shfl_xor_sync(0xffffffffu, n1, 2);
            uint32_t m = __float_as_uint(fmaxf(n0, n1)) | ((n0 != n0 || n1 != n1) ? 0x7F800000u : 0u);
            m = __reduce_max_sync(0xffffffffu, m);
            if (lane == 0) atomicMax(&s_red[(j * 4 + hh) * 3 + 0], m);
          }
        }
        {
          const float* a = &acc[32 + hh * 8];
          if (branch == 0) {
#pragma unroll
            for (int i = 0; i < 4; i++) r[i] = pack_bf16(a[(i & 1) * 2 + (i >> 1) * 4], a[(i & 1) * 2 + (i >> 1) * 4 + 1]);
          } else {
#pragma unroll
            for (int i = 0; i < 4; i++) r[i] = pack_bf16(phi_fn(a[(i & 1) * 2 + (i >> 1) * 4]), phi_fn(a[(i & 1) * 2 + (i >> 1) * 4 + 1]));
          }
          uint32_t* kp = reinterpret_cast<uint32_t*>(img + grp * 256) + lane;
          kp[0] = r[0];
          kp[64] = r[1];
          kp[32] = r[2];
          kp[64 + 32] = r[3];
          if (branch == 0) {
            float n0 = bf_lo(r[0]) * bf_lo(r[0]) + bf_hi(r[0]) * bf_hi(r[0]) + bf_lo(r[2]) * bf_lo(r[2]) + bf_hi(r[2]) * bf_hi(r[2]);
            float n1 = bf_lo(r[1]) * bf_lo(r[1]) + bf_hi(r[1]) * bf_hi(r[1]) + bf_lo(r[3]) * bf_lo(r[3]) + bf_hi(r[3]) * bf_hi(r[3]);
            n0 += __shfl_xor_sync(0xffffffffu, n0, 1);
            n1 += __shfl_xor_sync(0xffffffffu, n1, 1);
            n0 += __shfl_xor_sync(0xffffffffu, n0, 2);
            n1 += __shfl_xor_sync(0xffffffffu, n1, 2);
            uint32_t m = __float_as_uint(fmaxf(n0, n1)) | ((n0 != n0 || n1 != n1) ? 0x7F800000u : 0u);
            m = __reduce_max_sync(0xffffffffu, m);
            if (lane == 0) atomicMax(&s_red[(j * 4 + hh) * 3 + 1], m);
          }
        }
        {
          const float* a = &acc[64 + hh * 8];
#pragma unroll
          for (int i = 0; i < 4; i++) r[i] = pack_bf16(a[(i & 1) * 2 + (i >> 1) * 4], a[(i & 1) * 2 + (i >> 1) * 4 + 1]);
          uint32_t* vp = reinterpret_cast<uint32_t*>(img + 16384 + grp * 384) + lane;
          vp[0] = r[0];
          vp[96] = r[1];
          vp[32] = r[2];
          vp[96 + 32] = r[3];
          if (branch == 0) {
            vp[64] = 0x3F803F80u;
            vp[96 + 64] = 0x3F803F80u;
            uint32_t m = 0;
#pragma unroll
            for (int i = 0; i < 4; i++) m = max(m, max((r[i] << 16) & 0x7FFF0000u, r[i] & 0x7FFF0000u));
            m = __reduce_max_sync(0xffffffffu, m);
            if (lane == 0) atomicMax(&s_red[(j * 4 + hh) * 3 + 2], m);
          }
        }
      }
    }
    if (branch == 0) {
      asm volatile("bar.sync 1, 256;" ::: "memory");
      if (threadIdx.x < 24) {
        const int hh = threadIdx.x / 3, c = threadIdx.x % 3;
        g_nrm[((cp * 8 + hh) * 16 + rt) * 4 + c] = __uint_as_float(s_red[threadIdx.x]);
      }
    }
    __syncwarp();
    cluster_sync();
  }
}

constexpr int K2_SMEM = KV_HEAD_BYTES + 1024 + 256;

struct ExpC {
  uint32_t k3c00, kmask, seven;
};
__device__ __forceinline__ uint32_t hfma2(uint32_t a, uint32_t b, uint32_t c) {
  uint32_t r;
  asm("fma.rn.f16x2 %0, %1, %2, %3;" : "=r"(r) : "r"(a), "r"(b), "r"(c));
  return r;
}
__device__ __forceinline__ uint32_t exp2_poly_pair(float t0, float t1, const ExpC& c) {
  uint32_t u;
  asm("prmt.b32 %0, %1, %2, 0x5410;" : "=r"(u) : "r"(__float_as_uint(t0)), "r"(__float_as_uint(t1)));
  uint32_t m;
  asm("lop3.b32 %0, %1, 0x03FF03FF, %2, 0xEA;" : "=r"(m) : "r"(u), "r"(c.k3c00));
  uint32_t p = hfma2(m, 0x2cfd2cfdu, 0x9fe09fe0u);
  p = hfma2(p, m, 0x37a137a1u);
  p = hfma2(p, m, 0x4ab94abau);
  uint32_t mu;
  asm("lop3.b32 %0, %1, 0xFC00FC00, %2, 0xEA;" : "=r"(mu) : "r"(u), "r"(c.kmask));
  uint32_t r;
  asm("{.reg .b32 t; shf.r.wrap.b32 t, %1, %2, 3; add.u32 %0, t, %3;}" : "=r"(r) : "r"(mu), "r"(c.seven), "r"(p));
  return r;
}
__device__ __forceinline__ float gadd(float x, float M, uint32_t g) {
  float r = x;
  asm("{.reg .pred p; setp.ne.b32 p, %2, -1; @p add.f32 %0, %0, %1;}" : "+f"(r) : "f"(M), "r"(g));
  return r;
}
__device__ __forceinline__ float gex2(float x, uint32_t g) {
  float r = x;
  asm("{.reg .pred p; setp.ne.b32 p, %1, -1; @p ex2.approx.ftz.f32 %0, %0;}" : "+f"(r) : "r"(g));
  return r;
}
template <int NPOLY, int NPAIR, int CH, int D>
__device__ __forceinline__ void exp_tile(const float (&s)[2 * NPAIR], uint32_t (&p)[NPAIR], const ExpC& c) {
#pragma unroll
  for (int i = 0; i < NPAIR; i++) {
    const bool isPoly = ((i + 1) * NPOLY / 32) != (i * NPOLY / 32);
    const int ch = i / CH;
    const bool gated = ch >= D;
    int gi = (ch - D) * CH + CH - 1;
    if (gated) {
      while (gi > (ch - D) * CH && !(((gi + 1) * NPOLY / 32) != (gi * NPOLY / 32))) gi--;
    }
    const uint32_t g = gated ? p[gi] : 0;
    if (!isPoly) {
      if (gated) p[i] = pack_bf16(gex2(s[2 * i], g), gex2(s[2 * i + 1], g));
      else p[i] = pack_bf16(ex2f(s[2 * i]), ex2f(s[2 * i + 1]));
    } else {
      if (gated) p[i] = exp2_poly_pair(gadd(s[2 * i], 12329.f, g), gadd(s[2 * i + 1], 12329.f, g), c);
      else p[i] = exp2_poly_pair(s[2 * i] + 12329.f, s[2 * i + 1] + 12329.f, c);
    }
  }
}

__device__ __forceinline__ void ldsm4t(uint32_t (&b)[4], uint32_t addr) {
  asm volatile("ldmatrix.sync.aligned.m8n8.x4.trans.shared.b16 {%0,%1,%2,%3}, [%4];"
               : "=r"(b[0]), "=r"(b[1]), "=r"(b[2]), "=r"(b[3])
               : "r"(addr));
}
__device__ __forceinline__ void hmma(float (&c)[4], uint32_t a0, uint32_t a1, uint32_t a2, uint32_t a3, uint32_t b0, uint32_t b1) {
  asm("mma.sync.aligned.m16n8k16.row.col.f32.bf16.bf16.f32 {%0,%1,%2,%3}, {%4,%5,%6,%7}, {%8,%9}, {%0,%1,%2,%3};"
      : "+f"(c[0]), "+f"(c[1]), "+f"(c[2]), "+f"(c[3])
      : "r"(a0), "r"(a1), "r"(a2), "r"(a3), "r"(b0), "r"(b1));
}

__device__ __forceinline__ void store_o(__nv_bfloat16* o, int row0, int head, int lane, const uint32_t (&r)[4]) {
  const int g = lane >> 2, t = lane & 3;
  uint32_t* p0 = reinterpret_cast<uint32_t*>(o + (size_t)(row0 + g) * DM + head * 16) + t;
  uint32_t* p1 = reinterpret_cast<uint32_t*>(o + (size_t)(row0 + g + 8) * DM + head * 16) + t;
  p0[0] = r[0];
  p1[0] = r[1];
  p0[4] = r[2];
  p1[4] = r[3];
}

template <bool SAFE>
__device__ __forceinline__ void attn_tile(uint32_t sb, uint32_t bar, const uint4 qf, const ExpC& ec, uint32_t (&outp)[4]) {
  float s[32];
  uint32_t p[16];
  float o[12];
#pragma unroll
  for (int i = 0; i < 12; i++) asm volatile("mov.f32 %0, 0f00000000;" : "=f"(o[i]));
  float m0 = -INFINITY, m1 = -INFINITY;

  mbar_wait(bar, 0);
  uint64_t dK = mkdesc(sb, 128, 256, 0);
  uint64_t dV = mkdesc(sb + 16384, 384, 128, 0);
  wg_fence();
  wgmma_rs_n64_z(s, qf.x, qf.y, qf.z, qf.w, dK);
  wg_commit();
#pragma unroll 1
  for (int j = 0; j < 32; j++) {
    const int jn = (j + 1) & 31;
    if ((jn & 7) == 0) mbar_wait(bar + 8 * (jn >> 3), 0);
    const uint64_t dKn = mkdesc(sb + (jn >> 3) * KV_CHUNK_BYTES + (jn & 7) * 2048, 128, 256, 0);
    wg_wait<0>();
    fence_regs(s);
    if (!SAFE) {
      exp_tile<16, 16, 4, 2>(s, p, ec);
    } else {
      fence_regs(o);
      float x0 = s[0], x1 = s[2];
#pragma unroll
      for (int i = 0; i < 8; i++) {
        x0 = fmaxf(x0, fmaxf(s[4 * i], s[4 * i + 1]));
        x1 = fmaxf(x1, fmaxf(s[4 * i + 2], s[4 * i + 3]));
      }
      x0 = fmaxf(x0, __shfl_xor_sync(0xffffffffu, x0, 1));
      x1 = fmaxf(x1, __shfl_xor_sync(0xffffffffu, x1, 1));
      x0 = fmaxf(x0, __shfl_xor_sync(0xffffffffu, x0, 2));
      x1 = fmaxf(x1, __shfl_xor_sync(0xffffffffu, x1, 2));
      const float n0 = fmaxf(m0, x0), n1 = fmaxf(m1, x1);
      const float c0 = ex2f(m0 - n0), c1 = ex2f(m1 - n1);
      m0 = n0;
      m1 = n1;
#pragma unroll
      for (int i = 0; i < 3; i++) {
        o[4 * i] *= c0;
        o[4 * i + 1] *= c0;
        o[4 * i + 2] *= c1;
        o[4 * i + 3] *= c1;
      }
#pragma unroll
      for (int i = 0; i < 8; i++) {
        p[2 * i] = pack_bf16(ex2f(s[4 * i] - n0), ex2f(s[4 * i + 1] - n0));
        p[2 * i + 1] = pack_bf16(ex2f(s[4 * i + 2] - n1), ex2f(s[4 * i + 3] - n1));
      }
    }
    wg_fence();
    wgmma_rs_n64_z(s, qf.x, qf.y, qf.z, qf.w, dKn);
#pragma unroll
    for (int k = 0; k < 4; k++) wgmma_rs_n24_tb(o, p[4 * k], p[4 * k + 1], p[4 * k + 2], p[4 * k + 3], dV + k * 48, 1);
    wg_commit();
    dV = mkdesc(sb + 16384 + (jn >> 3) * KV_CHUNK_BYTES + (jn & 7) * 3072, 384, 128, 0);
  }
  wg_wait<0>();
  fence_regs(o);
  fence_regs(s);
  const float r0 = 1.0f / o[8], r1 = 1.0f / o[10];
  outp[0] = pack_bf16(o[0] * r0, o[1] * r0);
  outp[1] = pack_bf16(o[2] * r1, o[3] * r1);
  outp[2] = pack_bf16(o[4] * r0, o[5] * r0);
  outp[3] = pack_bf16(o[6] * r1, o[7] * r1);
}

__device__ __forceinline__ void linear_attn_cta(uint8_t* smem_raw, uint32_t sbase, uint32_t bar, int cta) {
  const int warp = threadIdx.x >> 5, lane = threadIdx.x & 31;
  float* red = reinterpret_cast<float*>(smem_raw + (sbase - smem_u32(smem_raw)) + 3 * KV_CHUNK_BYTES);
  uint32_t* kvs = reinterpret_cast<uint32_t*>(red + 16 * 384);
  const uint8_t* img = reinterpret_cast<const uint8_t*>(g_kv) + (size_t)(NH + cta * 8) * KV_HEAD_BYTES;
  if (threadIdx.x == 0) {
    for (int i = 0; i < 3; i++) {
      mbar_expect_tx(bar + 8 * i, KV_CHUNK_BYTES);
      bulk_load(sbase + i * KV_CHUNK_BYTES, img + (size_t)i * KV_CHUNK_BYTES, KV_CHUNK_BYTES, bar + 8 * i);
    }
  }
  int ci = 0;
  for (int hh = 0; hh < 8; hh++) {
    const int head = cta * 8 + hh;
    float c0[4] = {0, 0, 0, 0}, c1[4] = {0, 0, 0, 0}, c2[4] = {0, 0, 0, 0};
    for (int c = 0; c < 4; c++, ci++) {
      const int s = ci % 3;
      mbar_wait(bar + 8 * s, (ci / 3) & 1);
      const uint32_t cb = sbase + s * KV_CHUNK_BYTES;
#pragma unroll
      for (int kk = 0; kk < 2; kk++) {
        const int g0 = warp * 4 + kk * 2;
        uint32_t a[4], b[4];
        ldsm4t(a, cb + (g0 + (lane >> 4)) * 256 + ((lane >> 3) & 1) * 128 + (lane & 7) * 16);
        ldsm4t(b, cb + 16384 + (g0 + ((lane >> 3) & 1)) * 384 + (lane >> 4) * 128 + (lane & 7) * 16);
        hmma(c0, a[0], a[1], a[2], a[3], b[0], b[1]);
        hmma(c1, a[0], a[1], a[2], a[3], b[2], b[3]);
        hmma(c2, a[0], a[1], a[2], a[3], 0x3F803F80u, 0x3F803F80u);
      }
      __syncthreads();
      if (threadIdx.x == 0 && ci + 3 < 32) {
        mbar_expect_tx(bar + 8 * s, KV_CHUNK_BYTES);
        bulk_load(sbase + s * KV_CHUNK_BYTES, img + (size_t)(ci + 3) * KV_CHUNK_BYTES, KV_CHUNK_BYTES, bar + 8 * s);
      }
    }
#pragma unroll
    for (int i = 0; i < 4; i++) {
      red[warp * 384 + (0 + i) * 32 + lane] = c0[i];
      red[warp * 384 + (4 + i) * 32 + lane] = c1[i];
      red[warp * 384 + (8 + i) * 32 + lane] = c2[i];
    }
    __syncthreads();
    if (threadIdx.x < 384) {
      float acc = 0.f;
#pragma unroll
      for (int w = 0; w < 16; w++) acc += red[w * 384 + threadIdx.x];
      red[threadIdx.x] = round_bf16(acc);
    }
    __syncthreads();
    if (threadIdx.x < 192) {
      const int f = threadIdx.x >> 5;
      const int blk = f >> 1, half = f & 1;
      const int g = lane >> 2, t = lane & 3;
      float v[2];
#pragma unroll
      for (int x = 0; x < 2; x++) {
        const int d = 2 * t + 8 * half + x;
        const int e = (blk == 2) ? 0 : g;
        const int i = (d >> 3) * 2 + (e & 1);
        const int l = (d & 7) * 4 + (e >> 1);
        v[x] = red[(blk * 4 + i) * 32 + l];
      }
      kvs[f * 32 + lane] = pack_bf16(v[0], v[1]);
    }
    __syncthreads();
    uint32_t bf[6];
#pragma unroll
    for (int f = 0; f < 6; f++) bf[f] = kvs[f * 32 + lane];
#pragma unroll 2
    for (int rb = 0; rb < 8; rb++) {
      const int blk16 = warp * 8 + rb;
      const uint4 q = g_qfrag[((NH + head) * 32 + (blk16 >> 2)) * 128 + (blk16 & 3) * 32 + lane];
      float n0[4] = {0, 0, 0, 0}, n1[4] = {0, 0, 0, 0}, dn[4] = {0, 0, 0, 0};
      hmma(n0, q.x, q.y, q.z, q.w, bf[0], bf[1]);
      hmma(n1, q.x, q.y, q.z, q.w, bf[2], bf[3]);
      hmma(dn, q.x, q.y, q.z, q.w, bf[4], bf[5]);
      const float d0 = round_bf16(round_bf16(dn[0]) + 1e-6f), d1 = round_bf16(round_bf16(dn[2]) + 1e-6f);
      uint32_t r[4];
      r[0] = pack_bf16(__fdividef(round_bf16(n0[0]), d0), __fdividef(round_bf16(n0[1]), d0));
      r[1] = pack_bf16(__fdividef(round_bf16(n0[2]), d1), __fdividef(round_bf16(n0[3]), d1));
      r[2] = pack_bf16(__fdividef(round_bf16(n1[0]), d0), __fdividef(round_bf16(n1[1]), d0));
      r[3] = pack_bf16(__fdividef(round_bf16(n1[2]), d1), __fdividef(round_bf16(n1[3]), d1));
      store_o(g_o, blk16 * 16, head, lane, r);
    }
    __syncthreads();
  }
}

__global__ void __launch_bounds__(512, 1) attn_kernel(ExpC ec) {
  extern __shared__ uint8_t smem_raw[];
  const uint32_t sbase = (smem_u32(smem_raw) + 1023) & ~1023u;
  const uint32_t bar = sbase + KV_HEAD_BYTES;
  if (threadIdx.x == 0) {
    for (int i = 0; i < 4; i++) mbar_init(bar + 8 * i, 1);
    fence_barrier_init();
    fence_proxy_async();
  }
  __syncthreads();
  if (blockIdx.x >= 128) {
    linear_attn_cta(smem_raw, sbase, bar, blockIdx.x - 128);
    return;
  }
  const int head = blockIdx.x >> 2, qb = blockIdx.x & 3;
  if (threadIdx.x == 0) {
    const uint8_t* img = reinterpret_cast<const uint8_t*>(g_kv) + (size_t)head * KV_HEAD_BYTES;
    for (int i = 0; i < 4; i++) {
      mbar_expect_tx(bar + 8 * i, KV_CHUNK_BYTES);
      bulk_load(sbase + i * KV_CHUNK_BYTES, img + (size_t)i * KV_CHUNK_BYTES, KV_CHUNK_BYTES, bar + 8 * i);
    }
  }
  const int lane = threadIdx.x & 31;
  bool safe_path;
  {
    float4 n = make_float4(0.f, 0.f, 0.f, 0.f);
    if (lane < 16) n = *reinterpret_cast<const float4*>(&g_nrm[(head * 16 + lane) * 4]);
    uint32_t qm = ((lane >> 2) == qb) ? __float_as_uint(n.x) : 0u;
    qm = __reduce_max_sync(0xffffffffu, qm);
    const uint32_t km = __reduce_max_sync(0xffffffffu, __float_as_uint(n.y));
    const uint32_t vm = __reduce_max_sync(0xffffffffu, __float_as_uint(n.z));
    const float b2 = __uint_as_float(qm) * __uint_as_float(km);
    const float vmax = __uint_as_float(vm);
    const bool ok = (b2 <= 21.5f * 21.5f) && (vmax <= 1.0e24f) && (vmax >= 1.0e-18f || vmax == 0.f);
    safe_path = !ok;
  }
  const int wg = threadIdx.x >> 7, warp = (threadIdx.x >> 5) & 3;
  for (int t = 0; t < 2; t++) {
    const int tile64 = qb * 8 + wg * 2 + t;
    const uint4 qf = g_qfrag[(head * 32 + tile64) * 128 + (threadIdx.x & 127)];
    uint32_t r[4];
    if (!safe_path) attn_tile<false>(sbase, bar, qf, ec, r);
    else attn_tile<true>(sbase, bar, qf, ec, r);
    store_o(g_o + (size_t)S_LEN * DM, tile64 * 64 + warp * 16, head, lane, r);
  }
}

constexpr int K3_STAGES = 6;
constexpr int K3_STAGE_BYTES = 16384 + 2 * 8192;
constexpr int K3_SMEM = K3_STAGES * K3_STAGE_BYTES + 1024 + 256;

__global__ void __launch_bounds__(288, 1)
out_gemm_kernel(const __grid_constant__ CUtensorMap mo, const __grid_constant__ CUtensorMap mwA,
                const __grid_constant__ CUtensorMap mwB, const __grid_constant__ CUtensorMap mout) {
  extern __shared__ uint8_t smem_raw[];
  const uint32_t sbase = (smem_u32(smem_raw) + 1023) & ~1023u;
  const uint32_t bar_full = sbase + K3_STAGES * K3_STAGE_BYTES;
  const uint32_t bar_empty = bar_full + 8 * K3_STAGES;
  const int branch = blockIdx.x >> 6;
  const int rt = (blockIdx.x & 63) >> 2;
  const int ct = blockIdx.x & 3;
  const int warp = threadIdx.x >> 5;
  if (threadIdx.x == 0) {
    for (int i = 0; i < K3_STAGES; i++) {
      mbar_init(bar_full + 8 * i, 1);
      mbar_init(bar_empty + 8 * i, 2);
    }
    fence_barrier_init();
  }
  __syncthreads();
  if (warp == 8) {
    if ((threadIdx.x & 31) == 0) {
      const CUtensorMap* mw = branch ? &mwB : &mwA;
      for (int kb = 0; kb < 8; kb++) {
        const int s = kb % K3_STAGES;
        if (kb >= K3_STAGES) mbar_wait(bar_empty + 8 * s, ((kb / K3_STAGES) - 1) & 1);
        const uint32_t st = sbase + s * K3_STAGE_BYTES;
        mbar_expect_tx(bar_full + 8 * s, K3_STAGE_BYTES);
        tma_load_2d(st, &mo, kb * 64, branch * S_LEN + rt * 128, bar_full + 8 * s);
        tma_load_2d(st + 16384, mw, ct * 128, kb * 64, bar_full + 8 * s);
        tma_load_2d(st + 16384 + 8192, mw, ct * 128 + 64, kb * 64, bar_full + 8 * s);
      }
    }
  } else {
    const int wg = warp >> 2;
    float acc[64];
    for (int kb = 0; kb < 8; kb++) {
      const int s = kb % K3_STAGES;
      mbar_wait(bar_full + 8 * s, (kb / K3_STAGES) & 1);
      const uint32_t st = sbase + s * K3_STAGE_BYTES;
      const uint64_t dA = mkdesc(st + wg * 8192, 16, 1024, 1);
      const uint64_t dB = mkdesc(st + 16384, 8192, 1024, 1);
      wg_fence();
#pragma unroll
      for (int k = 0; k < 4; k++) wgmma_ss_n128_tb(acc, dA + k * 2, dB + k * 128, (kb | k) != 0);
      wg_commit();
      if (kb > 0) {
        wg_wait<1>();
        if ((threadIdx.x & 127) == 0) mbar_arrive(bar_empty + 8 * ((kb - 1) % K3_STAGES));
      }
    }
    wg_wait<0>();
    fence_regs(acc);
    asm volatile("bar.sync 1, 256;" ::: "memory");
    const int lane = threadIdx.x & 31;
    const int rloc = wg * 64 + (warp & 3) * 16 + (lane & 15);
#pragma unroll
    for (int c16 = 0; c16 < 8; c16++) {
      const float* a = &acc[c16 * 8];
      const uint32_t r0 = pack_bf16(a[0], a[1]), r1 = pack_bf16(a[2], a[3]), r2 = pack_bf16(a[4], a[5]), r3 = pack_bf16(a[6], a[7]);
      const int chunk = (c16 & 3) * 2 + (lane >> 4);
      const uint32_t addr = sbase + (c16 >> 2) * 16384 + rloc * 128 + ((chunk ^ (rloc & 7)) << 4);
      asm volatile("stmatrix.sync.aligned.m8n8.x4.shared.b16 [%0], {%1,%2,%3,%4};" ::"r"(addr), "r"(r0), "r"(r1), "r"(r2), "r"(r3)
                   : "memory");
    }
    fence_proxy_async();
    asm volatile("bar.sync 1, 256;" ::: "memory");
    if (threadIdx.x == 0) {
      tma_store_2d(&mout, sbase, branch * DM + ct * 128, rt * 128);
      tma_store_2d(&mout, sbase + 16384, branch * DM + ct * 128 + 64, rt * 128);
      asm volatile("cp.async.bulk.commit_group;" ::: "memory");
      asm volatile("cp.async.bulk.wait_group 0;" ::: "memory");
    }
  }
}

typedef CUresult (*EncodeFn)(CUtensorMap*, CUtensorMapDataType, cuuint32_t, void*, const cuuint64_t*, const cuuint64_t*,
                             const cuuint32_t*, const cuuint32_t*, CUtensorMapInterleave, CUtensorMapSwizzle,
                             CUtensorMapL2promotion, CUtensorMapFloatOOBfill);

void make_map(EncodeFn enc, CUtensorMap* m, const void* ptr, uint64_t inner, uint64_t outer, uint32_t box_inner, uint32_t box_outer) {
  cuuint64_t dims[2] = {inner, outer};
  cuuint64_t strides[1] = {inner * 2};
  cuuint32_t box[2] = {box_inner, box_outer};
  cuuint32_t es[2] = {1, 1};
  enc(m, CU_TENSOR_MAP_DATA_TYPE_BFLOAT16, 2, const_cast<void*>(ptr), dims, strides, box, es, CU_TENSOR_MAP_INTERLEAVE_NONE,
      CU_TENSOR_MAP_SWIZZLE_128B, CU_TENSOR_MAP_L2_PROMOTION_L2_256B, CU_TENSOR_MAP_FLOAT_OOB_FILL_NONE);
}

struct HostState {
  bool init;
  const void* key[7];
  CUtensorMap mxA, mxB, mwA, mwB, mo, mwoA, mwoB, mout;
};
HostState g_hs;

}

extern "C" void kernel_launch(void* const* d_in, const int* in_sizes, int n_in, void* d_out, int out_size) {
  (void)in_sizes; (void)n_in; (void)out_size;
  HostState& hs = g_hs;
  bool same = hs.init && hs.key[6] == d_out;
  for (int i = 0; i < 6 && same; i++) same = hs.key[i] == d_in[i];
  if (!same) {
    void* fn = nullptr;
    cudaDriverEntryPointQueryResult qr;
    cudaGetDriverEntryPoint("cuTensorMapEncodeTiled", &fn, cudaEnableDefault, &qr);
    EncodeFn enc = (EncodeFn)fn;
    void* go = nullptr;
    cudaGetSymbolAddress(&go, g_o);
    make_map(enc, &hs.mxA, d_in[0], 512, 2048, 64, 128);
    make_map(enc, &hs.mwA, d_in[1], 1536, 512, 64, 64);
    make_map(enc, &hs.mwoA, d_in[2], 512, 512, 64, 64);
    make_map(enc, &hs.mxB, d_in[3], 512, 2048, 64, 128);
    make_map(enc, &hs.mwB, d_in[4], 1536, 512, 64, 64);
    make_map(enc, &hs.mwoB, d_in[5], 512, 512, 64, 64);
    make_map(enc, &hs.mo, go, 512, 4096, 64, 128);
    make_map(enc, &hs.mout, d_out, 1024, 2048, 64, 128);
    cudaFuncSetAttribute(qkv_gemm_kernel, cudaFuncAttributeMaxDynamicSharedMemorySize, K1_SMEM);
    cudaFuncSetAttribute(attn_kernel, cudaFuncAttributeMaxDynamicSharedMemorySize, K2_SMEM);
    cudaFuncSetAttribute(out_gemm_kernel, cudaFuncAttributeMaxDynamicSharedMemorySize, K3_SMEM);
    for (int i = 0; i < 6; i++) hs.key[i] = d_in[i];
    hs.key[6] = d_out;
    hs.init = true;
  }
  cudaStream_t st = cudaStreamPerThread;
  {
    cudaLaunchConfig_t cfg = {};
    cfg.gridDim = dim3(128);
    cfg.blockDim = dim3(384);
    cfg.dynamicSmemBytes = K1_SMEM;
    cfg.stream = st;
    cudaLaunchAttribute at[1];
    at[0].id = cudaLaunchAttributeClusterDimension;
    at[0].val.clusterDim.x = 2;
    at[0].val.clusterDim.y = 1;
    at[0].val.clusterDim.z = 1;
    cfg.attrs = at;
    cfg.numAttrs = 1;
    cudaLaunchKernelEx(&cfg, qkv_gemm_kernel, hs.mxA, hs.mxB, hs.mwA, hs.mwB);
  }
  ExpC ec{0x3C003C00u, 0x00070000u, 7u};
  attn_kernel<<<132, 512, K2_SMEM, st>>>(ec);
  out_gemm_kernel<<<128, 288, K3_SMEM, st>>>(hs.mo, hs.mwoA, hs.mwoB, hs.mout);
}
```

```cpp
#include <cuda_runtime.h>
#include <cuda_bf16.h>
#include <cuda.h>
#include <stdint.h>

namespace {

constexpr int S_LEN = 2048;
constexpr int DM = 512;
constexpr int NH = 32;

constexpr int KV_CHUNK_BYTES = 16384 + 24576;
constexpr int KV_HEAD_BYTES = 4 * KV_CHUNK_BYTES;
__device__ uint4 g_qfrag[2 * NH * 32 * 128];
__device__ uint4 g_kv[2 * NH * KV_HEAD_BYTES / 16];
__device__ float g_kvpart[16 * NH * 384];
__device__ float g_nrm[NH * 16 * 4];
__device__ __nv_bfloat16 g_o[2 * S_LEN * DM];

#define PROF_T(k, i) do {} while (0)
#define PROF_G(k, i) do {} while (0)
__device__ __forceinline__ uint32_t smem_u32(const void* p) { return (uint32_t)__cvta_generic_to_shared(p); }
__device__ __forceinline__ void mbar_init(uint32_t bar, int cnt) {
  asm volatile("mbarrier.init.shared::cta.b64 [%0], %1;" ::"r"(bar), "r"(cnt) : "memory");
}
__device__ __forceinline__ void mbar_expect_tx(uint32_t bar, uint32_t bytes) {
  asm volatile("mbarrier.arrive.expect_tx.shared::cta.b64 _, [%0], %1;" ::"r"(bar), "r"(bytes) : "memory");
}
__device__ __forceinline__ void mbar_arrive(uint32_t bar) {
  asm volatile("mbarrier.arrive.shared::cta.b64 _, [%0];" ::"r"(bar) : "memory");
}
__device__ __forceinline__ void mbar_arrive_cluster(uint32_t bar, uint32_t cta) {
  asm volatile(
      "{\n.reg .b32 ra;\nmapa.shared::cluster.u32 ra, %0, %1;\n"
      "mbarrier.arrive.shared::cluster.b64 _, [ra];\n}" ::"r"(bar), "r"(cta) : "memory");
}
__device__ __forceinline__ void mbar_wait(uint32_t bar, uint32_t parity) {
  asm volatile(
      "{\n.reg .pred p;\n"
      "WAIT_LOOP:\n"
      "mbarrier.try_wait.parity.shared::cta.b64 p, [%0], %1, 0x989680;\n"
      "@p bra WAIT_DONE;\n"
      "bra WAIT_LOOP;\n"
      "WAIT_DONE:\n}" ::"r"(bar), "r"(parity) : "memory");
}
__device__ __forceinline__ void mbar_wait_cluster(uint32_t bar, uint32_t parity) {
  asm volatile(
      "{\n.reg .pred p;\n"
      "WAIT_LOOP:\n"
      "mbarrier.try_wait.parity.acquire.cluster.shared::cta.b64 p, [%0], %1, 0x989680;\n"
      "@p bra WAIT_DONE;\n"
      "bra WAIT_LOOP;\n"
      "WAIT_DONE:\n}" ::"r"(bar), "r"(parity) : "memory");
}
__device__ __forceinline__ void fence_barrier_init() {
  asm volatile("fence.mbarrier_init.release.cluster;" ::: "memory");
}
__device__ __forceinline__ void fence_proxy_async() { asm volatile("fence.proxy.async.shared::cta;" ::: "memory"); }
__device__ __forceinline__ void cluster_sync_relaxed() {
  asm volatile("barrier.cluster.arrive.relaxed.aligned;\nbarrier.cluster.wait.aligned;" ::: "memory");
}
__device__ __forceinline__ void tma_load_2d(uint32_t dst, const CUtensorMap* m, int x, int y, uint32_t bar) {
  asm volatile(
      "cp.async.bulk.tensor.2d.shared::cluster.global.mbarrier::complete_tx::bytes [%0], [%1, {%3, %4}], [%2];" ::"r"(dst),
      "l"(m), "r"(bar), "r"(x), "r"(y)
      : "memory");
}
__device__ __forceinline__ void tma_load_2d_mc(uint32_t dst, const CUtensorMap* m, int x, int y, uint32_t bar, uint16_t mask) {
  asm volatile(
      "cp.async.bulk.tensor.2d.shared::cluster.global.mbarrier::complete_tx::bytes.multicast::cluster [%0], [%1, {%3, %4}], "
      "[%2], %5;" ::"r"(dst),
      "l"(m), "r"(bar), "r"(x), "r"(y), "h"(mask)
      : "memory");
}
__device__ __forceinline__ void tma_store_2d(const CUtensorMap* m, uint32_t src, int x, int y) {
  asm volatile("cp.async.bulk.tensor.2d.global.shared::cta.bulk_group [%0, {%2, %3}], [%1];" ::"l"(m), "r"(src), "r"(x),
               "r"(y)
               : "memory");
}
__device__ __forceinline__ void bulk_load(uint32_t dst, const void* src, uint32_t bytes, uint32_t bar) {
  asm volatile("cp.async.bulk.shared::cluster.global.mbarrier::complete_tx::bytes [%0], [%1], %2, [%3];" ::"r"(dst),
               "l"(src), "r"(bytes), "r"(bar)
               : "memory");
}
__device__ __forceinline__ void wg_fence() { asm volatile("wgmma.fence.sync.aligned;" ::: "memory"); }
__device__ __forceinline__ void wg_commit() { asm volatile("wgmma.commit_group.sync.aligned;" ::: "memory"); }
template <int N>
__device__ __forceinline__ void wg_wait() {
  asm volatile("wgmma.wait_group.sync.aligned %0;" ::"n"(N) : "memory");
}
template <int M>
__device__ __forceinline__ void fence_regs(float (&r)[M]) {
#pragma unroll
  for (int i = 0; i < M; i++) asm volatile("" : "+f"(r[i])::"memory");
}
__device__ __forceinline__ uint64_t mkdesc(uint32_t addr, uint32_t lbo, uint32_t sbo, uint32_t layout) {
  return (uint64_t)((addr & 0x3FFFF) >> 4) | ((uint64_t)(lbo >> 4) << 16) | ((uint64_t)(sbo >> 4) << 32) |
         ((uint64_t)layout << 62);
}
__device__ __forceinline__ uint32_t pack_bf16(float lo, float hi) {
  uint32_t r;
  asm("cvt.rn.bf16x2.f32 %0, %1, %2;" : "=r"(r) : "f"(hi), "f"(lo));
  return r;
}
__device__ __forceinline__ float bf_lo(uint32_t v) { return __uint_as_float(v << 16); }
__device__ __forceinline__ float bf_hi(uint32_t v) { return __uint_as_float(v & 0xFFFF0000u); }
__device__ __forceinline__ float round_bf16(float x) { return bf_lo(pack_bf16(x, 0.f)); }
__device__ __forceinline__ float ex2f(float x) {
  float y;
  asm("ex2.approx.ftz.f32 %0, %1;" : "=f"(y) : "f"(x));
  return y;
}

__device__ __forceinline__ void wgmma_rs_n24_tb(float (&d)[12], uint32_t a0, uint32_t a1, uint32_t a2, uint32_t a3, uint64_t descB, int scaleD) {
  asm volatile("{\n.reg .pred p;\nsetp.ne.b32 p, %17, 0;\n"
    "wgmma.mma_async.sync.aligned.m64n24k16.f32.bf16.bf16 "
    "{%0, %1, %2, %3, %4, %5, %6, %7, %8, %9, %10, %11}, {%12, %13, %14, %15}, %16, p, 1, 1, 1;\n}\n"
    : "+f"(d[0]), "+f"(d[1]), "+f"(d[2]), "+f"(d[3]), "+f"(d[4]), "+f"(d[5]), "+f"(d[6]), "+f"(d[7]),
      "+f"(d[8]), "+f"(d[9]), "+f"(d[10]), "+f"(d[11])
    : "r"(a0), "r"(a1), "r"(a2), "r"(a3), "l"(descB), "r"(scaleD));
}
__device__ __forceinline__ void wgmma_rs_n64_z(float (&d)[32], uint32_t a0, uint32_t a1, uint32_t a2, uint32_t a3, uint64_t descB) {
  asm volatile("{\n.reg .pred p;\nsetp.ne.b32 p, %37, 0;\n"
    "wgmma.mma_async.sync.aligned.m64n64k16.f32.bf16.bf16 "
    "{%0, %1, %2, %3, %4, %5, %6, %7, %8, %9, %10, %11, %12, %13, %14, %15, %16, %17, %18, %19, %20, %21, %22, %23, %24, %25, %26, %27, %28, %29, %30, %31}, {%32, %33, %34, %35}, %36, p, 1, 1, 0;\n}\n"
    : "=f"(d[0]), "=f"(d[1]), "=f"(d[2]), "=f"(d[3]), "=f"(d[4]), "=f"(d[5]), "=f"(d[6]), "=f"(d[7]),
      "=f"(d[8]), "=f"(d[9]), "=f"(d[10]), "=f"(d[11]), "=f"(d[12]), "=f"(d[13]), "=f"(d[14]), "=f"(d[15]),
      "=f"(d[16]), "=f"(d[17]), "=f"(d[18]), "=f"(d[19]), "=f"(d[20]), "=f"(d[21]), "=f"(d[22]), "=f"(d[23]),
      "=f"(d[24]), "=f"(d[25]), "=f"(d[26]), "=f"(d[27]), "=f"(d[28]), "=f"(d[29]), "=f"(d[30]), "=f"(d[31])
    : "r"(a0), "r"(a1), "r"(a2), "r"(a3), "l"(descB), "n"(0));
}
__device__ __forceinline__ void wgmma_ss_n128_tb(float (&d)[64], uint64_t descA, uint64_t descB, int scaleD) {
  asm volatile("{\n.reg .pred p;\nsetp.ne.b32 p, %66, 0;\n"
    "wgmma.mma_async.sync.aligned.m64n128k16.f32.bf16.bf16 "
    "{%0, %1, %2, %3, %4, %5, %6, %7, %8, %9, %10, %11, %12, %13, %14, %15, %16, %17, %18, %19, %20, %21, %22, %23, %24, %25, %26, %27, %28, %29, %30, %31, %32, %33, %34, %35, %36, %37, %38, %39, %40, %41, %42, %43, %44, %45, %46, %47, %48, %49, %50, %51, %52, %53, %54, %55, %56, %57, %58, %59, %60, %61, %62, %63}, %64, %65, p, 1, 1, 0, 1;\n}\n"
    : "+f"(d[0]), "+f"(d[1]), "+f"(d[2]), "+f"(d[3]), "+f"(d[4]), "+f"(d[5]), "+f"(d[6]), "+f"(d[7]),
      "+f"(d[8]), "+f"(d[9]), "+f"(d[10]), "+f"(d[11]), "+f"(d[12]), "+f"(d[13]), "+f"(d[14]), "+f"(d[15]),
      "+f"(d[16]), "+f"(d[17]), "+f"(d[18]), "+f"(d[19]), "+f"(d[20]), "+f"(d[21]), "+f"(d[22]), "+f"(d[23]),
      "+f"(d[24]), "+f"(d[25]), "+f"(d[26]), "+f"(d[27]), "+f"(d[28]), "+f"(d[29]), "+f"(d[30]), "+f"(d[31]),
      "+f"(d[32]), "+f"(d[33]), "+f"(d[34]), "+f"(d[35]), "+f"(d[36]), "+f"(d[37]), "+f"(d[38]), "+f"(d[39]),
      "+f"(d[40]), "+f"(d[41]), "+f"(d[42]), "+f"(d[43]), "+f"(d[44]), "+f"(d[45]), "+f"(d[46]), "+f"(d[47]),
      "+f"(d[48]), "+f"(d[49]), "+f"(d[50]), "+f"(d[51]), "+f"(d[52]), "+f"(d[53]), "+f"(d[54]), "+f"(d[55]),
      "+f"(d[56]), "+f"(d[57]), "+f"(d[58]), "+f"(d[59]), "+f"(d[60]), "+f"(d[61]), "+f"(d[62]), "+f"(d[63])
    : "l"(descA), "l"(descB), "r"(scaleD));
}
__device__ __forceinline__ void wgmma_ss_n192_tb(float (&d)[96], uint64_t descA, uint64_t descB, int scaleD) {
  asm volatile("{\n.reg .pred p;\nsetp.ne.b32 p, %98, 0;\n"
    "wgmma.mma_async.sync.aligned.m64n192k16.f32.bf16.bf16 "
    "{%0, %1, %2, %3, %4, %5, %6, %7, %8, %9, %10, %11, %12, %13, %14, %15, %16, %17, %18, %19, %20, %21, %22, %23, %24, %25, %26, %27, %28, %29, %30, %31, %32, %33, %34, %35, %36, %37, %38, %39, %40, %41, %42, %43, %44, %45, %46, %47, %48, %49, %50, %51, %52, %53, %54, %55, %56, %57, %58, %59, %60, %61, %62, %63, %64, %65, %66, %67, %68, %69, %70, %71, %72, %73, %74, %75, %76, %77, %78, %79, %80, %81, %82, %83, %84, %85, %86, %87, %88, %89, %90, %91, %92, %93, %94, %95}, %96, %97, p, 1, 1, 0, 1;\n}\n"
    : "+f"(d[0]), "+f"(d[1]), "+f"(d[2]), "+f"(d[3]), "+f"(d[4]), "+f"(d[5]), "+f"(d[6]), "+f"(d[7]),
      "+f"(d[8]), "+f"(d[9]), "+f"(d[10]), "+f"(d[11]), "+f"(d[12]), "+f"(d[13]), "+f"(d[14]), "+f"(d[15]),
      "+f"(d[16]), "+f"(d[17]), "+f"(d[18]), "+f"(d[19]), "+f"(d[20]), "+f"(d[21]), "+f"(d[22]), "+f"(d[23]),
      "+f"(d[24]), "+f"(d[25]), "+f"(d[26]), "+f"(d[27]), "+f"(d[28]), "+f"(d[29]), "+f"(d[30]), "+f"(d[31]),
      "+f"(d[32]), "+f"(d[33]), "+f"(d[34]), "+f"(d[35]), "+f"(d[36]), "+f"(d[37]), "+f"(d[38]), "+f"(d[39]),
      "+f"(d[40]), "+f"(d[41]), "+f"(d[42]), "+f"(d[43]), "+f"(d[44]), "+f"(d[45]), "+f"(d[46]), "+f"(d[47]),
      "+f"(d[48]), "+f"(d[49]), "+f"(d[50]), "+f"(d[51]), "+f"(d[52]), "+f"(d[53]), "+f"(d[54]), "+f"(d[55]),
      "+f"(d[56]), "+f"(d[57]), "+f"(d[58]), "+f"(d[59]), "+f"(d[60]), "+f"(d[61]), "+f"(d[62]), "+f"(d[63]),
      "+f"(d[64]), "+f"(d[65]), "+f"(d[66]), "+f"(d[67]), "+f"(d[68]), "+f"(d[69]), "+f"(d[70]), "+f"(d[71]),
      "+f"(d[72]), "+f"(d[73]), "+f"(d[74]), "+f"(d[75]), "+f"(d[76]), "+f"(d[77]), "+f"(d[78]), "+f"(d[79]),
      "+f"(d[80]), "+f"(d[81]), "+f"(d[82]), "+f"(d[83]), "+f"(d[84]), "+f"(d[85]), "+f"(d[86]), "+f"(d[87]),
      "+f"(d[88]), "+f"(d[89]), "+f"(d[90]), "+f"(d[91]), "+f"(d[92]), "+f"(d[93]), "+f"(d[94]), "+f"(d[95])
    : "l"(descA), "l"(descB), "r"(scaleD));
}

__device__ __forceinline__ void ldsm4t(uint32_t (&b)[4], uint32_t addr) {
  asm volatile("ldmatrix.sync.aligned.m8n8.x4.trans.shared.b16 {%0,%1,%2,%3}, [%4];"
               : "=r"(b[0]), "=r"(b[1]), "=r"(b[2]), "=r"(b[3])
               : "r"(addr));
}
__device__ __forceinline__ void hmma(float (&c)[4], uint32_t a0, uint32_t a1, uint32_t a2, uint32_t a3, uint32_t b0, uint32_t b1) {
  asm("mma.sync.aligned.m16n8k16.row.col.f32.bf16.bf16.f32 {%0,%1,%2,%3}, {%4,%5,%6,%7}, {%8,%9}, {%0,%1,%2,%3};"
      : "+f"(c[0]), "+f"(c[1]), "+f"(c[2]), "+f"(c[3])
      : "r"(a0), "r"(a1), "r"(a2), "r"(a3), "r"(b0), "r"(b1));
}

__device__ __forceinline__ uint32_t movm(uint32_t a) {
  uint32_t d;
  asm volatile("movmatrix.sync.aligned.m8n8.trans.b16 %0, %1;" : "=r"(d) : "r"(a));
  return d;
}

constexpr int K1_STAGES = 3;
constexpr int K1_STAGE_BYTES = 16384 + 6 * 8192;
constexpr int K1_SMEM = K1_STAGES * K1_STAGE_BYTES + 1024 + 256;
constexpr float QSCALE = 0.25f * 1.4426950408889634f;

__device__ __forceinline__ float phi_fn(float acc) {
  float t = round_bf16(acc);
  float a = round_bf16(t + 1.0f);
  float e = round_bf16(ex2f(t * 1.4426950408889634f));
  float r = t > 0.f ? a : e;
  return r + 1e-6f;
}

__global__ void __launch_bounds__(384, 1)
qkv_gemm_kernel(const __grid_constant__ CUtensorMap mxA, const __grid_constant__ CUtensorMap mxB,
                const __grid_constant__ CUtensorMap mwA, const __grid_constant__ CUtensorMap mwB) {
  extern __shared__ uint8_t smem_raw[];
  const uint32_t sbase = (smem_u32(smem_raw) + 1023) & ~1023u;
  const uint32_t bar_full = sbase + K1_STAGES * K1_STAGE_BYTES;
  const uint32_t bar_empty = bar_full + 8 * K1_STAGES;
  __shared__ uint32_t s_red[24];

  const int rank = blockIdx.x & 1;
  const int pair = blockIdx.x >> 1;
  const int branch = pair >> 5;
  const int rp = (pair & 31) >> 2;
  const int cp = pair & 3;
  const int rt = rp * 2 + rank;
  const int warp = threadIdx.x >> 5;
  if (threadIdx.x == 0) { PROF_G(0, 30); PROF_T(0, 0); }

  if (threadIdx.x == 0) {
    for (int i = 0; i < K1_STAGES; i++) {
      mbar_init(bar_full + 8 * i, 1);
      mbar_init(bar_empty + 8 * i, 4);
    }
    fence_barrier_init();
  }
  if (threadIdx.x < 24) s_red[threadIdx.x] = 0;
  __syncthreads();
  cluster_sync_relaxed();
  if (threadIdx.x == 0) PROF_T(0, 1);

  if (warp >= 8) {
    asm volatile("setmaxnreg.dec.sync.aligned.u32 40;");
    if (threadIdx.x == 256) {
      const CUtensorMap* mx = branch ? &mxA : &mxB;
      const CUtensorMap* mw = branch ? &mwA : &mwB;
      const int h0 = cp * 8 + rank * 4;
      for (int kb = 0; kb < 8; kb++) {
        const int s = kb % K1_STAGES;
        if (kb >= K1_STAGES) mbar_wait(bar_empty + 8 * s, ((kb / K1_STAGES) - 1) & 1);
        const uint32_t st = sbase + s * K1_STAGE_BYTES;
        mbar_expect_tx(bar_full + 8 * s, K1_STAGE_BYTES);
        tma_load_2d(st, mx, kb * 64, rt * 128, bar_full + 8 * s);
#pragma unroll
        for (int p = 0; p < 3; p++)
          tma_load_2d_mc(st + 16384 + (rank * 3 + p) * 8192, mw, p * 512 + h0 * 16, kb * 64, bar_full + 8 * s, (uint16_t)3);
      }
    }
    __syncwarp();
    cluster_sync_relaxed();
  } else {
    asm volatile("setmaxnreg.inc.sync.aligned.u32 232;");
    const int wg = warp >> 2;
    float acc0[96], acc1[96];
    for (int kb = 0; kb < 8; kb++) {
      const int s = kb % K1_STAGES;
      mbar_wait(bar_full + 8 * s, (kb / K1_STAGES) & 1);
      if (threadIdx.x == 0) PROF_T(0, 2 + kb);
      const uint32_t st = sbase + s * K1_STAGE_BYTES;
      const uint64_t dA = mkdesc(st + wg * 8192, 16, 1024, 1);
      const uint64_t dB = mkdesc(st + 16384, 8192, 1024, 1);
      wg_fence();
#pragma unroll
      for (int k = 0; k < 4; k++) {
        wgmma_ss_n192_tb(acc0, dA + k * 2, dB + k * 128, (kb | k) != 0);
        wgmma_ss_n192_tb(acc1, dA + k * 2, dB + k * 128 + 3 * 512, (kb | k) != 0);
      }
      wg_commit();
      if (kb > 0) {
        wg_wait<1>();
        if ((threadIdx.x & 127) == 0) {
          const int sp = (kb - 1) % K1_STAGES;
          mbar_arrive_cluster(bar_empty + 8 * sp, 0);
          mbar_arrive_cluster(bar_empty + 8 * sp, 1);
        }
      }
    }
    wg_wait<0>();
    fence_regs(acc0);
    fence_regs(acc1);
    if (threadIdx.x == 0) PROF_T(0, 10);

    const int lane = threadIdx.x & 31;
    const int tid = threadIdx.x & 127;
    const int row0 = rt * 128 + wg * 64 + (warp & 3) * 16;
    const int tile64 = rt * 2 + wg;
    uint4* qf = g_qfrag + ((size_t)(branch * NH + cp * 8) * 32 + tile64) * 128 + tid;
    if (branch == 0) {
      uint32_t* img = reinterpret_cast<uint32_t*>(reinterpret_cast<uint8_t*>(g_kv) + (size_t)(cp * 8) * KV_HEAD_BYTES +
                                                  (row0 >> 9) * KV_CHUNK_BYTES);
      const int grp = (row0 & 511) >> 3;
      uint32_t* kp = img + grp * 64 + lane;
      uint32_t* vp = img + 4096 + grp * 96 + lane;
      float vmax = 0.f;
#pragma unroll
      for (int j = 0; j < 2; j++) {
        float(&acc)[96] = j ? acc1 : acc0;
#pragma unroll
        for (int hh = 0; hh < 4; hh++) {
          const int h = j * 4 + hh;
          const float* a = &acc[hh * 8];
          const float* k = &acc[32 + hh * 8];
          const float* v = &acc[64 + hh * 8];
          qf[h * 32 * 128] = make_uint4(pack_bf16(a[0] * QSCALE, a[1] * QSCALE), pack_bf16(a[2] * QSCALE, a[3] * QSCALE),
                                        pack_bf16(a[4] * QSCALE, a[5] * QSCALE), pack_bf16(a[6] * QSCALE, a[7] * QSCALE));
          uint32_t* kh = kp + h * (KV_HEAD_BYTES / 4);
          kh[0] = pack_bf16(k[0], k[1]);
          kh[64] = pack_bf16(k[2], k[3]);
          kh[32] = pack_bf16(k[4], k[5]);
          kh[96] = pack_bf16(k[6], k[7]);
          uint32_t* vh = vp + h * (KV_HEAD_BYTES / 4);
          vh[0] = pack_bf16(v[0], v[1]);
          vh[96] = pack_bf16(v[2], v[3]);
          vh[32] = pack_bf16(v[4], v[5]);
          vh[128] = pack_bf16(v[6], v[7]);
          vh[64] = 0x3F803F80u;
          vh[160] = 0x3F803F80u;
          float q0 = a[0] * a[0] + a[1] * a[1] + a[4] * a[4] + a[5] * a[5];
          float q1 = a[2] * a[2] + a[3] * a[3] + a[6] * a[6] + a[7] * a[7];
          float k0 = k[0] * k[0] + k[1] * k[1] + k[4] * k[4] + k[5] * k[5];
          float k1 = k[2] * k[2] + k[3] * k[3] + k[6] * k[6] + k[7] * k[7];
#pragma unroll
          for (int o = 1; o <= 2; o <<= 1) {
            q0 += __shfl_xor_sync(0xffffffffu, q0, o);
            q1 += __shfl_xor_sync(0xffffffffu, q1, o);
            k0 += __shfl_xor_sync(0xffffffffu, k0, o);
            k1 += __shfl_xor_sync(0xffffffffu, k1, o);
          }
          const uint32_t qm = __reduce_max_sync(0xffffffffu, max(__float_as_uint(q0) & 0x7FFFFFFFu, __float_as_uint(q1) & 0x7FFFFFFFu));
          const uint32_t km = __reduce_max_sync(0xffffffffu, max(__float_as_uint(k0) & 0x7FFFFFFFu, __float_as_uint(k1) & 0x7FFFFFFFu));
          if (lane == 0) {
            atomicMax(&s_red[h * 2 + 0], qm);
            atomicMax(&s_red[h * 2 + 1], km);
          }
#pragma unroll
          for (int i = 0; i < 8; i++) vmax = fmaxf(vmax, fabsf(v[i]) + (v[i] != v[i] ? INFINITY : 0.f));
        }
      }
      const uint32_t vm = __reduce_max_sync(0xffffffffu, __float_as_uint(vmax) & 0x7FFFFFFFu);
      if (lane == 0) atomicMax(&s_red[16], vm);
      asm volatile("bar.sync 1, 256;" ::: "memory");
      if (threadIdx.x < 8) {
        *reinterpret_cast<float4*>(&g_nrm[((cp * 8 + threadIdx.x) * 16 + rt) * 4]) =
            make_float4(__uint_as_float(s_red[threadIdx.x * 2]), __uint_as_float(s_red[threadIdx.x * 2 + 1]), __uint_as_float(s_red[16]), 0.f);
      }
    } else {
      asm volatile("bar.sync 1, 256;" ::: "memory");
      float* slot = reinterpret_cast<float*>(smem_raw + (sbase - smem_u32(smem_raw)));
      float* myslot = slot + warp * 3072 + lane;
#pragma unroll
      for (int j = 0; j < 2; j++) {
        float(&acc)[96] = j ? acc1 : acc0;
#pragma unroll
        for (int hh = 0; hh < 4; hh++) {
          const int h = j * 4 + hh;
          const float* a = &acc[hh * 8];
          const float* k = &acc[32 + hh * 8];
          const float* v = &acc[64 + hh * 8];
          qf[h * 32 * 128] = make_uint4(pack_bf16(phi_fn(a[0]), phi_fn(a[1])), pack_bf16(phi_fn(a[2]), phi_fn(a[3])),
                                        pack_bf16(phi_fn(a[4]), phi_fn(a[5])), pack_bf16(phi_fn(a[6]), phi_fn(a[7])));
          const uint32_t a0 = movm(pack_bf16(phi_fn(k[0]), phi_fn(k[1])));
          const uint32_t a2 = movm(pack_bf16(phi_fn(k[2]), phi_fn(k[3])));
          const uint32_t a1 = movm(pack_bf16(phi_fn(k[4]), phi_fn(k[5])));
          const uint32_t a3 = movm(pack_bf16(phi_fn(k[6]), phi_fn(k[7])));
          const uint32_t b0 = movm(pack_bf16(v[0], v[1]));
          const uint32_t b1 = movm(pack_bf16(v[2], v[3]));
          const uint32_t b2 = movm(pack_bf16(v[4], v[5]));
          const uint32_t b3 = movm(pack_bf16(v[6], v[7]));
          float c0[4] = {0, 0, 0, 0}, c1[4] = {0, 0, 0, 0}, c2[4] = {0, 0, 0, 0};
          hmma(c0, a0, a1, a2, a3, b0, b1);
          hmma(c1, a0, a1, a2, a3, b2, b3);
          hmma(c2, a0, a1, a2, a3, 0x3F803F80u, 0x3F803F80u);
#pragma unroll
          for (int i = 0; i < 4; i++) {
            myslot[h * 384 + i * 32] = c0[i];
            myslot[h * 384 + (4 + i) * 32] = c1[i];
            myslot[h * 384 + (8 + i) * 32] = c2[i];
          }
        }
      }
      asm volatile("bar.sync 1, 256;" ::: "memory");
      float* dst = g_kvpart + ((size_t)rt * NH + cp * 8) * 384;
#pragma unroll
      for (int i = 0; i < 12; i++) {
        const int o = threadIdx.x + i * 256;
        float sum = 0.f;
#pragma unroll
        for (int w = 0; w < 8; w++) sum += slot[w * 3072 + o];
        dst[o] = sum;
      }
    }
    if (threadIdx.x == 0) PROF_T(0, 11);
    __syncwarp();
    cluster_sync_relaxed();
    if (threadIdx.x == 0) { PROF_T(0, 12); PROF_G(0, 31); }
  }
}

constexpr int K2_SMEM = KV_HEAD_BYTES + 1024 + 256;

struct ExpC {
  uint32_t k3c00, kmask, seven;
};
__device__ __forceinline__ uint32_t hfma2(uint32_t a, uint32_t b, uint32_t c) {
  uint32_t r;
  asm("fma.rn.f16x2 %0, %1, %2, %3;" : "=r"(r) : "r"(a), "r"(b), "r"(c));
  return r;
}
__device__ __forceinline__ uint32_t exp2_poly_pair(float t0, float t1, const ExpC& c) {
  uint32_t u;
  asm("prmt.b32 %0, %1, %2, 0x5410;" : "=r"(u) : "r"(__float_as_uint(t0)), "r"(__float_as_uint(t1)));
  uint32_t m;
  asm("lop3.b32 %0, %1, 0x03FF03FF, %2, 0xEA;" : "=r"(m) : "r"(u), "r"(c.k3c00));
  uint32_t p = hfma2(m, 0x2cfd2cfdu, 0x9fe09fe0u);
  p = hfma2(p, m, 0x37a137a1u);
  p = hfma2(p, m, 0x4ab94abau);
  uint32_t mu;
  asm("lop3.b32 %0, %1, 0xFC00FC00, %2, 0xEA;" : "=r"(mu) : "r"(u), "r"(c.kmask));
  uint32_t r;
  asm("{.reg .b32 t; shf.r.wrap.b32 t, %1, %2, 3; add.u32 %0, t, %3;}" : "=r"(r) : "r"(mu), "r"(c.seven), "r"(p));
  return r;
}
__device__ __forceinline__ float gadd(float x, float M, uint32_t g) {
  float r = x;
  asm("{.reg .pred p; setp.ne.b32 p, %2, -1; @p add.f32 %0, %0, %1;}" : "+f"(r) : "f"(M), "r"(g));
  return r;
}
__device__ __forceinline__ float gex2(float x, uint32_t g) {
  float r = x;
  asm("{.reg .pred p; setp.ne.b32 p, %1, -1; @p ex2.approx.ftz.f32 %0, %0;}" : "+f"(r) : "r"(g));
  return r;
}
template <int NPOLY, int NPAIR, int CH, int D>
__device__ __forceinline__ void exp_tile(const float (&s)[2 * NPAIR], uint32_t (&p)[NPAIR], const ExpC& c) {
#pragma unroll
  for (int i = 0; i < NPAIR; i++) {
    const bool isPoly = ((i + 1) * NPOLY / 32) != (i * NPOLY / 32);
    const int ch = i / CH;
    const bool gated = ch >= D;
    int gi = (ch - D) * CH + CH - 1;
    if (gated) {
      while (gi > (ch - D) * CH && !(((gi + 1) * NPOLY / 32) != (gi * NPOLY / 32))) gi--;
    }
    const uint32_t g = gated ? p[gi] : 0;
    if (!isPoly) {
      if (gated) p[i] = pack_bf16(gex2(s[2 * i], g), gex2(s[2 * i + 1], g));
      else p[i] = pack_bf16(ex2f(s[2 * i]), ex2f(s[2 * i + 1]));
    } else {
      if (gated) p[i] = exp2_poly_pair(gadd(s[2 * i], 12329.f, g), gadd(s[2 * i + 1], 12329.f, g), c);
      else p[i] = exp2_poly_pair(s[2 * i] + 12329.f, s[2 * i + 1] + 12329.f, c);
    }
  }
}

__device__ __forceinline__ void store_o(__nv_bfloat16* o, int row0, int head, int lane, const uint32_t (&r)[4]) {
  const int g = lane >> 2, t = lane & 3;
  uint32_t* p0 = reinterpret_cast<uint32_t*>(o + (size_t)(row0 + g) * DM + head * 16) + t;
  uint32_t* p1 = reinterpret_cast<uint32_t*>(o + (size_t)(row0 + g + 8) * DM + head * 16) + t;
  p0[0] = r[0];
  p1[0] = r[1];
  p0[4] = r[2];
  p1[4] = r[3];
}

template <bool SAFE>
__device__ __forceinline__ void attn_tile(uint32_t sb, uint32_t bar, const uint4 qf, const ExpC& ec, uint32_t (&outp)[4]) {
  float s[32];
  uint32_t p[16];
  float o[12];
#pragma unroll
  for (int i = 0; i < 12; i++) asm volatile("mov.f32 %0, 0f00000000;" : "=f"(o[i]));
  float m0 = -INFINITY, m1 = -INFINITY;

  mbar_wait(bar, 0);
  uint64_t dK = mkdesc(sb, 128, 256, 0);
  uint64_t dV = mkdesc(sb + 16384, 384, 128, 0);
  wg_fence();
  wgmma_rs_n64_z(s, qf.x, qf.y, qf.z, qf.w, dK);
  wg_commit();
#pragma unroll 1
  for (int j = 0; j < 32; j++) {
    const int jn = (j + 1) & 31;
    if ((jn & 7) == 0) mbar_wait(bar + 8 * (jn >> 3), 0);
    const uint64_t dKn = mkdesc(sb + (jn >> 3) * KV_CHUNK_BYTES + (jn & 7) * 2048, 128, 256, 0);
    wg_wait<0>();
    fence_regs(s);
    if (!SAFE) {
      exp_tile<16, 16, 4, 2>(s, p, ec);
    } else {
      fence_regs(o);
      float x0 = s[0], x1 = s[2];
#pragma unroll
      for (int i = 0; i < 8; i++) {
        x0 = fmaxf(x0, fmaxf(s[4 * i], s[4 * i + 1]));
        x1 = fmaxf(x1, fmaxf(s[4 * i + 2], s[4 * i + 3]));
      }
      x0 = fmaxf(x0, __shfl_xor_sync(0xffffffffu, x0, 1));
      x1 = fmaxf(x1, __shfl_xor_sync(0xffffffffu, x1, 1));
      x0 = fmaxf(x0, __shfl_xor_sync(0xffffffffu, x0, 2));
      x1 = fmaxf(x1, __shfl_xor_sync(0xffffffffu, x1, 2));
      const float n0 = fmaxf(m0, x0), n1 = fmaxf(m1, x1);
      const float c0 = ex2f(m0 - n0), c1 = ex2f(m1 - n1);
      m0 = n0;
      m1 = n1;
#pragma unroll
      for (int i = 0; i < 3; i++) {
        o[4 * i] *= c0;
        o[4 * i + 1] *= c0;
        o[4 * i + 2] *= c1;
        o[4 * i + 3] *= c1;
      }
#pragma unroll
      for (int i = 0; i < 8; i++) {
        p[2 * i] = pack_bf16(ex2f(s[4 * i] - n0), ex2f(s[4 * i + 1] - n0));
        p[2 * i + 1] = pack_bf16(ex2f(s[4 * i + 2] - n1), ex2f(s[4 * i + 3] - n1));
      }
    }
    wg_fence();
    wgmma_rs_n64_z(s, qf.x, qf.y, qf.z, qf.w, dKn);
#pragma unroll
    for (int k = 0; k < 4; k++) wgmma_rs_n24_tb(o, p[4 * k], p[4 * k + 1], p[4 * k + 2], p[4 * k + 3], dV + k * 48, 1);
    wg_commit();
    dV = mkdesc(sb + 16384 + (jn >> 3) * KV_CHUNK_BYTES + (jn & 7) * 3072, 384, 128, 0);
  }
  wg_wait<0>();
  fence_regs(o);
  fence_regs(s);
  const float r0 = 1.0f / o[8], r1 = 1.0f / o[10];
  outp[0] = pack_bf16(o[0] * r0, o[1] * r0);
  outp[1] = pack_bf16(o[2] * r1, o[3] * r1);
  outp[2] = pack_bf16(o[4] * r0, o[5] * r0);
  outp[3] = pack_bf16(o[6] * r1, o[7] * r1);
}

__device__ __forceinline__ void linear_attn_cta(uint8_t* smem_raw, uint32_t sbase, const CUtensorMap* mo16, int cta) {
  const int warp = threadIdx.x >> 5, lane = threadIdx.x & 31;
  float* red = reinterpret_cast<float*>(smem_raw + (sbase - smem_u32(smem_raw)) + 131072);
  {
    const float* src = g_kvpart + (size_t)cta * 8 * 384;
    float sum[6];
#pragma unroll
    for (int i = 0; i < 6; i++) sum[i] = 0.f;
#pragma unroll
    for (int r = 0; r < 16; r++) {
#pragma unroll
      for (int i = 0; i < 6; i++) sum[i] += src[(size_t)r * NH * 384 + threadIdx.x + i * 512];
    }
#pragma unroll
    for (int i = 0; i < 6; i++) red[threadIdx.x + i * 512] = round_bf16(sum[i]);
  }
  __syncthreads();
  uint32_t bf[8][6];
  {
    const int g = lane >> 2, t = lane & 3;
#pragma unroll
    for (int h = 0; h < 8; h++) {
#pragma unroll
      for (int f = 0; f < 6; f++) {
        const int blk = f >> 1, half = f & 1;
        const int e = (blk == 2) ? 0 : g;
        const int d = 2 * t + 8 * half;
        const int base = h * 384 + (blk * 4 + half * 2 + (e & 1)) * 32 + (e >> 1);
        bf[h][f] = pack_bf16(red[base + (d & 7) * 4], red[base + ((d + 1) & 7) * 4]);
      }
    }
  }
  const uint32_t stg = sbase + warp * 8192;
#pragma unroll 1
  for (int rb = 0; rb < 8; rb++) {
    const int blk16 = rb * 16 + warp;
    const uint4* qp = g_qfrag + ((size_t)(NH + cta * 8) * 32 + (blk16 >> 2)) * 128 + (blk16 & 3) * 32 + lane;
    uint4 q[8];
#pragma unroll
    for (int h = 0; h < 8; h++) q[h] = qp[h * 32 * 128];
    const uint32_t buf = stg + (rb & 1) * 4096;
    if (rb >= 2) {
      if (lane == 0) asm volatile("cp.async.bulk.wait_group.read 1;" ::: "memory");
      __syncwarp();
    }
#pragma unroll
    for (int h = 0; h < 8; h++) {
      float n0[4] = {0, 0, 0, 0}, n1[4] = {0, 0, 0, 0}, dn[4] = {0, 0, 0, 0};
      hmma(n0, q[h].x, q[h].y, q[h].z, q[h].w, bf[h][0], bf[h][1]);
      hmma(n1, q[h].x, q[h].y, q[h].z, q[h].w, bf[h][2], bf[h][3]);
      hmma(dn, q[h].x, q[h].y, q[h].z, q[h].w, bf[h][4], bf[h][5]);
      const float d0 = round_bf16(round_bf16(dn[0]) + 1e-6f), d1 = round_bf16(round_bf16(dn[2]) + 1e-6f);
      const uint32_t r0 = pack_bf16(__fdividef(round_bf16(n0[0]), d0), __fdividef(round_bf16(n0[1]), d0));
      const uint32_t r1 = pack_bf16(__fdividef(round_bf16(n0[2]), d1), __fdividef(round_bf16(n0[3]), d1));
      const uint32_t r2 = pack_bf16(__fdividef(round_bf16(n1[0]), d0), __fdividef(round_bf16(n1[1]), d0));
      const uint32_t r3 = pack_bf16(__fdividef(round_bf16(n1[2]), d1), __fdividef(round_bf16(n1[3]), d1));
      const int row = lane & 15;
      const int chunk = (h & 3) * 2 + (lane >> 4);
      const uint32_t addr = buf + (h >> 2) * 2048 + row * 128 + ((chunk ^ (row & 7)) << 4);
      asm volatile("stmatrix.sync.aligned.m8n8.x4.shared.b16 [%0], {%1,%2,%3,%4};" ::"r"(addr), "r"(r0), "r"(r1), "r"(r2), "r"(r3)
                   : "memory");
    }
    fence_proxy_async();
    __syncwarp();
    if (lane == 0) {
      tma_store_2d(mo16, buf, cta * 128, blk16 * 16);
      tma_store_2d(mo16, buf + 2048, cta * 128 + 64, blk16 * 16);
      asm volatile("cp.async.bulk.commit_group;" ::: "memory");
    }
  }
  if (lane == 0) asm volatile("cp.async.bulk.wait_group 0;" ::: "memory");
}

__global__ void __launch_bounds__(512, 1) attn_kernel(const __grid_constant__ CUtensorMap mo16, ExpC ec) {
  extern __shared__ uint8_t smem_raw[];
  const uint32_t sbase = (smem_u32(smem_raw) + 1023) & ~1023u;
  const uint32_t bar = sbase + KV_HEAD_BYTES;
  if (threadIdx.x == 0) { PROF_G(1, 30); PROF_T(1, 0); }
  if (threadIdx.x == 0) {
    for (int i = 0; i < 4; i++) mbar_init(bar + 8 * i, 1);
    fence_barrier_init();
    fence_proxy_async();
  }
  __syncthreads();
  if (blockIdx.x >= 128) {
    linear_attn_cta(smem_raw, sbase, &mo16, blockIdx.x - 128);
    if (threadIdx.x == 0) { PROF_T(1, 5); PROF_G(1, 31); }
    return;
  }
  const int head = blockIdx.x >> 2, qb = blockIdx.x & 3;
  if (threadIdx.x == 0) {
    const uint8_t* img = reinterpret_cast<const uint8_t*>(g_kv) + (size_t)head * KV_HEAD_BYTES;
    for (int i = 0; i < 4; i++) {
      mbar_expect_tx(bar + 8 * i, KV_CHUNK_BYTES);
      bulk_load(sbase + i * KV_CHUNK_BYTES, img + (size_t)i * KV_CHUNK_BYTES, KV_CHUNK_BYTES, bar + 8 * i);
    }
  }
  const int lane = threadIdx.x & 31;
  bool safe_path;
  {
    float4 n = make_float4(0.f, 0.f, 0.f, 0.f);
    if (lane < 16) n = *reinterpret_cast<const float4*>(&g_nrm[(head * 16 + lane) * 4]);
    uint32_t qm = ((lane >> 2) == qb) ? __float_as_uint(n.x) : 0u;
    qm = __reduce_max_sync(0xffffffffu, qm);
    const uint32_t km = __reduce_max_sync(0xffffffffu, __float_as_uint(n.y));
    const uint32_t vm = __reduce_max_sync(0xffffffffu, __float_as_uint(n.z));
    const float b2 = __uint_as_float(qm) * (QSCALE * QSCALE) * __uint_as_float(km) * 1.02f;
    const float vmax = __uint_as_float(vm);
    const bool ok = (b2 <= 21.5f * 21.5f) && (vmax <= 1.0e24f) && (vmax >= 1.0e-18f || vmax == 0.f);
    safe_path = !ok;
  }
  const int wg = threadIdx.x >> 7, warp = (threadIdx.x >> 5) & 3;
  for (int t = 0; t < 2; t++) {
    const int tile64 = qb * 8 + wg * 2 + t;
    const uint4 qf = g_qfrag[(head * 32 + tile64) * 128 + (threadIdx.x & 127)];
    uint32_t r[4];
    if (threadIdx.x == 0) PROF_T(1, 1 + t);
    if (!safe_path) attn_tile<false>(sbase, bar, qf, ec, r);
    else attn_tile<true>(sbase, bar, qf, ec, r);
    store_o(g_o + (size_t)S_LEN * DM, tile64 * 64 + warp * 16, head, lane, r);
  }
  if (threadIdx.x == 0) { PROF_T(1, 5); PROF_G(1, 31); }
}

constexpr int K3_STAGES = 6;
constexpr int K3_STAGE_BYTES = 16384 + 2 * 8192;
constexpr int K3_SMEM = K3_STAGES * K3_STAGE_BYTES + 1024 + 256;

__global__ void __launch_bounds__(288, 1)
out_gemm_kernel(const __grid_constant__ CUtensorMap mo, const __grid_constant__ CUtensorMap mwA,
                const __grid_constant__ CUtensorMap mwB, const __grid_constant__ CUtensorMap mout) {
  extern __shared__ uint8_t smem_raw[];
  const uint32_t sbase = (smem_u32(smem_raw) + 1023) & ~1023u;
  const uint32_t bar_full = sbase + K3_STAGES * K3_STAGE_BYTES;
  const uint32_t bar_empty = bar_full + 8 * K3_STAGES;
  const int branch = blockIdx.x >> 6;
  const int rt = (blockIdx.x & 63) >> 2;
  const int ct = blockIdx.x & 3;
  const int warp = threadIdx.x >> 5;
  if (threadIdx.x == 0) { PROF_G(2, 30); PROF_T(2, 0); }
  if (threadIdx.x == 0) {
    for (int i = 0; i < K3_STAGES; i++) {
      mbar_init(bar_full + 8 * i, 1);
      mbar_init(bar_empty + 8 * i, 2);
    }
    fence_barrier_init();
  }
  __syncthreads();
  if (warp == 8) {
    if ((threadIdx.x & 31) == 0) {
      const CUtensorMap* mw = branch ? &mwB : &mwA;
      for (int kb = 0; kb < 8; kb++) {
        const int s = kb % K3_STAGES;
        if (kb >= K3_STAGES) mbar_wait(bar_empty + 8 * s, ((kb / K3_STAGES) - 1) & 1);
        const uint32_t st = sbase + s * K3_STAGE_BYTES;
        mbar_expect_tx(bar_full + 8 * s, K3_STAGE_BYTES);
        tma_load_2d(st, &mo, kb * 64, branch * S_LEN + rt * 128, bar_full + 8 * s);
        tma_load_2d(st + 16384, mw, ct * 128, kb * 64, bar_full + 8 * s);
        tma_load_2d(st + 16384 + 8192, mw, ct * 128 + 64, kb * 64, bar_full + 8 * s);
      }
    }
  } else {
    const int wg = warp >> 2;
    float acc[64];
    for (int kb = 0; kb < 8; kb++) {
      const int s = kb % K3_STAGES;
      mbar_wait(bar_full + 8 * s, (kb / K3_STAGES) & 1);
      if (threadIdx.x == 0) PROF_T(2, 2 + kb);
      const uint32_t st = sbase + s * K3_STAGE_BYTES;
      const uint64_t dA = mkdesc(st + wg * 8192, 16, 1024, 1);
      const uint64_t dB = mkdesc(st + 16384, 8192, 1024, 1);
      wg_fence();
#pragma unroll
      for (int k = 0; k < 4; k++) wgmma_ss_n128_tb(acc, dA + k * 2, dB + k * 128, (kb | k) != 0);
      wg_commit();
      if (kb > 0) {
        wg_wait<1>();
        if ((threadIdx.x & 127) == 0) mbar_arrive(bar_empty + 8 * ((kb - 1) % K3_STAGES));
      }
    }
    wg_wait<0>();
    fence_regs(acc);
    if (threadIdx.x == 0) PROF_T(2, 10);
    asm volatile("bar.sync 1, 256;" ::: "memory");
    const int lane = threadIdx.x & 31;
    const int rloc = wg * 64 + (warp & 3) * 16 + (lane & 15);
#pragma unroll
    for (int c16 = 0; c16 < 8; c16++) {
      const float* a = &acc[c16 * 8];
      const uint32_t r0 = pack_bf16(a[0], a[1]), r1 = pack_bf16(a[2], a[3]), r2 = pack_bf16(a[4], a[5]), r3 = pack_bf16(a[6], a[7]);
      const int chunk = (c16 & 3) * 2 + (lane >> 4);
      const uint32_t addr = sbase + (c16 >> 2) * 16384 + rloc * 128 + ((chunk ^ (rloc & 7)) << 4);
      asm volatile("stmatrix.sync.aligned.m8n8.x4.shared.b16 [%0], {%1,%2,%3,%4};" ::"r"(addr), "r"(r0), "r"(r1), "r"(r2), "r"(r3)
                   : "memory");
    }
    fence_proxy_async();
    asm volatile("bar.sync 1, 256;" ::: "memory");
    if (threadIdx.x == 0) {
      tma_store_2d(&mout, sbase, branch * DM + ct * 128, rt * 128);
      tma_store_2d(&mout, sbase + 16384, branch * DM + ct * 128 + 64, rt * 128);
      asm volatile("cp.async.bulk.commit_group;" ::: "memory");
      asm volatile("cp.async.bulk.wait_group 0;" ::: "memory");
      PROF_T(2, 12); PROF_G(2, 31);
    }
  }
}

typedef CUresult (*EncodeFn)(CUtensorMap*, CUtensorMapDataType, cuuint32_t, void*, const cuuint64_t*, const cuuint64_t*,
                             const cuuint32_t*, const cuuint32_t*, CUtensorMapInterleave, CUtensorMapSwizzle,
                             CUtensorMapL2promotion, CUtensorMapFloatOOBfill);

void make_map(EncodeFn enc, CUtensorMap* m, const void* ptr, uint64_t inner, uint64_t outer, uint32_t box_inner, uint32_t box_outer) {
  cuuint64_t dims[2] = {inner, outer};
  cuuint64_t strides[1] = {inner * 2};
  cuuint32_t box[2] = {box_inner, box_outer};
  cuuint32_t es[2] = {1, 1};
  enc(m, CU_TENSOR_MAP_DATA_TYPE_BFLOAT16, 2, const_cast<void*>(ptr), dims, strides, box, es, CU_TENSOR_MAP_INTERLEAVE_NONE,
      CU_TENSOR_MAP_SWIZZLE_128B, CU_TENSOR_MAP_L2_PROMOTION_L2_256B, CU_TENSOR_MAP_FLOAT_OOB_FILL_NONE);
}

struct HostState {
  bool init;
  const void* key[7];
  CUtensorMap mxA, mxB, mwA, mwB, mo, mo16, mwoA, mwoB, mout;
};
HostState g_hs;

}

extern "C" void kernel_launch(void* const* d_in, const int* in_sizes, int n_in, void* d_out, int out_size) {
  (void)in_sizes; (void)n_in; (void)out_size;
  HostState& hs = g_hs;
  bool same = hs.init && hs.key[6] == d_out;
  for (int i = 0; i < 6 && same; i++) same = hs.key[i] == d_in[i];
  if (!same) {
    void* fn = nullptr;
    cudaDriverEntryPointQueryResult qr;
    cudaGetDriverEntryPoint("cuTensorMapEncodeTiled", &fn, cudaEnableDefault, &qr);
    EncodeFn enc = (EncodeFn)fn;
    void* go = nullptr;
    cudaGetSymbolAddress(&go, g_o);
    make_map(enc, &hs.mxA, d_in[0], 512, 2048, 64, 128);
    make_map(enc, &hs.mwA, d_in[1], 1536, 512, 64, 64);
    make_map(enc, &hs.mwoA, d_in[2], 512, 512, 64, 64);
    make_map(enc, &hs.mxB, d_in[3], 512, 2048, 64, 128);
    make_map(enc, &hs.mwB, d_in[4], 1536, 512, 64, 64);
    make_map(enc, &hs.mwoB, d_in[5], 512, 512, 64, 64);
    make_map(enc, &hs.mo, go, 512, 4096, 64, 128);
    make_map(enc, &hs.mo16, go, 512, 4096, 64, 16);
    make_map(enc, &hs.mout, d_out, 1024, 2048, 64, 128);
    cudaFuncSetAttribute(qkv_gemm_kernel, cudaFuncAttributeMaxDynamicSharedMemorySize, K1_SMEM);
    cudaFuncSetAttribute(attn_kernel, cudaFuncAttributeMaxDynamicSharedMemorySize, K2_SMEM);
    cudaFuncSetAttribute(out_gemm_kernel, cudaFuncAttributeMaxDynamicSharedMemorySize, K3_SMEM);
    for (int i = 0; i < 6; i++) hs.key[i] = d_in[i];
    hs.key[6] = d_out;
    hs.init = true;
  }
  cudaStream_t st = cudaStreamPerThread;
  {
    cudaLaunchConfig_t cfg = {};
    cfg.gridDim = dim3(128);
    cfg.blockDim = dim3(384);
    cfg.dynamicSmemBytes = K1_SMEM;
    cfg.stream = st;
    cudaLaunchAttribute at[1];
    at[0].id = cudaLaunchAttributeClusterDimension;
    at[0].val.clusterDim.x = 2;
    at[0].val.clusterDim.y = 1;
    at[0].val.clusterDim.z = 1;
    cfg.attrs = at;
    cfg.numAttrs = 1;
    cudaLaunchKernelEx(&cfg, qkv_gemm_kernel, hs.mxA, hs.mxB, hs.mwA, hs.mwB);
  }
  ExpC ec{0x3C003C00u, 0x00070000u, 7u};
  attn_kernel<<<132, 512, K2_SMEM, st>>>(hs.mo16, ec);
  out_gemm_kernel<<<128, 288, K3_SMEM, st>>>(hs.mo, hs.mwoA, hs.mwoB, hs.mout);
}
```

```cpp
#include <cuda_runtime.h>
#include <cuda_bf16.h>
#include <cuda.h>
#include <stdint.h>

namespace {

constexpr int S_LEN = 2048;
constexpr int DM = 512;
constexpr int NH = 32;

constexpr int KV_K_BYTES = 65536;
constexpr int KV_HEAD_BYTES = KV_K_BYTES + 98304;
__device__ uint4 g_qfrag[2 * NH * 32 * 128];
__device__ uint4 g_kv[NH * KV_HEAD_BYTES / 16];
__device__ float g_kvpart[16 * NH * 384];
__device__ float g_nrm[NH * 16 * 4];
__device__ __nv_bfloat16 g_o[2 * S_LEN * DM];

#define PROF_T(k, i) do {} while (0)
#define PROF_G(k, i) do {} while (0)
__device__ __forceinline__ uint32_t smem_u32(const void* p) { return (uint32_t)__cvta_generic_to_shared(p); }
__device__ __forceinline__ void mbar_init(uint32_t bar, int cnt) {
  asm volatile("mbarrier.init.shared::cta.b64 [%0], %1;" ::"r"(bar), "r"(cnt) : "memory");
}
__device__ __forceinline__ void mbar_expect_tx(uint32_t bar, uint32_t bytes) {
  asm volatile("mbarrier.arrive.expect_tx.shared::cta.b64 _, [%0], %1;" ::"r"(bar), "r"(bytes) : "memory");
}
__device__ __forceinline__ void mbar_arrive(uint32_t bar) {
  asm volatile("mbarrier.arrive.shared::cta.b64 _, [%0];" ::"r"(bar) : "memory");
}
__device__ __forceinline__ void mbar_arrive_cluster(uint32_t bar, uint32_t cta) {
  asm volatile(
      "{\n.reg .b32 ra;\nmapa.shared::cluster.u32 ra, %0, %1;\n"
      "mbarrier.arrive.shared::cluster.b64 _, [ra];\n}" ::"r"(bar), "r"(cta) : "memory");
}
__device__ __forceinline__ void mbar_wait(uint32_t bar, uint32_t parity) {
  asm volatile(
      "{\n.reg .pred p;\n"
      "WAIT_LOOP:\n"
      "mbarrier.try_wait.parity.shared::cta.b64 p, [%0], %1, 0x989680;\n"
      "@p bra WAIT_DONE;\n"
      "bra WAIT_LOOP;\n"
      "WAIT_DONE:\n}" ::"r"(bar), "r"(parity) : "memory");
}
__device__ __forceinline__ void mbar_wait_cluster(uint32_t bar, uint32_t parity) {
  asm volatile(
      "{\n.reg .pred p;\n"
      "WAIT_LOOP:\n"
      "mbarrier.try_wait.parity.acquire.cluster.shared::cta.b64 p, [%0], %1, 0x989680;\n"
      "@p bra WAIT_DONE;\n"
      "bra WAIT_LOOP;\n"
      "WAIT_DONE:\n}" ::"r"(bar), "r"(parity) : "memory");
}
__device__ __forceinline__ void fence_barrier_init() {
  asm volatile("fence.mbarrier_init.release.cluster;" ::: "memory");
}
__device__ __forceinline__ void fence_proxy_async() { asm volatile("fence.proxy.async.shared::cta;" ::: "memory"); }
__device__ __forceinline__ void cluster_sync_relaxed() {
  asm volatile("barrier.cluster.arrive.relaxed.aligned;\nbarrier.cluster.wait.aligned;" ::: "memory");
}
__device__ __forceinline__ void tma_load_2d(uint32_t dst, const CUtensorMap* m, int x, int y, uint32_t bar) {
  asm volatile(
      "cp.async.bulk.tensor.2d.shared::cluster.global.mbarrier::complete_tx::bytes [%0], [%1, {%3, %4}], [%2];" ::"r"(dst),
      "l"(m), "r"(bar), "r"(x), "r"(y)
      : "memory");
}
__device__ __forceinline__ void tma_load_2d_mc(uint32_t dst, const CUtensorMap* m, int x, int y, uint32_t bar, uint16_t mask) {
  asm volatile(
      "cp.async.bulk.tensor.2d.shared::cluster.global.mbarrier::complete_tx::bytes.multicast::cluster [%0], [%1, {%3, %4}], "
      "[%2], %5;" ::"r"(dst),
      "l"(m), "r"(bar), "r"(x), "r"(y), "h"(mask)
      : "memory");
}
__device__ __forceinline__ void tma_store_2d(const CUtensorMap* m, uint32_t src, int x, int y) {
  asm volatile("cp.async.bulk.tensor.2d.global.shared::cta.bulk_group [%0, {%2, %3}], [%1];" ::"l"(m), "r"(src), "r"(x),
               "r"(y)
               : "memory");
}
__device__ __forceinline__ void bulk_load(uint32_t dst, const void* src, uint32_t bytes, uint32_t bar) {
  asm volatile("cp.async.bulk.shared::cluster.global.mbarrier::complete_tx::bytes [%0], [%1], %2, [%3];" ::"r"(dst),
               "l"(src), "r"(bytes), "r"(bar)
               : "memory");
}
__device__ __forceinline__ void wg_fence() { asm volatile("wgmma.fence.sync.aligned;" ::: "memory"); }
__device__ __forceinline__ void wg_commit() { asm volatile("wgmma.commit_group.sync.aligned;" ::: "memory"); }
template <int N>
__device__ __forceinline__ void wg_wait() {
  asm volatile("wgmma.wait_group.sync.aligned %0;" ::"n"(N) : "memory");
}
template <int M>
__device__ __forceinline__ void fence_regs(float (&r)[M]) {
#pragma unroll
  for (int i = 0; i < M; i++) asm volatile("" : "+f"(r[i])::"memory");
}
__device__ __forceinline__ uint64_t mkdesc(uint32_t addr, uint32_t lbo, uint32_t sbo, uint32_t layout) {
  return (uint64_t)((addr & 0x3FFFF) >> 4) | ((uint64_t)(lbo >> 4) << 16) | ((uint64_t)(sbo >> 4) << 32) |
         ((uint64_t)layout << 62);
}
__device__ __forceinline__ uint32_t pack_bf16(float lo, float hi) {
  uint32_t r;
  asm("cvt.rn.bf16x2.f32 %0, %1, %2;" : "=r"(r) : "f"(hi), "f"(lo));
  return r;
}
__device__ __forceinline__ float bf_lo(uint32_t v) { return __uint_as_float(v << 16); }
__device__ __forceinline__ float bf_hi(uint32_t v) { return __uint_as_float(v & 0xFFFF0000u); }
__device__ __forceinline__ float round_bf16(float x) { return bf_lo(pack_bf16(x, 0.f)); }
__device__ __forceinline__ float ex2f(float x) {
  float y;
  asm("ex2.approx.ftz.f32 %0, %1;" : "=f"(y) : "f"(x));
  return y;
}

__device__ __forceinline__ void wgmma_rs_n24_tb(float (&d)[12], uint32_t a0, uint32_t a1, uint32_t a2, uint32_t a3, uint64_t descB, int scaleD) {
  asm volatile("{\n.reg .pred p;\nsetp.ne.b32 p, %17, 0;\n"
    "wgmma.mma_async.sync.aligned.m64n24k16.f32.bf16.bf16 "
    "{%0, %1, %2, %3, %4, %5, %6, %7, %8, %9, %10, %11}, {%12, %13, %14, %15}, %16, p, 1, 1, 1;\n}\n"
    : "+f"(d[0]), "+f"(d[1]), "+f"(d[2]), "+f"(d[3]), "+f"(d[4]), "+f"(d[5]), "+f"(d[6]), "+f"(d[7]),
      "+f"(d[8]), "+f"(d[9]), "+f"(d[10]), "+f"(d[11])
    : "r"(a0), "r"(a1), "r"(a2), "r"(a3), "l"(descB), "r"(scaleD));
}
__device__ __forceinline__ void wgmma_rs_n64_z(float (&d)[32], uint32_t a0, uint32_t a1, uint32_t a2, uint32_t a3, uint64_t descB) {
  asm volatile("{\n.reg .pred p;\nsetp.ne.b32 p, %37, 0;\n"
    "wgmma.mma_async.sync.aligned.m64n64k16.f32.bf16.bf16 "
    "{%0, %1, %2, %3, %4, %5, %6, %7, %8, %9, %10, %11, %12, %13, %14, %15, %16, %17, %18, %19, %20, %21, %22, %23, %24, %25, %26, %27, %28, %29, %30, %31}, {%32, %33, %34, %35}, %36, p, 1, 1, 0;\n}\n"
    : "=f"(d[0]), "=f"(d[1]), "=f"(d[2]), "=f"(d[3]), "=f"(d[4]), "=f"(d[5]), "=f"(d[6]), "=f"(d[7]),
      "=f"(d[8]), "=f"(d[9]), "=f"(d[10]), "=f"(d[11]), "=f"(d[12]), "=f"(d[13]), "=f"(d[14]), "=f"(d[15]),
      "=f"(d[16]), "=f"(d[17]), "=f"(d[18]), "=f"(d[19]), "=f"(d[20]), "=f"(d[21]), "=f"(d[22]), "=f"(d[23]),
      "=f"(d[24]), "=f"(d[25]), "=f"(d[26]), "=f"(d[27]), "=f"(d[28]), "=f"(d[29]), "=f"(d[30]), "=f"(d[31])
    : "r"(a0), "r"(a1), "r"(a2), "r"(a3), "l"(descB), "n"(0));
}
__device__ __forceinline__ void wgmma_ss_n128_tb(float (&d)[64], uint64_t descA, uint64_t descB, int scaleD) {
  asm volatile("{\n.reg .pred p;\nsetp.ne.b32 p, %66, 0;\n"
    "wgmma.mma_async.sync.aligned.m64n128k16.f32.bf16.bf16 "
    "{%0, %1, %2, %3, %4, %5, %6, %7, %8, %9, %10, %11, %12, %13, %14, %15, %16, %17, %18, %19, %20, %21, %22, %23, %24, %25, %26, %27, %28, %29, %30, %31, %32, %33, %34, %35, %36, %37, %38, %39, %40, %41, %42, %43, %44, %45, %46, %47, %48, %49, %50, %51, %52, %53, %54, %55, %56, %57, %58, %59, %60, %61, %62, %63}, %64, %65, p, 1, 1, 0, 1;\n}\n"
    : "+f"(d[0]), "+f"(d[1]), "+f"(d[2]), "+f"(d[3]), "+f"(d[4]), "+f"(d[5]), "+f"(d[6]), "+f"(d[7]),
      "+f"(d[8]), "+f"(d[9]), "+f"(d[10]), "+f"(d[11]), "+f"(d[12]), "+f"(d[13]), "+f"(d[14]), "+f"(d[15]),
      "+f"(d[16]), "+f"(d[17]), "+f"(d[18]), "+f"(d[19]), "+f"(d[20]), "+f"(d[21]), "+f"(d[22]), "+f"(d[23]),
      "+f"(d[24]), "+f"(d[25]), "+f"(d[26]), "+f"(d[27]), "+f"(d[28]), "+f"(d[29]), "+f"(d[30]), "+f"(d[31]),
      "+f"(d[32]), "+f"(d[33]), "+f"(d[34]), "+f"(d[35]), "+f"(d[36]), "+f"(d[37]), "+f"(d[38]), "+f"(d[39]),
      "+f"(d[40]), "+f"(d[41]), "+f"(d[42]), "+f"(d[43]), "+f"(d[44]), "+f"(d[45]), "+f"(d[46]), "+f"(d[47]),
      "+f"(d[48]), "+f"(d[49]), "+f"(d[50]), "+f"(d[51]), "+f"(d[52]), "+f"(d[53]), "+f"(d[54]), "+f"(d[55]),
      "+f"(d[56]), "+f"(d[57]), "+f"(d[58]), "+f"(d[59]), "+f"(d[60]), "+f"(d[61]), "+f"(d[62]), "+f"(d[63])
    : "l"(descA), "l"(descB), "r"(scaleD));
}
__device__ __forceinline__ void wgmma_ss_n192_tb(float (&d)[96], uint64_t descA, uint64_t descB, int scaleD) {
  asm volatile("{\n.reg .pred p;\nsetp.ne.b32 p, %98, 0;\n"
    "wgmma.mma_async.sync.aligned.m64n192k16.f32.bf16.bf16 "
    "{%0, %1, %2, %3, %4, %5, %6, %7, %8, %9, %10, %11, %12, %13, %14, %15, %16, %17, %18, %19, %20, %21, %22, %23, %24, %25, %26, %27, %28, %29, %30, %31, %32, %33, %34, %35, %36, %37, %38, %39, %40, %41, %42, %43, %44, %45, %46, %47, %48, %49, %50, %51, %52, %53, %54, %55, %56, %57, %58, %59, %60, %61, %62, %63, %64, %65, %66, %67, %68, %69, %70, %71, %72, %73, %74, %75, %76, %77, %78, %79, %80, %81, %82, %83, %84, %85, %86, %87, %88, %89, %90, %91, %92, %93, %94, %95}, %96, %97, p, 1, 1, 0, 1;\n}\n"
    : "+f"(d[0]), "+f"(d[1]), "+f"(d[2]), "+f"(d[3]), "+f"(d[4]), "+f"(d[5]), "+f"(d[6]), "+f"(d[7]),
      "+f"(d[8]), "+f"(d[9]), "+f"(d[10]), "+f"(d[11]), "+f"(d[12]), "+f"(d[13]), "+f"(d[14]), "+f"(d[15]),
      "+f"(d[16]), "+f"(d[17]), "+f"(d[18]), "+f"(d[19]), "+f"(d[20]), "+f"(d[21]), "+f"(d[22]), "+f"(d[23]),
      "+f"(d[24]), "+f"(d[25]), "+f"(d[26]), "+f"(d[27]), "+f"(d[28]), "+f"(d[29]), "+f"(d[30]), "+f"(d[31]),
      "+f"(d[32]), "+f"(d[33]), "+f"(d[34]), "+f"(d[35]), "+f"(d[36]), "+f"(d[37]), "+f"(d[38]), "+f"(d[39]),
      "+f"(d[40]), "+f"(d[41]), "+f"(d[42]), "+f"(d[43]), "+f"(d[44]), "+f"(d[45]), "+f"(d[46]), "+f"(d[47]),
      "+f"(d[48]), "+f"(d[49]), "+f"(d[50]), "+f"(d[51]), "+f"(d[52]), "+f"(d[53]), "+f"(d[54]), "+f"(d[55]),
      "+f"(d[56]), "+f"(d[57]), "+f"(d[58]), "+f"(d[59]), "+f"(d[60]), "+f"(d[61]), "+f"(d[62]), "+f"(d[63]),
      "+f"(d[64]), "+f"(d[65]), "+f"(d[66]), "+f"(d[67]), "+f"(d[68]), "+f"(d[69]), "+f"(d[70]), "+f"(d[71]),
      "+f"(d[72]), "+f"(d[73]), "+f"(d[74]), "+f"(d[75]), "+f"(d[76]), "+f"(d[77]), "+f"(d[78]), "+f"(d[79]),
      "+f"(d[80]), "+f"(d[81]), "+f"(d[82]), "+f"(d[83]), "+f"(d[84]), "+f"(d[85]), "+f"(d[86]), "+f"(d[87]),
      "+f"(d[88]), "+f"(d[89]), "+f"(d[90]), "+f"(d[91]), "+f"(d[92]), "+f"(d[93]), "+f"(d[94]), "+f"(d[95])
    : "l"(descA), "l"(descB), "r"(scaleD));
}

__device__ __forceinline__ void ldsm4t(uint32_t (&b)[4], uint32_t addr) {
  asm volatile("ldmatrix.sync.aligned.m8n8.x4.trans.shared.b16 {%0,%1,%2,%3}, [%4];"
               : "=r"(b[0]), "=r"(b[1]), "=r"(b[2]), "=r"(b[3])
               : "r"(addr));
}
__device__ __forceinline__ void hmma(float (&c)[4], uint32_t a0, uint32_t a1, uint32_t a2, uint32_t a3, uint32_t b0, uint32_t b1) {
  asm("mma.sync.aligned.m16n8k16.row.col.f32.bf16.bf16.f32 {%0,%1,%2,%3}, {%4,%5,%6,%7}, {%8,%9}, {%0,%1,%2,%3};"
      : "+f"(c[0]), "+f"(c[1]), "+f"(c[2]), "+f"(c[3])
      : "r"(a0), "r"(a1), "r"(a2), "r"(a3), "r"(b0), "r"(b1));
}

__device__ __forceinline__ uint32_t movm(uint32_t a) {
  uint32_t d;
  asm volatile("movmatrix.sync.aligned.m8n8.trans.b16 %0, %1;" : "=r"(d) : "r"(a));
  return d;
}

constexpr int K1_STAGES = 3;
constexpr int K1_STAGE_BYTES = 16384 + 6 * 8192;
constexpr int K1_SMEM = K1_STAGES * K1_STAGE_BYTES + 1024 + 256;
constexpr float QSCALE = 0.25f * 1.4426950408889634f;

__device__ __forceinline__ float phi_fn(float acc) {
  float t = round_bf16(acc);
  float a = round_bf16(t + 1.0f);
  float e = round_bf16(ex2f(t * 1.4426950408889634f));
  float r = t > 0.f ? a : e;
  return r + 1e-6f;
}

__global__ void __launch_bounds__(384, 1)
qkv_gemm_kernel(const __grid_constant__ CUtensorMap mxA, const __grid_constant__ CUtensorMap mxB,
                const __grid_constant__ CUtensorMap mwA, const __grid_constant__ CUtensorMap mwB) {
  extern __shared__ uint8_t smem_raw[];
  const uint32_t sbase = (smem_u32(smem_raw) + 1023) & ~1023u;
  const uint32_t bar_full = sbase + K1_STAGES * K1_STAGE_BYTES;
  const uint32_t bar_empty = bar_full + 8 * K1_STAGES;
  __shared__ uint32_t s_red[24];

  const int rank = blockIdx.x & 1;
  const int pair = blockIdx.x >> 1;
  const int branch = pair >> 5;
  const int rp = (pair & 31) >> 2;
  const int cp = pair & 3;
  const int rt = rp * 2 + rank;
  const int warp = threadIdx.x >> 5;
  if (threadIdx.x == 0) { PROF_G(0, 30); PROF_T(0, 0); }

  if (threadIdx.x == 0) {
    for (int i = 0; i < K1_STAGES; i++) {
      mbar_init(bar_full + 8 * i, 1);
      mbar_init(bar_empty + 8 * i, 4);
    }
    fence_barrier_init();
  }
  if (threadIdx.x < 24) s_red[threadIdx.x] = 0;
  __syncthreads();
  cluster_sync_relaxed();
  if (threadIdx.x == 0) PROF_T(0, 1);

  if (warp >= 8) {
    asm volatile("setmaxnreg.dec.sync.aligned.u32 40;");
    if (threadIdx.x == 256) {
      const CUtensorMap* mx = branch ? &mxA : &mxB;
      const CUtensorMap* mw = branch ? &mwA : &mwB;
      const int h0 = cp * 8 + rank * 4;
      for (int kb = 0; kb < 8; kb++) {
        const int s = kb % K1_STAGES;
        if (kb >= K1_STAGES) mbar_wait(bar_empty + 8 * s, ((kb / K1_STAGES) - 1) & 1);
        const uint32_t st = sbase + s * K1_STAGE_BYTES;
        mbar_expect_tx(bar_full + 8 * s, K1_STAGE_BYTES);
        tma_load_2d(st, mx, kb * 64, rt * 128, bar_full + 8 * s);
#pragma unroll
        for (int p = 0; p < 3; p++)
          tma_load_2d_mc(st + 16384 + (rank * 3 + p) * 8192, mw, p * 512 + h0 * 16, kb * 64, bar_full + 8 * s, (uint16_t)3);
      }
    }
    __syncwarp();
    cluster_sync_relaxed();
  } else {
    asm volatile("setmaxnreg.inc.sync.aligned.u32 232;");
    const int wg = warp >> 2;
    float acc0[96], acc1[96];
    for (int kb = 0; kb < 8; kb++) {
      const int s = kb % K1_STAGES;
      mbar_wait(bar_full + 8 * s, (kb / K1_STAGES) & 1);
      if (threadIdx.x == 0) PROF_T(0, 2 + kb);
      const uint32_t st = sbase + s * K1_STAGE_BYTES;
      const uint64_t dA = mkdesc(st + wg * 8192, 16, 1024, 1);
      const uint64_t dB = mkdesc(st + 16384, 8192, 1024, 1);
      wg_fence();
#pragma unroll
      for (int k = 0; k < 4; k++) {
        wgmma_ss_n192_tb(acc0, dA + k * 2, dB + k * 128, (kb | k) != 0);
        wgmma_ss_n192_tb(acc1, dA + k * 2, dB + k * 128 + 3 * 512, (kb | k) != 0);
      }
      wg_commit();
      if (kb > 0) {
        wg_wait<1>();
        if ((threadIdx.x & 127) == 0) {
          const int sp = (kb - 1) % K1_STAGES;
          mbar_arrive_cluster(bar_empty + 8 * sp, 0);
          mbar_arrive_cluster(bar_empty + 8 * sp, 1);
        }
      }
    }
    wg_wait<0>();
    fence_regs(acc0);
    fence_regs(acc1);
    if (threadIdx.x == 0) PROF_T(0, 10);

    const int lane = threadIdx.x & 31;
    const int tid = threadIdx.x & 127;
    const int row0 = rt * 128 + wg * 64 + (warp & 3) * 16;
    const int tile64 = rt * 2 + wg;
    uint4* qf = g_qfrag + ((size_t)(branch * NH + cp * 8) * 32 + tile64) * 128 + tid;
    if (branch == 0) {
      uint32_t* img = reinterpret_cast<uint32_t*>(reinterpret_cast<uint8_t*>(g_kv) + (size_t)(cp * 8) * KV_HEAD_BYTES);
      const int grp = row0 >> 3;
      uint32_t* kp = img + grp * 64 + lane;
      uint32_t* vp = img + KV_K_BYTES / 4 + grp * 96 + lane;
      float vmax = 0.f;
#pragma unroll
      for (int j = 0; j < 2; j++) {
        float(&acc)[96] = j ? acc1 : acc0;
#pragma unroll
        for (int hh = 0; hh < 4; hh++) {
          const int h = j * 4 + hh;
          const float* a = &acc[hh * 8];
          const float* k = &acc[32 + hh * 8];
          const float* v = &acc[64 + hh * 8];
          qf[h * 32 * 128] = make_uint4(pack_bf16(a[0] * QSCALE, a[1] * QSCALE), pack_bf16(a[2] * QSCALE, a[3] * QSCALE),
                                        pack_bf16(a[4] * QSCALE, a[5] * QSCALE), pack_bf16(a[6] * QSCALE, a[7] * QSCALE));
          uint32_t* kh = kp + h * (KV_HEAD_BYTES / 4);
          kh[0] = pack_bf16(k[0], k[1]);
          kh[64] = pack_bf16(k[2], k[3]);
          kh[32] = pack_bf16(k[4], k[5]);
          kh[96] = pack_bf16(k[6], k[7]);
          uint32_t* vh = vp + h * (KV_HEAD_BYTES / 4);
          vh[0] = pack_bf16(v[0], v[1]);
          vh[96] = pack_bf16(v[2], v[3]);
          vh[32] = pack_bf16(v[4], v[5]);
          vh[128] = pack_bf16(v[6], v[7]);
          vh[64] = 0x3F803F80u;
          vh[160] = 0x3F803F80u;
          float q0 = a[0] * a[0] + a[1] * a[1] + a[4] * a[4] + a[5] * a[5];
          float q1 = a[2] * a[2] + a[3] * a[3] + a[6] * a[6] + a[7] * a[7];
          float k0 = k[0] * k[0] + k[1] * k[1] + k[4] * k[4] + k[5] * k[5];
          float k1 = k[2] * k[2] + k[3] * k[3] + k[6] * k[6] + k[7] * k[7];
#pragma unroll
          for (int o = 1; o <= 2; o <<= 1) {
            q0 += __shfl_xor_sync(0xffffffffu, q0, o);
            q1 += __shfl_xor_sync(0xffffffffu, q1, o);
            k0 += __shfl_xor_sync(0xffffffffu, k0, o);
            k1 += __shfl_xor_sync(0xffffffffu, k1, o);
          }
          const uint32_t qm = __reduce_max_sync(0xffffffffu, max(__float_as_uint(q0) & 0x7FFFFFFFu, __float_as_uint(q1) & 0x7FFFFFFFu));
          const uint32_t km = __reduce_max_sync(0xffffffffu, max(__float_as_uint(k0) & 0x7FFFFFFFu, __float_as_uint(k1) & 0x7FFFFFFFu));
          if (lane == 0) {
            atomicMax(&s_red[h * 2 + 0], qm);
            atomicMax(&s_red[h * 2 + 1], km);
          }
#pragma unroll
          for (int i = 0; i < 8; i++) vmax = fmaxf(vmax, fabsf(v[i]) + (v[i] != v[i] ? INFINITY : 0.f));
        }
      }
      const uint32_t vm = __reduce_max_sync(0xffffffffu, __float_as_uint(vmax) & 0x7FFFFFFFu);
      if (lane == 0) atomicMax(&s_red[16], vm);
      asm volatile("bar.sync 1, 256;" ::: "memory");
      if (threadIdx.x < 8) {
        *reinterpret_cast<float4*>(&g_nrm[((cp * 8 + threadIdx.x) * 16 + rt) * 4]) =
            make_float4(__uint_as_float(s_red[threadIdx.x * 2]), __uint_as_float(s_red[threadIdx.x * 2 + 1]), __uint_as_float(s_red[16]), 0.f);
      }
    } else {
      asm volatile("bar.sync 1, 256;" ::: "memory");
      float* slot = reinterpret_cast<float*>(smem_raw + (sbase - smem_u32(smem_raw)));
      float* myslot = slot + warp * 3072 + lane;
#pragma unroll
      for (int j = 0; j < 2; j++) {
        float(&acc)[96] = j ? acc1 : acc0;
#pragma unroll
        for (int hh = 0; hh < 4; hh++) {
          const int h = j * 4 + hh;
          const float* a = &acc[hh * 8];
          const float* k = &acc[32 + hh * 8];
          const float* v = &acc[64 + hh * 8];
          qf[h * 32 * 128] = make_uint4(pack_bf16(phi_fn(a[0]), phi_fn(a[1])), pack_bf16(phi_fn(a[2]), phi_fn(a[3])),
                                        pack_bf16(phi_fn(a[4]), phi_fn(a[5])), pack_bf16(phi_fn(a[6]), phi_fn(a[7])));
          const uint32_t a0 = movm(pack_bf16(phi_fn(k[0]), phi_fn(k[1])));
          const uint32_t a2 = movm(pack_bf16(phi_fn(k[2]), phi_fn(k[3])));
          const uint32_t a1 = movm(pack_bf16(phi_fn(k[4]), phi_fn(k[5])));
          const uint32_t a3 = movm(pack_bf16(phi_fn(k[6]), phi_fn(k[7])));
          const uint32_t b0 = movm(pack_bf16(v[0], v[1]));
          const uint32_t b1 = movm(pack_bf16(v[2], v[3]));
          const uint32_t b2 = movm(pack_bf16(v[4], v[5]));
          const uint32_t b3 = movm(pack_bf16(v[6], v[7]));
          float c0[4] = {0, 0, 0, 0}, c1[4] = {0, 0, 0, 0}, c2[4] = {0, 0, 0, 0};
          hmma(c0, a0, a1, a2, a3, b0, b1);
          hmma(c1, a0, a1, a2, a3, b2, b3);
          hmma(c2, a0, a1, a2, a3, 0x3F803F80u, 0x3F803F80u);
#pragma unroll
          for (int i = 0; i < 4; i++) {
            myslot[h * 384 + i * 32] = c0[i];
            myslot[h * 384 + (4 + i) * 32] = c1[i];
            myslot[h * 384 + (8 + i) * 32] = c2[i];
          }
        }
      }
      asm volatile("bar.sync 1, 256;" ::: "memory");
      float* dst = g_kvpart + ((size_t)rt * NH + cp * 8) * 384;
#pragma unroll
      for (int i = 0; i < 12; i++) {
        const int o = threadIdx.x + i * 256;
        float sum = 0.f;
#pragma unroll
        for (int w = 0; w < 8; w++) sum += slot[w * 3072 + o];
        dst[o] = sum;
      }
    }
    if (threadIdx.x == 0) PROF_T(0, 11);
    __syncwarp();
    cluster_sync_relaxed();
    if (threadIdx.x == 0) { PROF_T(0, 12); PROF_G(0, 31); }
  }
}

constexpr int K2_SMEM = KV_HEAD_BYTES + 1024 + 256;

struct ExpC {
  uint32_t k3c00, kmask, seven, c3;
};
__device__ __forceinline__ uint32_t hfma2(uint32_t a, uint32_t b, uint32_t c) {
  uint32_t r;
  asm("fma.rn.f16x2 %0, %1, %2, %3;" : "=r"(r) : "r"(a), "r"(b), "r"(c));
  return r;
}
__device__ __forceinline__ uint32_t exp2_poly_pair(float t0, float t1, const ExpC& c) {
  uint32_t u;
  asm("prmt.b32 %0, %1, %2, 0x5410;" : "=r"(u) : "r"(__float_as_uint(t0)), "r"(__float_as_uint(t1)));
  uint32_t m;
  asm("lop3.b32 %0, %1, 0x03FF03FF, %2, 0xEA;" : "=r"(m) : "r"(u), "r"(c.k3c00));
  uint32_t p = hfma2(m, c.c3, 0x9fe09fe0u);
  p = hfma2(p, m, 0x37a137a1u);
  p = hfma2(p, m, 0x4ab94abau);
  uint32_t mu;
  asm("lop3.b32 %0, %1, 0xFC00FC00, %2, 0xEA;" : "=r"(mu) : "r"(u), "r"(c.kmask));
  uint32_t r;
  asm("{.reg .b32 t; shf.r.wrap.b32 t, %1, %2, 3; add.u32 %0, t, %3;}" : "=r"(r) : "r"(mu), "r"(c.seven), "r"(p));
  return r;
}
__device__ __forceinline__ float gadd(float x, float M, uint32_t g) {
  float r = x;
  asm("{.reg .pred p; setp.ne.b32 p, %2, -1; @p add.f32 %0, %0, %1;}" : "+f"(r) : "f"(M), "r"(g));
  return r;
}
__device__ __forceinline__ float gex2(float x, uint32_t g) {
  float r = x;
  asm("{.reg .pred p; setp.ne.b32 p, %1, -1; @p ex2.approx.ftz.f32 %0, %0;}" : "+f"(r) : "r"(g));
  return r;
}
template <int NPOLY, int NPAIR, int CH, int D>
__device__ __forceinline__ void exp_tile(const float (&s)[2 * NPAIR], uint32_t (&p)[NPAIR], const ExpC& c) {
#pragma unroll
  for (int i = 0; i < NPAIR; i++) {
    const bool isPoly = ((i + 1) * NPOLY / 32) != (i * NPOLY / 32);
    const int ch = i / CH;
    const bool gated = ch >= D;
    int gi = (ch - D) * CH + CH - 1;
    if (gated) {
      while (gi > (ch - D) * CH && !(((gi + 1) * NPOLY / 32) != (gi * NPOLY / 32))) gi--;
    }
    const uint32_t g = gated ? p[gi] : 0;
    if (!isPoly) {
      if (gated) p[i] = pack_bf16(gex2(s[2 * i], g), gex2(s[2 * i + 1], g));
      else p[i] = pack_bf16(ex2f(s[2 * i]), ex2f(s[2 * i + 1]));
    } else {
      if (gated) p[i] = exp2_poly_pair(gadd(s[2 * i], 12329.f, g), gadd(s[2 * i + 1], 12329.f, g), c);
      else p[i] = exp2_poly_pair(s[2 * i] + 12329.f, s[2 * i + 1] + 12329.f, c);
    }
  }
}

__device__ __forceinline__ void store_o(__nv_bfloat16* o, int row0, int head, int lane, const uint32_t (&r)[4]) {
  const int g = lane >> 2, t = lane & 3;
  uint32_t* p0 = reinterpret_cast<uint32_t*>(o + (size_t)(row0 + g) * DM + head * 16) + t;
  uint32_t* p1 = reinterpret_cast<uint32_t*>(o + (size_t)(row0 + g + 8) * DM + head * 16) + t;
  p0[0] = r[0];
  p1[0] = r[1];
  p0[4] = r[2];
  p1[4] = r[3];
}

template <bool SAFE>
__device__ __forceinline__ void attn_step(float (&s)[32], float (&o)[12], float& m0, float& m1, const uint4& qf, uint64_t dKn,
                                          uint64_t dV, const ExpC& ec) {
  uint32_t p[16];
  wg_wait<0>();
  fence_regs(s);
  if (!SAFE) {
    exp_tile<16, 16, 4, 2>(s, p, ec);
  } else {
    fence_regs(o);
    float x0 = s[0], x1 = s[2];
#pragma unroll
    for (int i = 0; i < 8; i++) {
      x0 = fmaxf(x0, fmaxf(s[4 * i], s[4 * i + 1]));
      x1 = fmaxf(x1, fmaxf(s[4 * i + 2], s[4 * i + 3]));
    }
    x0 = fmaxf(x0, __shfl_xor_sync(0xffffffffu, x0, 1));
    x1 = fmaxf(x1, __shfl_xor_sync(0xffffffffu, x1, 1));
    x0 = fmaxf(x0, __shfl_xor_sync(0xffffffffu, x0, 2));
    x1 = fmaxf(x1, __shfl_xor_sync(0xffffffffu, x1, 2));
    const float n0 = fmaxf(m0, x0), n1 = fmaxf(m1, x1);
    const float c0 = ex2f(m0 - n0), c1 = ex2f(m1 - n1);
    m0 = n0;
    m1 = n1;
#pragma unroll
    for (int i = 0; i < 3; i++) {
      o[4 * i] *= c0;
      o[4 * i + 1] *= c0;
      o[4 * i + 2] *= c1;
      o[4 * i + 3] *= c1;
    }
#pragma unroll
    for (int i = 0; i < 8; i++) {
      p[2 * i] = pack_bf16(ex2f(s[4 * i] - n0), ex2f(s[4 * i + 1] - n0));
      p[2 * i + 1] = pack_bf16(ex2f(s[4 * i + 2] - n1), ex2f(s[4 * i + 3] - n1));
    }
  }
  wg_fence();
  wgmma_rs_n64_z(s, qf.x, qf.y, qf.z, qf.w, dKn);
#pragma unroll
  for (int k = 0; k < 4; k++) wgmma_rs_n24_tb(o, p[4 * k], p[4 * k + 1], p[4 * k + 2], p[4 * k + 3], dV + k * 48, 1);
  wg_commit();
}

template <bool SAFE>
__device__ __forceinline__ void attn_tile(uint64_t dK, uint64_t dV, uint32_t bar, const uint4 qf, const ExpC& ec, uint32_t (&outp)[4]) {
  float s[32];
  float o[12];
#pragma unroll
  for (int i = 0; i < 12; i++) asm volatile("mov.f32 %0, 0f00000000;" : "=f"(o[i]));
  float m0 = -INFINITY, m1 = -INFINITY;
  mbar_wait(bar, 0);
  wg_fence();
  wgmma_rs_n64_z(s, qf.x, qf.y, qf.z, qf.w, dK);
  wg_commit();
#pragma unroll 1
  for (int c = 0; c < 4; c++) {
    if (c > 0) mbar_wait(bar + 8 * c, 0);
#pragma unroll 1
    for (int j = 0; j < 4; j++) {
      attn_step<SAFE>(s, o, m0, m1, qf, dK + 128, dV, ec);
      attn_step<SAFE>(s, o, m0, m1, qf, dK + 256, dV + 192, ec);
      dK += 256;
      dV += 384;
    }
  }
  wg_wait<0>();
  fence_regs(o);
  fence_regs(s);
  const float r0 = 1.0f / o[8], r1 = 1.0f / o[10];
  outp[0] = pack_bf16(o[0] * r0, o[1] * r0);
  outp[1] = pack_bf16(o[2] * r1, o[3] * r1);
  outp[2] = pack_bf16(o[4] * r0, o[5] * r0);
  outp[3] = pack_bf16(o[6] * r1, o[7] * r1);
}

__device__ __forceinline__ void linear_attn_cta(uint8_t* smem_raw, uint32_t sbase, const CUtensorMap* mo16, int cta) {
  const int warp = threadIdx.x >> 5, lane = threadIdx.x & 31;
  float* red = reinterpret_cast<float*>(smem_raw + (sbase - smem_u32(smem_raw)) + 131072);
  {
    const float* src = g_kvpart + (size_t)cta * 8 * 384;
    float sum[6];
#pragma unroll
    for (int i = 0; i < 6; i++) sum[i] = 0.f;
#pragma unroll
    for (int r = 0; r < 16; r++) {
#pragma unroll
      for (int i = 0; i < 6; i++) sum[i] += src[(size_t)r * NH * 384 + threadIdx.x + i * 512];
    }
#pragma unroll
    for (int i = 0; i < 6; i++) red[threadIdx.x + i * 512] = round_bf16(sum[i]);
  }
  __syncthreads();
  uint32_t bf[8][6];
  {
    const int g = lane >> 2, t = lane & 3;
#pragma unroll
    for (int h = 0; h < 8; h++) {
#pragma unroll
      for (int f = 0; f < 6; f++) {
        const int blk = f >> 1, half = f & 1;
        const int e = (blk == 2) ? 0 : g;
        const int d = 2 * t + 8 * half;
        const int base = h * 384 + (blk * 4 + half * 2 + (e & 1)) * 32 + (e >> 1);
        bf[h][f] = pack_bf16(red[base + (d & 7) * 4], red[base + ((d + 1) & 7) * 4]);
      }
    }
  }
  const uint32_t stg = sbase + warp * 8192;
#pragma unroll 1
  for (int rb = 0; rb < 8; rb++) {
    const int blk16 = rb * 16 + warp;
    const uint4* qp = g_qfrag + ((size_t)(NH + cta * 8) * 32 + (blk16 >> 2)) * 128 + (blk16 & 3) * 32 + lane;
    uint4 q[8];
#pragma unroll
    for (int h = 0; h < 8; h++) q[h] = qp[h * 32 * 128];
    const uint32_t buf = stg + (rb & 1) * 4096;
    if (rb >= 2) {
      if (lane == 0) asm volatile("cp.async.bulk.wait_group.read 1;" ::: "memory");
      __syncwarp();
    }
#pragma unroll
    for (int h = 0; h < 8; h++) {
      float n0[4] = {0, 0, 0, 0}, n1[4] = {0, 0, 0, 0}, dn[4] = {0, 0, 0, 0};
      hmma(n0, q[h].x, q[h].y, q[h].z, q[h].w, bf[h][0], bf[h][1]);
      hmma(n1, q[h].x, q[h].y, q[h].z, q[h].w, bf[h][2], bf[h][3]);
      hmma(dn, q[h].x, q[h].y, q[h].z, q[h].w, bf[h][4], bf[h][5]);
      const float d0 = round_bf16(round_bf16(dn[0]) + 1e-6f), d1 = round_bf16(round_bf16(dn[2]) + 1e-6f);
      const uint32_t r0 = pack_bf16(__fdividef(round_bf16(n0[0]), d0), __fdividef(round_bf16(n0[1]), d0));
      const uint32_t r1 = pack_bf16(__fdividef(round_bf16(n0[2]), d1), __fdividef(round_bf16(n0[3]), d1));
      const uint32_t r2 = pack_bf16(__fdividef(round_bf16(n1[0]), d0), __fdividef(round_bf16(n1[1]), d0));
      const uint32_t r3 = pack_bf16(__fdividef(round_bf16(n1[2]), d1), __fdividef(round_bf16(n1[3]), d1));
      const int row = lane & 15;
      const int chunk = (h & 3) * 2 + (lane >> 4);
      const uint32_t addr = buf + (h >> 2) * 2048 + row * 128 + ((chunk ^ (row & 7)) << 4);
      asm volatile("stmatrix.sync.aligned.m8n8.x4.shared.b16 [%0], {%1,%2,%3,%4};" ::"r"(addr), "r"(r0), "r"(r1), "r"(r2), "r"(r3)
                   : "memory");
    }
    fence_proxy_async();
    __syncwarp();
    if (lane == 0) {
      tma_store_2d(mo16, buf, cta * 128, blk16 * 16);
      tma_store_2d(mo16, buf + 2048, cta * 128 + 64, blk16 * 16);
      asm volatile("cp.async.bulk.commit_group;" ::: "memory");
    }
  }
  if (lane == 0) asm volatile("cp.async.bulk.wait_group 0;" ::: "memory");
}

__global__ void __launch_bounds__(512, 1) attn_kernel(const __grid_constant__ CUtensorMap mo16) {
  extern __shared__ uint8_t smem_raw[];
  const uint32_t sbase = (smem_u32(smem_raw) + 1023) & ~1023u;
  const uint32_t bar = sbase + KV_HEAD_BYTES;
  if (threadIdx.x == 0) { PROF_G(1, 30); PROF_T(1, 0); }
  if (threadIdx.x == 0) {
    for (int i = 0; i < 4; i++) mbar_init(bar + 8 * i, 1);
    fence_barrier_init();
    fence_proxy_async();
  }
  __syncthreads();
  if (blockIdx.x >= 128) {
    linear_attn_cta(smem_raw, sbase, &mo16, blockIdx.x - 128);
    if (threadIdx.x == 0) { PROF_T(1, 5); PROF_G(1, 31); }
    return;
  }
  const int head = blockIdx.x >> 2, qb = blockIdx.x & 3;
  if (threadIdx.x == 0) {
    const uint8_t* img = reinterpret_cast<const uint8_t*>(g_kv) + (size_t)head * KV_HEAD_BYTES;
    mbar_expect_tx(bar, 32768 + 24576);
    bulk_load(sbase, img, 32768, bar);
    bulk_load(sbase + KV_K_BYTES, img + KV_K_BYTES, 24576, bar);
    for (int i = 1; i < 4; i++) {
      mbar_expect_tx(bar + 8 * i, (i < 3 ? 16384 : 0) + 24576);
      if (i < 3) bulk_load(sbase + (i + 1) * 16384, img + (i + 1) * 16384, 16384, bar + 8 * i);
      bulk_load(sbase + KV_K_BYTES + i * 24576, img + KV_K_BYTES + i * 24576, 24576, bar + 8 * i);
    }
  }
  const int lane = threadIdx.x & 31;
  bool safe_path;
  {
    float4 n = make_float4(0.f, 0.f, 0.f, 0.f);
    if (lane < 16) n = *reinterpret_cast<const float4*>(&g_nrm[(head * 16 + lane) * 4]);
    uint32_t qm = ((lane >> 2) == qb) ? __float_as_uint(n.x) : 0u;
    qm = __reduce_max_sync(0xffffffffu, qm);
    const uint32_t km = __reduce_max_sync(0xffffffffu, __float_as_uint(n.y));
    const uint32_t vm = __reduce_max_sync(0xffffffffu, __float_as_uint(n.z));
    const float b2 = __uint_as_float(qm) * (QSCALE * QSCALE) * __uint_as_float(km) * 1.02f;
    const float vmax = __uint_as_float(vm);
    const bool ok = (b2 <= 21.5f * 21.5f) && (vmax <= 1.0e24f) && (vmax >= 1.0e-18f || vmax == 0.f);
    safe_path = !ok;
  }
  const int wg = threadIdx.x >> 7, warp = (threadIdx.x >> 5) & 3;
  uint32_t zero;
  asm volatile("mov.u32 %0, %%smid;" : "=r"(zero));
  zero >>= 16;
  const ExpC ec{0x3C003C00u + zero, 0x00070000u + zero, 7u + zero, 0x2cfd2cfdu + zero};
  const uint64_t dK = mkdesc(sbase, 128, 256, 0);
  const uint64_t dV = mkdesc(sbase + KV_K_BYTES, 384, 128, 0);
#pragma unroll 1
  for (int t = 0; t < 2; t++) {
    const int tile64 = qb * 8 + wg * 2 + t;
    const uint4 qf = g_qfrag[(head * 32 + tile64) * 128 + (threadIdx.x & 127)];
    uint32_t r[4];
    if (threadIdx.x == 0) PROF_T(1, 1 + t);
    if (!safe_path) attn_tile<false>(dK, dV, bar, qf, ec, r);
    else attn_tile<true>(dK, dV, bar, qf, ec, r);
    store_o(g_o + (size_t)S_LEN * DM, tile64 * 64 + warp * 16, head, lane, r);
  }
  if (threadIdx.x == 0) { PROF_T(1, 5); PROF_G(1, 31); }
}

constexpr int K3_STAGES = 6;
constexpr int K3_STAGE_BYTES = 16384 + 2 * 8192;
constexpr int K3_SMEM = K3_STAGES * K3_STAGE_BYTES + 1024 + 256;

__global__ void __launch_bounds__(288, 1)
out_gemm_kernel(const __grid_constant__ CUtensorMap mo, const __grid_constant__ CUtensorMap mwA,
                const __grid_constant__ CUtensorMap mwB, const __grid_constant__ CUtensorMap mout) {
  extern __shared__ uint8_t smem_raw[];
  const uint32_t sbase = (smem_u32(smem_raw) + 1023) & ~1023u;
  const uint32_t bar_full = sbase + K3_STAGES * K3_STAGE_BYTES;
  const uint32_t bar_empty = bar_full + 8 * K3_STAGES;
  const int branch = blockIdx.x >> 6;
  const int rt = (blockIdx.x & 63) >> 2;
  const int ct = blockIdx.x & 3;
  const int warp = threadIdx.x >> 5;
  if (threadIdx.x == 0) { PROF_G(2, 30); PROF_T(2, 0); }
  if (threadIdx.x == 0) {
    for (int i = 0; i < K3_STAGES; i++) {
      mbar_init(bar_full + 8 * i, 1);
      mbar_init(bar_empty + 8 * i, 2);
    }
    fence_barrier_init();
  }
  __syncthreads();
  if (warp == 8) {
    if ((threadIdx.x & 31) == 0) {
      const CUtensorMap* mw = branch ? &mwB : &mwA;
      for (int kb = 0; kb < 8; kb++) {
        const int s = kb % K3_STAGES;
        if (kb >= K3_STAGES) mbar_wait(bar_empty + 8 * s, ((kb / K3_STAGES) - 1) & 1);
        const uint32_t st = sbase + s * K3_STAGE_BYTES;
        mbar_expect_tx(bar_full + 8 * s, K3_STAGE_BYTES);
        tma_load_2d(st, &mo, kb * 64, branch * S_LEN + rt * 128, bar_full + 8 * s);
        tma_load_2d(st + 16384, mw, ct * 128, kb * 64, bar_full + 8 * s);
        tma_load_2d(st + 16384 + 8192, mw, ct * 128 + 64, kb * 64, bar_full + 8 * s);
      }
    }
  } else {
    const int wg = warp >> 2;
    float acc[64];
    for (int kb = 0; kb < 8; kb++) {
      const int s = kb % K3_STAGES;
      mbar_wait(bar_full + 8 * s, (kb / K3_STAGES) & 1);
      if (threadIdx.x == 0) PROF_T(2, 2 + kb);
      const uint32_t st = sbase + s * K3_STAGE_BYTES;
      const uint64_t dA = mkdesc(st + wg * 8192, 16, 1024, 1);
      const uint64_t dB = mkdesc(st + 16384, 8192, 1024, 1);
      wg_fence();
#pragma unroll
      for (int k = 0; k < 4; k++) wgmma_ss_n128_tb(acc, dA + k * 2, dB + k * 128, (kb | k) != 0);
      wg_commit();
      if (kb > 0) {
        wg_wait<1>();
        if ((threadIdx.x & 127) == 0) mbar_arrive(bar_empty + 8 * ((kb - 1) % K3_STAGES));
      }
    }
    wg_wait<0>();
    fence_regs(acc);
    if (threadIdx.x == 0) PROF_T(2, 10);
    asm volatile("bar.sync 1, 256;" ::: "memory");
    const int lane = threadIdx.x & 31;
    const int rloc = wg * 64 + (warp & 3) * 16 + (lane & 15);
#pragma unroll
    for (int c16 = 0; c16 < 8; c16++) {
      const float* a = &acc[c16 * 8];
      const uint32_t r0 = pack_bf16(a[0], a[1]), r1 = pack_bf16(a[2], a[3]), r2 = pack_bf16(a[4], a[5]), r3 = pack_bf16(a[6], a[7]);
      const int chunk = (c16 & 3) * 2 + (lane >> 4);
      const uint32_t addr = sbase + (c16 >> 2) * 16384 + rloc * 128 + ((chunk ^ (rloc & 7)) << 4);
      asm volatile("stmatrix.sync.aligned.m8n8.x4.shared.b16 [%0], {%1,%2,%3,%4};" ::"r"(addr), "r"(r0), "r"(r1), "r"(r2), "r"(r3)
                   : "memory");
    }
    fence_proxy_async();
    asm volatile("bar.sync 1, 256;" ::: "memory");
    if (threadIdx.x == 0) {
      tma_store_2d(&mout, sbase, branch * DM + ct * 128, rt * 128);
      tma_store_2d(&mout, sbase + 16384, branch * DM + ct * 128 + 64, rt * 128);
      asm volatile("cp.async.bulk.commit_group;" ::: "memory");
      asm volatile("cp.async.bulk.wait_group 0;" ::: "memory");
      PROF_T(2, 12); PROF_G(2, 31);
    }
  }
}

typedef CUresult (*EncodeFn)(CUtensorMap*, CUtensorMapDataType, cuuint32_t, void*, const cuuint64_t*, const cuuint64_t*,
                             const cuuint32_t*, const cuuint32_t*, CUtensorMapInterleave, CUtensorMapSwizzle,
                             CUtensorMapL2promotion, CUtensorMapFloatOOBfill);

void make_map(EncodeFn enc, CUtensorMap* m, const void* ptr, uint64_t inner, uint64_t outer, uint32_t box_inner, uint32_t box_outer) {
  cuuint64_t dims[2] = {inner, outer};
  cuuint64_t strides[1] = {inner * 2};
  cuuint32_t box[2] = {box_inner, box_outer};
  cuuint32_t es[2] = {1, 1};
  enc(m, CU_TENSOR_MAP_DATA_TYPE_BFLOAT16, 2, const_cast<void*>(ptr), dims, strides, box, es, CU_TENSOR_MAP_INTERLEAVE_NONE,
      CU_TENSOR_MAP_SWIZZLE_128B, CU_TENSOR_MAP_L2_PROMOTION_L2_256B, CU_TENSOR_MAP_FLOAT_OOB_FILL_NONE);
}

struct HostState {
  bool init;
  const void* key[7];
  CUtensorMap mxA, mxB, mwA, mwB, mo, mo16, mwoA, mwoB, mout;
};
HostState g_hs;

}

extern "C" void kernel_launch(void* const* d_in, const int* in_sizes, int n_in, void* d_out, int out_size) {
  (void)in_sizes; (void)n_in; (void)out_size;
  HostState& hs = g_hs;
  bool same = hs.init && hs.key[6] == d_out;
  for (int i = 0; i < 6 && same; i++) same = hs.key[i] == d_in[i];
  if (!same) {
    void* fn = nullptr;
    cudaDriverEntryPointQueryResult qr;
    cudaGetDriverEntryPoint("cuTensorMapEncodeTiled", &fn, cudaEnableDefault, &qr);
    EncodeFn enc = (EncodeFn)fn;
    void* go = nullptr;
    cudaGetSymbolAddress(&go, g_o);
    make_map(enc, &hs.mxA, d_in[0], 512, 2048, 64, 128);
    make_map(enc, &hs.mwA, d_in[1], 1536, 512, 64, 64);
    make_map(enc, &hs.mwoA, d_in[2], 512, 512, 64, 64);
    make_map(enc, &hs.mxB, d_in[3], 512, 2048, 64, 128);
    make_map(enc, &hs.mwB, d_in[4], 1536, 512, 64, 64);
    make_map(enc, &hs.mwoB, d_in[5], 512, 512, 64, 64);
    make_map(enc, &hs.mo, go, 512, 4096, 64, 128);
    make_map(enc, &hs.mo16, go, 512, 4096, 64, 16);
    make_map(enc, &hs.mout, d_out, 1024, 2048, 64, 128);
    cudaFuncSetAttribute(qkv_gemm_kernel, cudaFuncAttributeMaxDynamicSharedMemorySize, K1_SMEM);
    cudaFuncSetAttribute(attn_kernel, cudaFuncAttributeMaxDynamicSharedMemorySize, K2_SMEM);
    cudaFuncSetAttribute(out_gemm_kernel, cudaFuncAttributeMaxDynamicSharedMemorySize, K3_SMEM);
    for (int i = 0; i < 6; i++) hs.key[i] = d_in[i];
    hs.key[6] = d_out;
    hs.init = true;
  }
  cudaStream_t st = cudaStreamPerThread;
  {
    cudaLaunchConfig_t cfg = {};
    cfg.gridDim = dim3(128);
    cfg.blockDim = dim3(384);
    cfg.dynamicSmemBytes = K1_SMEM;
    cfg.stream = st;
    cudaLaunchAttribute at[1];
    at[0].id = cudaLaunchAttributeClusterDimension;
    at[0].val.clusterDim.x = 2;
    at[0].val.clusterDim.y = 1;
    at[0].val.clusterDim.z = 1;
    cfg.attrs = at;
    cfg.numAttrs = 1;
    cudaLaunchKernelEx(&cfg, qkv_gemm_kernel, hs.mxA, hs.mxB, hs.mwA, hs.mwB);
  }
  attn_kernel<<<132, 512, K2_SMEM, st>>>(hs.mo16);
  out_gemm_kernel<<<128, 288, K3_SMEM, st>>>(hs.mo, hs.mwoA, hs.mwoB, hs.mout);
}
```

```cpp
#include <cuda_runtime.h>
#include <cuda_bf16.h>
#include <cuda.h>
#include <stdint.h>

namespace {

constexpr int S_LEN = 2048;
constexpr int DM = 512;
constexpr int NH = 32;

constexpr int KV_K_BYTES = 65536;
constexpr int KV_HEAD_BYTES = KV_K_BYTES + 98304;
__device__ uint4 g_qfrag[2 * NH * 32 * 128];
__device__ uint4 g_kv[NH * KV_HEAD_BYTES / 16];
__device__ float g_kvpart[16 * NH * 384];
__device__ float g_nrm[NH * 16 * 4];
__device__ __nv_bfloat16 g_o[2 * S_LEN * DM];

#define PROF_T(k, i) do {} while (0)
#define PROF_G(k, i) do {} while (0)
__device__ __forceinline__ uint32_t smem_u32(const void* p) { return (uint32_t)__cvta_generic_to_shared(p); }
__device__ __forceinline__ void mbar_init(uint32_t bar, int cnt) {
  asm volatile("mbarrier.init.shared::cta.b64 [%0], %1;" ::"r"(bar), "r"(cnt) : "memory");
}
__device__ __forceinline__ void mbar_expect_tx(uint32_t bar, uint32_t bytes) {
  asm volatile("mbarrier.arrive.expect_tx.shared::cta.b64 _, [%0], %1;" ::"r"(bar), "r"(bytes) : "memory");
}
__device__ __forceinline__ void mbar_arrive(uint32_t bar) {
  asm volatile("mbarrier.arrive.shared::cta.b64 _, [%0];" ::"r"(bar) : "memory");
}
__device__ __forceinline__ void mbar_arrive_cluster(uint32_t bar, uint32_t cta) {
  asm volatile(
      "{\n.reg .b32 ra;\nmapa.shared::cluster.u32 ra, %0, %1;\n"
      "mbarrier.arrive.shared::cluster.b64 _, [ra];\n}" ::"r"(bar), "r"(cta) : "memory");
}
__device__ __forceinline__ void mbar_wait(uint32_t bar, uint32_t parity) {
  asm volatile(
      "{\n.reg .pred p;\n"
      "WAIT_LOOP:\n"
      "mbarrier.try_wait.parity.shared::cta.b64 p, [%0], %1, 0x989680;\n"
      "@p bra WAIT_DONE;\n"
      "bra WAIT_LOOP;\n"
      "WAIT_DONE:\n}" ::"r"(bar), "r"(parity) : "memory");
}
__device__ __forceinline__ void mbar_wait_cluster(uint32_t bar, uint32_t parity) {
  asm volatile(
      "{\n.reg .pred p;\n"
      "WAIT_LOOP:\n"
      "mbarrier.try_wait.parity.acquire.cluster.shared::cta.b64 p, [%0], %1, 0x989680;\n"
      "@p bra WAIT_DONE;\n"
      "bra WAIT_LOOP;\n"
      "WAIT_DONE:\n}" ::"r"(bar), "r"(parity) : "memory");
}
__device__ __forceinline__ void fence_barrier_init() {
  asm volatile("fence.mbarrier_init.release.cluster;" ::: "memory");
}
__device__ __forceinline__ void fence_proxy_async() { asm volatile("fence.proxy.async.shared::cta;" ::: "memory"); }
__device__ __forceinline__ void cluster_sync_relaxed() {
  asm volatile("barrier.cluster.arrive.relaxed.aligned;\nbarrier.cluster.wait.aligned;" ::: "memory");
}
__device__ __forceinline__ void tma_load_2d(uint32_t dst, const CUtensorMap* m, int x, int y, uint32_t bar) {
  asm volatile(
      "cp.async.bulk.tensor.2d.shared::cluster.global.mbarrier::complete_tx::bytes [%0], [%1, {%3, %4}], [%2];" ::"r"(dst),
      "l"(m), "r"(bar), "r"(x), "r"(y)
      : "memory");
}
__device__ __forceinline__ void tma_load_2d_mc(uint32_t dst, const CUtensorMap* m, int x, int y, uint32_t bar, uint16_t mask) {
  asm volatile(
      "cp.async.bulk.tensor.2d.shared::cluster.global.mbarrier::complete_tx::bytes.multicast::cluster [%0], [%1, {%3, %4}], "
      "[%2], %5;" ::"r"(dst),
      "l"(m), "r"(bar), "r"(x), "r"(y), "h"(mask)
      : "memory");
}
__device__ __forceinline__ void tma_store_2d(const CUtensorMap* m, uint32_t src, int x, int y) {
  asm volatile("cp.async.bulk.tensor.2d.global.shared::cta.bulk_group [%0, {%2, %3}], [%1];" ::"l"(m), "r"(src), "r"(x),
               "r"(y)
               : "memory");
}
__device__ __forceinline__ void bulk_load(uint32_t dst, const void* src, uint32_t bytes, uint32_t bar) {
  asm volatile("cp.async.bulk.shared::cluster.global.mbarrier::complete_tx::bytes [%0], [%1], %2, [%3];" ::"r"(dst),
               "l"(src), "r"(bytes), "r"(bar)
               : "memory");
}
__device__ __forceinline__ void wg_fence() { asm volatile("wgmma.fence.sync.aligned;" ::: "memory"); }
__device__ __forceinline__ void wg_commit() { asm volatile("wgmma.commit_group.sync.aligned;" ::: "memory"); }
template <int N>
__device__ __forceinline__ void wg_wait() {
  asm volatile("wgmma.wait_group.sync.aligned %0;" ::"n"(N) : "memory");
}
template <int M>
__device__ __forceinline__ void fence_regs(float (&r)[M]) {
#pragma unroll
  for (int i = 0; i < M; i++) asm volatile("" : "+f"(r[i])::"memory");
}
__device__ __forceinline__ uint64_t mkdesc(uint32_t addr, uint32_t lbo, uint32_t sbo, uint32_t layout) {
  return (uint64_t)((addr & 0x3FFFF) >> 4) | ((uint64_t)(lbo >> 4) << 16) | ((uint64_t)(sbo >> 4) << 32) |
         ((uint64_t)layout << 62);
}
__device__ __forceinline__ uint32_t pack_bf16(float lo, float hi) {
  uint32_t r;
  asm("cvt.rn.bf16x2.f32 %0, %1, %2;" : "=r"(r) : "f"(hi), "f"(lo));
  return r;
}
__device__ __forceinline__ float bf_lo(uint32_t v) { return __uint_as_float(v << 16); }
__device__ __forceinline__ float bf_hi(uint32_t v) { return __uint_as_float(v & 0xFFFF0000u); }
__device__ __forceinline__ float round_bf16(float x) { return bf_lo(pack_bf16(x, 0.f)); }
__device__ __forceinline__ float ex2f(float x) {
  float y;
  asm("ex2.approx.ftz.f32 %0, %1;" : "=f"(y) : "f"(x));
  return y;
}

__device__ __forceinline__ void wgmma_rs_n24_tb(float (&d)[12], uint32_t a0, uint32_t a1, uint32_t a2, uint32_t a3, uint64_t descB, int scaleD) {
  asm volatile("{\n.reg .pred p;\nsetp.ne.b32 p, %17, 0;\n"
    "wgmma.mma_async.sync.aligned.m64n24k16.f32.bf16.bf16 "
    "{%0, %1, %2, %3, %4, %5, %6, %7, %8, %9, %10, %11}, {%12, %13, %14, %15}, %16, p, 1, 1, 1;\n}\n"
    : "+f"(d[0]), "+f"(d[1]), "+f"(d[2]), "+f"(d[3]), "+f"(d[4]), "+f"(d[5]), "+f"(d[6]), "+f"(d[7]),
      "+f"(d[8]), "+f"(d[9]), "+f"(d[10]), "+f"(d[11])
    : "r"(a0), "r"(a1), "r"(a2), "r"(a3), "l"(descB), "r"(scaleD));
}
__device__ __forceinline__ void wgmma_rs_n64_z(float (&d)[32], uint32_t a0, uint32_t a1, uint32_t a2, uint32_t a3, uint64_t descB) {
  asm volatile("{\n.reg .pred p;\nsetp.ne.b32 p, %37, 0;\n"
    "wgmma.mma_async.sync.aligned.m64n64k16.f32.bf16.bf16 "
    "{%0, %1, %2, %3, %4, %5, %6, %7, %8, %9, %10, %11, %12, %13, %14, %15, %16, %17, %18, %19, %20, %21, %22, %23, %24, %25, %26, %27, %28, %29, %30, %31}, {%32, %33, %34, %35}, %36, p, 1, 1, 0;\n}\n"
    : "=f"(d[0]), "=f"(d[1]), "=f"(d[2]), "=f"(d[3]), "=f"(d[4]), "=f"(d[5]), "=f"(d[6]), "=f"(d[7]),
      "=f"(d[8]), "=f"(d[9]), "=f"(d[10]), "=f"(d[11]), "=f"(d[12]), "=f"(d[13]), "=f"(d[14]), "=f"(d[15]),
      "=f"(d[16]), "=f"(d[17]), "=f"(d[18]), "=f"(d[19]), "=f"(d[20]), "=f"(d[21]), "=f"(d[22]), "=f"(d[23]),
      "=f"(d[24]), "=f"(d[25]), "=f"(d[26]), "=f"(d[27]), "=f"(d[28]), "=f"(d[29]), "=f"(d[30]), "=f"(d[31])
    : "r"(a0), "r"(a1), "r"(a2), "r"(a3), "l"(descB), "n"(0));
}
__device__ __forceinline__ void wgmma_ss_n128_tb(float (&d)[64], uint64_t descA, uint64_t descB, int scaleD) {
  asm volatile("{\n.reg .pred p;\nsetp.ne.b32 p, %66, 0;\n"
    "wgmma.mma_async.sync.aligned.m64n128k16.f32.bf16.bf16 "
    "{%0, %1, %2, %3, %4, %5, %6, %7, %8, %9, %10, %11, %12, %13, %14, %15, %16, %17, %18, %19, %20, %21, %22, %23, %24, %25, %26, %27, %28, %29, %30, %31, %32, %33, %34, %35, %36, %37, %38, %39, %40, %41, %42, %43, %44, %45, %46, %47, %48, %49, %50, %51, %52, %53, %54, %55, %56, %57, %58, %59, %60, %61, %62, %63}, %64, %65, p, 1, 1, 0, 1;\n}\n"
    : "+f"(d[0]), "+f"(d[1]), "+f"(d[2]), "+f"(d[3]), "+f"(d[4]), "+f"(d[5]), "+f"(d[6]), "+f"(d[7]),
      "+f"(d[8]), "+f"(d[9]), "+f"(d[10]), "+f"(d[11]), "+f"(d[12]), "+f"(d[13]), "+f"(d[14]), "+f"(d[15]),
      "+f"(d[16]), "+f"(d[17]), "+f"(d[18]), "+f"(d[19]), "+f"(d[20]), "+f"(d[21]), "+f"(d[22]), "+f"(d[23]),
      "+f"(d[24]), "+f"(d[25]), "+f"(d[26]), "+f"(d[27]), "+f"(d[28]), "+f"(d[29]), "+f"(d[30]), "+f"(d[31]),
      "+f"(d[32]), "+f"(d[33]), "+f"(d[34]), "+f"(d[35]), "+f"(d[36]), "+f"(d[37]), "+f"(d[38]), "+f"(d[39]),
      "+f"(d[40]), "+f"(d[41]), "+f"(d[42]), "+f"(d[43]), "+f"(d[44]), "+f"(d[45]), "+f"(d[46]), "+f"(d[47]),
      "+f"(d[48]), "+f"(d[49]), "+f"(d[50]), "+f"(d[51]), "+f"(d[52]), "+f"(d[53]), "+f"(d[54]), "+f"(d[55]),
      "+f"(d[56]), "+f"(d[57]), "+f"(d[58]), "+f"(d[59]), "+f"(d[60]), "+f"(d[61]), "+f"(d[62]), "+f"(d[63])
    : "l"(descA), "l"(descB), "r"(scaleD));
}
__device__ __forceinline__ void wgmma_ss_n192_tb(float (&d)[96], uint64_t descA, uint64_t descB, int scaleD) {
  asm volatile("{\n.reg .pred p;\nsetp.ne.b32 p, %98, 0;\n"
    "wgmma.mma_async.sync.aligned.m64n192k16.f32.bf16.bf16 "
    "{%0, %1, %2, %3, %4, %5, %6, %7, %8, %9, %10, %11, %12, %13, %14, %15, %16, %17, %18, %19, %20, %21, %22, %23, %24, %25, %26, %27, %28, %29, %30, %31, %32, %33, %34, %35, %36, %37, %38, %39, %40, %41, %42, %43, %44, %45, %46, %47, %48, %49, %50, %51, %52, %53, %54, %55, %56, %57, %58, %59, %60, %61, %62, %63, %64, %65, %66, %67, %68, %69, %70, %71, %72, %73, %74, %75, %76, %77, %78, %79, %80, %81, %82, %83, %84, %85, %86, %87, %88, %89, %90, %91, %92, %93, %94, %95}, %96, %97, p, 1, 1, 0, 1;\n}\n"
    : "+f"(d[0]), "+f"(d[1]), "+f"(d[2]), "+f"(d[3]), "+f"(d[4]), "+f"(d[5]), "+f"(d[6]), "+f"(d[7]),
      "+f"(d[8]), "+f"(d[9]), "+f"(d[10]), "+f"(d[11]), "+f"(d[12]), "+f"(d[13]), "+f"(d[14]), "+f"(d[15]),
      "+f"(d[16]), "+f"(d[17]), "+f"(d[18]), "+f"(d[19]), "+f"(d[20]), "+f"(d[21]), "+f"(d[22]), "+f"(d[23]),
      "+f"(d[24]), "+f"(d[25]), "+f"(d[26]), "+f"(d[27]), "+f"(d[28]), "+f"(d[29]), "+f"(d[30]), "+f"(d[31]),
      "+f"(d[32]), "+f"(d[33]), "+f"(d[34]), "+f"(d[35]), "+f"(d[36]), "+f"(d[37]), "+f"(d[38]), "+f"(d[39]),
      "+f"(d[40]), "+f"(d[41]), "+f"(d[42]), "+f"(d[43]), "+f"(d[44]), "+f"(d[45]), "+f"(d[46]), "+f"(d[47]),
      "+f"(d[48]), "+f"(d[49]), "+f"(d[50]), "+f"(d[51]), "+f"(d[52]), "+f"(d[53]), "+f"(d[54]), "+f"(d[55]),
      "+f"(d[56]), "+f"(d[57]), "+f"(d[58]), "+f"(d[59]), "+f"(d[60]), "+f"(d[61]), "+f"(d[62]), "+f"(d[63]),
      "+f"(d[64]), "+f"(d[65]), "+f"(d[66]), "+f"(d[67]), "+f"(d[68]), "+f"(d[69]), "+f"(d[70]), "+f"(d[71]),
      "+f"(d[72]), "+f"(d[73]), "+f"(d[74]), "+f"(d[75]), "+f"(d[76]), "+f"(d[77]), "+f"(d[78]), "+f"(d[79]),
      "+f"(d[80]), "+f"(d[81]), "+f"(d[82]), "+f"(d[83]), "+f"(d[84]), "+f"(d[85]), "+f"(d[86]), "+f"(d[87]),
      "+f"(d[88]), "+f"(d[89]), "+f"(d[90]), "+f"(d[91]), "+f"(d[92]), "+f"(d[93]), "+f"(d[94]), "+f"(d[95])
    : "l"(descA), "l"(descB), "r"(scaleD));
}

__device__ __forceinline__ void ldsm4t(uint32_t (&b)[4], uint32_t addr) {
  asm volatile("ldmatrix.sync.aligned.m8n8.x4.trans.shared.b16 {%0,%1,%2,%3}, [%4];"
               : "=r"(b[0]), "=r"(b[1]), "=r"(b[2]), "=r"(b[3])
               : "r"(addr));
}
__device__ __forceinline__ void hmma(float (&c)[4], uint32_t a0, uint32_t a1, uint32_t a2, uint32_t a3, uint32_t b0, uint32_t b1) {
  asm("mma.sync.aligned.m16n8k16.row.col.f32.bf16.bf16.f32 {%0,%1,%2,%3}, {%4,%5,%6,%7}, {%8,%9}, {%0,%1,%2,%3};"
      : "+f"(c[0]), "+f"(c[1]), "+f"(c[2]), "+f"(c[3])
      : "r"(a0), "r"(a1), "r"(a2), "r"(a3), "r"(b0), "r"(b1));
}

__device__ __forceinline__ uint32_t movm(uint32_t a) {
  uint32_t d;
  asm volatile("movmatrix.sync.aligned.m8n8.trans.b16 %0, %1;" : "=r"(d) : "r"(a));
  return d;
}

constexpr int K1_STAGES = 3;
constexpr int K1_W_BYTES = 3 * 8192;
constexpr int K1_X_BYTES = 8 * 16384;
constexpr int K1_RED_OFF = K1_X_BYTES + K1_STAGES * K1_W_BYTES;
constexpr int K1_BAR_OFF = K1_RED_OFF + 8 * 384 * 4;
constexpr int K1_SMEM = K1_BAR_OFF + 256 + 1024;
constexpr float QSCALE = 0.25f * 1.4426950408889634f;

__device__ __forceinline__ uint32_t phi2(uint32_t t2) {
  uint32_t a2, mask, r2, o2;
  asm("add.rn.bf16x2 %0, %1, %2;" : "=r"(a2) : "r"(t2), "r"(0x3F803F80u));
  const uint32_t e2 = pack_bf16(ex2f(bf_lo(t2) * 1.4426950408889634f), ex2f(bf_hi(t2) * 1.4426950408889634f));
  asm("set.gt.u32.bf16x2 %0, %1, %2;" : "=r"(mask) : "r"(t2), "r"(0u));
  r2 = (a2 & mask) | (e2 & ~mask);
  asm("add.rn.bf16x2 %0, %1, %2;" : "=r"(o2) : "r"(r2), "r"(0x35863586u));
  return o2;
}

struct EpiCtx {
  uint4* qf;
  uint32_t* kp;
  uint32_t* vp;
  uint32_t* s_red;
  float* red;
  int lane;
};

template <bool LINEAR, int J, int HH, int PART>
__device__ __forceinline__ void epi_slice(const float (&acc)[96], const EpiCtx& c, uint32_t (&pk)[4], float& vmax) {
  constexpr int h = J * 4 + HH;
  const float* a = &acc[HH * 8];
  const float* k = &acc[32 + HH * 8];
  const float* v = &acc[64 + HH * 8];
  if (!LINEAR) {
    if (PART == 0) {
      c.qf[h * 32 * 128] = make_uint4(pack_bf16(a[0] * QSCALE, a[1] * QSCALE), pack_bf16(a[2] * QSCALE, a[3] * QSCALE),
                                      pack_bf16(a[4] * QSCALE, a[5] * QSCALE), pack_bf16(a[6] * QSCALE, a[7] * QSCALE));
      uint32_t* kh = c.kp + h * (KV_HEAD_BYTES / 4);
      kh[0] = pack_bf16(k[0], k[1]);
      kh[64] = pack_bf16(k[2], k[3]);
      kh[32] = pack_bf16(k[4], k[5]);
      kh[96] = pack_bf16(k[6], k[7]);
      float q0 = a[0] * a[0] + a[1] * a[1] + a[4] * a[4] + a[5] * a[5];
      float q1 = a[2] * a[2] + a[3] * a[3] + a[6] * a[6] + a[7] * a[7];
      float k0 = k[0] * k[0] + k[1] * k[1] + k[4] * k[4] + k[5] * k[5];
      float k1 = k[2] * k[2] + k[3] * k[3] + k[6] * k[6] + k[7] * k[7];
#pragma unroll
      for (int o = 1; o <= 2; o <<= 1) {
        q0 += __shfl_xor_sync(0xffffffffu, q0, o);
        q1 += __shfl_xor_sync(0xffffffffu, q1, o);
        k0 += __shfl_xor_sync(0xffffffffu, k0, o);
        k1 += __shfl_xor_sync(0xffffffffu, k1, o);
      }
      const uint32_t qm = __reduce_max_sync(0xffffffffu, max(__float_as_uint(q0) & 0x7FFFFFFFu, __float_as_uint(q1) & 0x7FFFFFFFu));
      const uint32_t km = __reduce_max_sync(0xffffffffu, max(__float_as_uint(k0) & 0x7FFFFFFFu, __float_as_uint(k1) & 0x7FFFFFFFu));
      if (c.lane == 0) {
        atomicMax(&c.s_red[h * 2 + 0], qm);
        atomicMax(&c.s_red[h * 2 + 1], km);
      }
    } else {
      uint32_t* vh = c.vp + h * (KV_HEAD_BYTES / 4);
      vh[0] = pack_bf16(v[0], v[1]);
      vh[96] = pack_bf16(v[2], v[3]);
      vh[32] = pack_bf16(v[4], v[5]);
      vh[128] = pack_bf16(v[6], v[7]);
      vh[64] = 0x3F803F80u;
      vh[160] = 0x3F803F80u;
#pragma unroll
      for (int i = 0; i < 8; i++) asm("max.NaN.f32 %0, %0, %1;" : "+f"(vmax) : "f"(fabsf(v[i])));
    }
  } else {
    if (PART == 0) {
      c.qf[h * 32 * 128] = make_uint4(phi2(pack_bf16(a[0], a[1])), phi2(pack_bf16(a[2], a[3])), phi2(pack_bf16(a[4], a[5])),
                                      phi2(pack_bf16(a[6], a[7])));
      pk[0] = movm(phi2(pack_bf16(k[0], k[1])));
      pk[2] = movm(phi2(pack_bf16(k[2], k[3])));
      pk[1] = movm(phi2(pack_bf16(k[4], k[5])));
      pk[3] = movm(phi2(pack_bf16(k[6], k[7])));
    } else {
      const uint32_t b0 = movm(pack_bf16(v[0], v[1]));
      const uint32_t b1 = movm(pack_bf16(v[2], v[3]));
      const uint32_t b2 = movm(pack_bf16(v[4], v[5]));
      const uint32_t b3 = movm(pack_bf16(v[6], v[7]));
      float c0[4] = {0, 0, 0, 0}, c1[4] = {0, 0, 0, 0}, c2[4] = {0, 0, 0, 0};
      hmma(c0, pk[0], pk[1], pk[2], pk[3], b0, b1);
      hmma(c1, pk[0], pk[1], pk[2], pk[3], b2, b3);
      hmma(c2, pk[0], pk[1], pk[2], pk[3], 0x3F803F80u, 0x3F803F80u);
#pragma unroll
      for (int i = 0; i < 4; i++) {
        atomicAdd(c.red + h * 384 + i * 32, c0[i]);
        atomicAdd(c.red + h * 384 + (4 + i) * 32, c1[i]);
        atomicAdd(c.red + h * 384 + (8 + i) * 32, c2[i]);
      }
    }
  }
}

template <bool LINEAR>
__device__ __forceinline__ void qkv_consumer(uint32_t sbase, uint8_t* smem_gen, uint32_t* s_red, int cp, int rt) {
  const uint32_t bar_full = sbase + K1_BAR_OFF;
  const uint32_t bar_empty = bar_full + 8 * K1_STAGES;
  const int warp = threadIdx.x >> 5;
  const int wg = warp >> 2;
  const int lane = threadIdx.x & 31;
  float acc0[96], acc1[96];
#pragma unroll 1
  for (int kb = 0; kb < 8; kb++) {
    const int s = kb % K1_STAGES;
    mbar_wait(bar_full + 8 * s, (kb / K1_STAGES) & 1);
    if (threadIdx.x == 0) PROF_T(0, 2 + (kb >> 1));
    const uint64_t dA = mkdesc(sbase + kb * 16384 + wg * 8192, 16, 1024, 1);
    const uint64_t dB = mkdesc(sbase + K1_X_BYTES + s * K1_W_BYTES, 8192, 1024, 1);
    wg_fence();
#pragma unroll
    for (int k = 0; k < 4; k++) wgmma_ss_n192_tb(acc0, dA + k * 2, dB + k * 128, (kb | k) != 0);
    wg_commit();
    if (kb > 0) {
      wg_wait<1>();
      if ((threadIdx.x & 127) == 0) {
        const int sp = (kb - 1) % K1_STAGES;
        mbar_arrive_cluster(bar_empty + 8 * sp, 0);
        mbar_arrive_cluster(bar_empty + 8 * sp, 1);
      }
    }
  }
  wg_wait<0>();
  fence_regs(acc0);
  if ((threadIdx.x & 127) == 0) {
    mbar_arrive_cluster(bar_empty + 8 * (7 % K1_STAGES), 0);
    mbar_arrive_cluster(bar_empty + 8 * (7 % K1_STAGES), 1);
  }
  if (threadIdx.x == 0) PROF_T(0, 6);

  EpiCtx c;
  {
    const int row0 = rt * 128 + wg * 64 + (warp & 3) * 16;
    c.qf = g_qfrag + ((size_t)((LINEAR ? NH : 0) + cp * 8) * 32 + (rt * 2 + wg)) * 128 + (threadIdx.x & 127);
    uint32_t* img = reinterpret_cast<uint32_t*>(reinterpret_cast<uint8_t*>(g_kv) + (size_t)(cp * 8) * KV_HEAD_BYTES);
    c.kp = img + (row0 >> 3) * 64 + lane;
    c.vp = img + KV_K_BYTES / 4 + (row0 >> 3) * 96 + lane;
    c.s_red = s_red;
    c.red = reinterpret_cast<float*>(smem_gen + K1_RED_OFF) + lane;
    c.lane = lane;
  }
  uint32_t pk[4];
  float vmax = 0.f;
#define K1_T1_STEP(KB)                                                                           \
  {                                                                                              \
    constexpr int g = 8 + KB;                                                                    \
    constexpr int s = g % K1_STAGES;                                                             \
    mbar_wait(bar_full + 8 * s, (g / K1_STAGES) & 1);                                            \
    const uint64_t dA = mkdesc(sbase + KB * 16384 + wg * 8192, 16, 1024, 1);                     \
    const uint64_t dB = mkdesc(sbase + K1_X_BYTES + s * K1_W_BYTES, 8192, 1024, 1);              \
    wg_fence();                                                                                  \
    _Pragma("unroll") for (int k = 0; k < 4; k++) wgmma_ss_n192_tb(acc1, dA + k * 2, dB + k * 128, (KB | k) != 0); \
    wg_commit();                                                                                 \
    epi_slice<LINEAR, 0, KB / 2, KB & 1>(acc0, c, pk, vmax);                                     \
    wg_wait<0>();                                                                                \
    if (KB + K1_STAGES < 8 && (threadIdx.x & 127) == 0) {                                        \
      mbar_arrive_cluster(bar_empty + 8 * s, 0);                                                 \
      mbar_arrive_cluster(bar_empty + 8 * s, 1);                                                 \
    }                                                                                            \
  }
  K1_T1_STEP(0) K1_T1_STEP(1) K1_T1_STEP(2) K1_T1_STEP(3) K1_T1_STEP(4) K1_T1_STEP(5) K1_T1_STEP(6) K1_T1_STEP(7)
#undef K1_T1_STEP
  fence_regs(acc1);
  if (threadIdx.x == 0) PROF_T(0, 10);
  epi_slice<LINEAR, 1, 0, 0>(acc1, c, pk, vmax);
  epi_slice<LINEAR, 1, 0, 1>(acc1, c, pk, vmax);
  epi_slice<LINEAR, 1, 1, 0>(acc1, c, pk, vmax);
  epi_slice<LINEAR, 1, 1, 1>(acc1, c, pk, vmax);
  epi_slice<LINEAR, 1, 2, 0>(acc1, c, pk, vmax);
  epi_slice<LINEAR, 1, 2, 1>(acc1, c, pk, vmax);
  epi_slice<LINEAR, 1, 3, 0>(acc1, c, pk, vmax);
  epi_slice<LINEAR, 1, 3, 1>(acc1, c, pk, vmax);
  if (!LINEAR) {
    const uint32_t vm = __reduce_max_sync(0xffffffffu, __float_as_uint(vmax) & 0x7FFFFFFFu);
    if (lane == 0) atomicMax(&s_red[16], vm);
    asm volatile("bar.sync 1, 256;" ::: "memory");
    if (threadIdx.x < 8) {
      *reinterpret_cast<float4*>(&g_nrm[((cp * 8 + threadIdx.x) * 16 + rt) * 4]) =
          make_float4(__uint_as_float(s_red[threadIdx.x * 2]), __uint_as_float(s_red[threadIdx.x * 2 + 1]), __uint_as_float(s_red[16]), 0.f);
    }
  } else {
    asm volatile("bar.sync 1, 256;" ::: "memory");
    const float* red = reinterpret_cast<const float*>(smem_gen + K1_RED_OFF);
    float* dst = g_kvpart + ((size_t)rt * NH + cp * 8) * 384;
#pragma unroll
    for (int i = 0; i < 12; i++) dst[threadIdx.x + i * 256] = red[threadIdx.x + i * 256];
  }
}

__global__ void __launch_bounds__(384, 1)
qkv_gemm_kernel(const __grid_constant__ CUtensorMap mxA, const __grid_constant__ CUtensorMap mxB,
                const __grid_constant__ CUtensorMap mwA, const __grid_constant__ CUtensorMap mwB) {
  extern __shared__ uint8_t smem_raw[];
  const uint32_t sbase = (smem_u32(smem_raw) + 1023) & ~1023u;
  uint8_t* smem_gen = smem_raw + (sbase - smem_u32(smem_raw));
  const uint32_t bar_full = sbase + K1_BAR_OFF;
  const uint32_t bar_empty = bar_full + 8 * K1_STAGES;
  uint32_t* s_red = reinterpret_cast<uint32_t*>(smem_gen + K1_BAR_OFF + 64);

  const int rank = blockIdx.x & 1;
  const int pair = blockIdx.x >> 1;
  const int branch = pair >> 5;
  const int rp = (pair & 31) >> 2;
  const int cp = pair & 3;
  const int rt = rp * 2 + rank;
  const int warp = threadIdx.x >> 5;
  if (threadIdx.x == 0) { PROF_G(0, 30); PROF_T(0, 0); }
  const CUtensorMap* mx = branch ? &mxA : &mxB;
  const CUtensorMap* mw = branch ? &mwA : &mwB;

  if (threadIdx.x == 256) {
    asm volatile("prefetch.tensormap [%0];" ::"l"(mx) : "memory");
    asm volatile("prefetch.tensormap [%0];" ::"l"(mw) : "memory");
    for (int i = 0; i < K1_STAGES; i++) {
      mbar_init(bar_full + 8 * i, 1);
      mbar_init(bar_empty + 8 * i, 4);
    }
    fence_barrier_init();
    fence_proxy_async();
    for (int kb = 0; kb < K1_STAGES; kb++) {
      mbar_expect_tx(bar_full + 8 * kb, 16384 + K1_W_BYTES);
      tma_load_2d(sbase + kb * 16384, mx, kb * 64, rt * 128, bar_full + 8 * kb);
    }
  }
  if (threadIdx.x < 32) s_red[threadIdx.x] = 0;
  for (int i = threadIdx.x; i < 8 * 384; i += 384) reinterpret_cast<float*>(smem_gen + K1_RED_OFF)[i] = 0.f;
  __syncthreads();
  cluster_sync_relaxed();
  if (threadIdx.x == 0) PROF_T(0, 1);

  if (warp >= 8) {
    asm volatile("setmaxnreg.dec.sync.aligned.u32 40;");
    if (threadIdx.x == 256) {
      for (int g = 0; g < 16; g++) {
        const int s = g % K1_STAGES;
        const int kb = g & 7;
        if (g >= K1_STAGES) {
          mbar_wait(bar_empty + 8 * s, ((g / K1_STAGES) - 1) & 1);
          mbar_expect_tx(bar_full + 8 * s, (g < 8 ? 16384 : 0) + K1_W_BYTES);
          if (g < 8) tma_load_2d(sbase + kb * 16384, mx, kb * 64, rt * 128, bar_full + 8 * s);
        }
        const int h0 = cp * 8 + (g >> 3) * 4;
        const uint32_t st = sbase + K1_X_BYTES + s * K1_W_BYTES + rank * 4096;
#pragma unroll
        for (int p = 0; p < 3; p++)
          tma_load_2d_mc(st + p * 8192, mw, p * 512 + h0 * 16, kb * 64 + rank * 32, bar_full + 8 * s, (uint16_t)3);
      }
    }
    __syncwarp();
    cluster_sync_relaxed();
  } else {
    asm volatile("setmaxnreg.inc.sync.aligned.u32 232;");
    if (branch == 0) qkv_consumer<false>(sbase, smem_gen, s_red, cp, rt);
    else qkv_consumer<true>(sbase, smem_gen, s_red, cp, rt);
    if (threadIdx.x == 0) PROF_T(0, 11);
    __syncwarp();
    cluster_sync_relaxed();
    if (threadIdx.x == 0) { PROF_T(0, 12); PROF_G(0, 31); }
  }
}

constexpr int K2_SMEM = KV_HEAD_BYTES + 1024 + 256;

struct ExpC {
  uint32_t k3c00, kmask, seven, c3;
};
__device__ __forceinline__ uint32_t hfma2(uint32_t a, uint32_t b, uint32_t c) {
  uint32_t r;
  asm("fma.rn.f16x2 %0, %1, %2, %3;" : "=r"(r) : "r"(a), "r"(b), "r"(c));
  return r;
}
__device__ __forceinline__ uint32_t exp2_poly_pair(float t0, float t1, const ExpC& c) {
  uint32_t u;
  asm("prmt.b32 %0, %1, %2, 0x5410;" : "=r"(u) : "r"(__float_as_uint(t0)), "r"(__float_as_uint(t1)));
  uint32_t m;
  asm("lop3.b32 %0, %1, 0x03FF03FF, %2, 0xEA;" : "=r"(m) : "r"(u), "r"(c.k3c00));
  uint32_t p = hfma2(m, c.c3, 0x9fe09fe0u);
  p = hfma2(p, m, 0x37a137a1u);
  p = hfma2(p, m, 0x4ab94abau);
  uint32_t mu;
  asm("lop3.b32 %0, %1, 0xFC00FC00, %2, 0xEA;" : "=r"(mu) : "r"(u), "r"(c.kmask));
  uint32_t r;
  asm("{.reg .b32 t; shf.r.wrap.b32 t, %1, %2, 3; add.u32 %0, t, %3;}" : "=r"(r) : "r"(mu), "r"(c.seven), "r"(p));
  return r;
}
__device__ __forceinline__ float gadd(float x, float M, uint32_t g) {
  float r = x;
  asm("{.reg .pred p; setp.ne.b32 p, %2, -1; @p add.f32 %0, %0, %1;}" : "+f"(r) : "f"(M), "r"(g));
  return r;
}
__device__ __forceinline__ float gex2(float x, uint32_t g) {
  float r = x;
  asm("{.reg .pred p; setp.ne.b32 p, %1, -1; @p ex2.approx.ftz.f32 %0, %0;}" : "+f"(r) : "r"(g));
  return r;
}
template <int NPOLY, int NPAIR, int CH, int D>
__device__ __forceinline__ void exp_tile(const float (&s)[2 * NPAIR], uint32_t (&p)[NPAIR], const ExpC& c) {
#pragma unroll
  for (int i = 0; i < NPAIR; i++) {
    const bool isPoly = ((i + 1) * NPOLY / 32) != (i * NPOLY / 32);
    const int ch = i / CH;
    const bool gated = ch >= D;
    int gi = (ch - D) * CH + CH - 1;
    if (gated) {
      while (gi > (ch - D) * CH && !(((gi + 1) * NPOLY / 32) != (gi * NPOLY / 32))) gi--;
    }
    const uint32_t g = gated ? p[gi] : 0;
    if (!isPoly) {
      if (gated) p[i] = pack_bf16(gex2(s[2 * i], g), gex2(s[2 * i + 1], g));
      else p[i] = pack_bf16(ex2f(s[2 * i]), ex2f(s[2 * i + 1]));
    } else {
      if (gated) p[i] = exp2_poly_pair(gadd(s[2 * i], 12329.f, g), gadd(s[2 * i + 1], 12329.f, g), c);
      else p[i] = exp2_poly_pair(s[2 * i] + 12329.f, s[2 * i + 1] + 12329.f, c);
    }
  }
}

__device__ __forceinline__ void store_o(__nv_bfloat16* o, int row0, int head, int lane, const uint32_t (&r)[4]) {
  const int g = lane >> 2, t = lane & 3;
  uint32_t* p0 = reinterpret_cast<uint32_t*>(o + (size_t)(row0 + g) * DM + head * 16) + t;
  uint32_t* p1 = reinterpret_cast<uint32_t*>(o + (size_t)(row0 + g + 8) * DM + head * 16) + t;
  p0[0] = r[0];
  p1[0] = r[1];
  p0[4] = r[2];
  p1[4] = r[3];
}

template <bool SAFE>
__device__ __forceinline__ void attn_step(float (&s)[32], float (&o)[12], float& m0, float& m1, const uint4& qf, uint64_t dKn,
                                          uint64_t dV, const ExpC& ec) {
  uint32_t p[16];
  wg_wait<0>();
  fence_regs(s);
  if (!SAFE) {
    exp_tile<16, 16, 4, 2>(s, p, ec);
  } else {
    fence_regs(o);
    float x0 = s[0], x1 = s[2];
#pragma unroll
    for (int i = 0; i < 8; i++) {
      x0 = fmaxf(x0, fmaxf(s[4 * i], s[4 * i + 1]));
      x1 = fmaxf(x1, fmaxf(s[4 * i + 2], s[4 * i + 3]));
    }
    x0 = fmaxf(x0, __shfl_xor_sync(0xffffffffu, x0, 1));
    x1 = fmaxf(x1, __shfl_xor_sync(0xffffffffu, x1, 1));
    x0 = fmaxf(x0, __shfl_xor_sync(0xffffffffu, x0, 2));
    x1 = fmaxf(x1, __shfl_xor_sync(0xffffffffu, x1, 2));
    const float n0 = fmaxf(m0, x0), n1 = fmaxf(m1, x1);
    const float c0 = ex2f(m0 - n0), c1 = ex2f(m1 - n1);
    m0 = n0;
    m1 = n1;
#pragma unroll
    for (int i = 0; i < 3; i++) {
      o[4 * i] *= c0;
      o[4 * i + 1] *= c0;
      o[4 * i + 2] *= c1;
      o[4 * i + 3] *= c1;
    }
#pragma unroll
    for (int i = 0; i < 8; i++) {
      p[2 * i] = pack_bf16(ex2f(s[4 * i] - n0), ex2f(s[4 * i + 1] - n0));
      p[2 * i + 1] = pack_bf16(ex2f(s[4 * i + 2] - n1), ex2f(s[4 * i + 3] - n1));
    }
  }
  wg_fence();
  wgmma_rs_n64_z(s, qf.x, qf.y, qf.z, qf.w, dKn);
#pragma unroll
  for (int k = 0; k < 4; k++) wgmma_rs_n24_tb(o, p[4 * k], p[4 * k + 1], p[4 * k + 2], p[4 * k + 3], dV + k * 48, 1);
  wg_commit();
}

template <bool SAFE>
__device__ __forceinline__ void attn_tile(uint64_t dK, uint64_t dV, uint32_t bar, const uint4 qf, const ExpC& ec, uint32_t (&outp)[4]) {
  float s[32];
  float o[12];
#pragma unroll
  for (int i = 0; i < 12; i++) asm volatile("mov.f32 %0, 0f00000000;" : "=f"(o[i]));
  float m0 = -INFINITY, m1 = -INFINITY;
  mbar_wait(bar, 0);
  wg_fence();
  wgmma_rs_n64_z(s, qf.x, qf.y, qf.z, qf.w, dK);
  wg_commit();
#pragma unroll 1
  for (int c = 0; c < 4; c++) {
    if (c > 0) mbar_wait(bar + 8 * c, 0);
#pragma unroll 1
    for (int j = 0; j < 4; j++) {
      attn_step<SAFE>(s, o, m0, m1, qf, dK + 128, dV, ec);
      attn_step<SAFE>(s, o, m0, m1, qf, dK + 256, dV + 192, ec);
      dK += 256;
      dV += 384;
    }
  }
  wg_wait<0>();
  fence_regs(o);
  fence_regs(s);
  const float r0 = 1.0f / o[8], r1 = 1.0f / o[10];
  outp[0] = pack_bf16(o[0] * r0, o[1] * r0);
  outp[1] = pack_bf16(o[2] * r1, o[3] * r1);
  outp[2] = pack_bf16(o[4] * r0, o[5] * r0);
  outp[3] = pack_bf16(o[6] * r1, o[7] * r1);
}

__device__ __forceinline__ void linear_attn_cta(uint8_t* smem_raw, uint32_t sbase, const CUtensorMap* mo16, int cta) {
  const int warp = threadIdx.x >> 5, lane = threadIdx.x & 31;
  float* red = reinterpret_cast<float*>(smem_raw + (sbase - smem_u32(smem_raw)) + 131072);
  {
    const float* src = g_kvpart + (size_t)cta * 8 * 384;
    float sum[6];
#pragma unroll
    for (int i = 0; i < 6; i++) sum[i] = 0.f;
#pragma unroll
    for (int r = 0; r < 16; r++) {
#pragma unroll
      for (int i = 0; i < 6; i++) sum[i] += src[(size_t)r * NH * 384 + threadIdx.x + i * 512];
    }
#pragma unroll
    for (int i = 0; i < 6; i++) red[threadIdx.x + i * 512] = round_bf16(sum[i]);
  }
  __syncthreads();
  uint32_t bf[8][6];
  {
    const int g = lane >> 2, t = lane & 3;
#pragma unroll
    for (int h = 0; h < 8; h++) {
#pragma unroll
      for (int f = 0; f < 6; f++) {
        const int blk = f >> 1, half = f & 1;
        const int e = (blk == 2) ? 0 : g;
        const int d = 2 * t + 8 * half;
        const int base = h * 384 + (blk * 4 + half * 2 + (e & 1)) * 32 + (e >> 1);
        bf[h][f] = pack_bf16(red[base + (d & 7) * 4], red[base + ((d + 1) & 7) * 4]);
      }
    }
  }
  const uint32_t stg = sbase + warp * 8192;
#pragma unroll 1
  for (int rb = 0; rb < 8; rb++) {
    const int blk16 = rb * 16 + warp;
    const uint4* qp = g_qfrag + ((size_t)(NH + cta * 8) * 32 + (blk16 >> 2)) * 128 + (blk16 & 3) * 32 + lane;
    uint4 q[8];
#pragma unroll
    for (int h = 0; h < 8; h++) q[h] = qp[h * 32 * 128];
    const uint32_t buf = stg + (rb & 1) * 4096;
    if (rb >= 2) {
      if (lane == 0) asm volatile("cp.async.bulk.wait_group.read 1;" ::: "memory");
      __syncwarp();
    }
#pragma unroll
    for (int h = 0; h < 8; h++) {
      float n0[4] = {0, 0, 0, 0}, n1[4] = {0, 0, 0, 0}, dn[4] = {0, 0, 0, 0};
      hmma(n0, q[h].x, q[h].y, q[h].z, q[h].w, bf[h][0], bf[h][1]);
      hmma(n1, q[h].x, q[h].y, q[h].z, q[h].w, bf[h][2], bf[h][3]);
      hmma(dn, q[h].x, q[h].y, q[h].z, q[h].w, bf[h][4], bf[h][5]);
      const float d0 = round_bf16(round_bf16(dn[0]) + 1e-6f), d1 = round_bf16(round_bf16(dn[2]) + 1e-6f);
      const uint32_t r0 = pack_bf16(__fdividef(round_bf16(n0[0]), d0), __fdividef(round_bf16(n0[1]), d0));
      const uint32_t r1 = pack_bf16(__fdividef(round_bf16(n0[2]), d1), __fdividef(round_bf16(n0[3]), d1));
      const uint32_t r2 = pack_bf16(__fdividef(round_bf16(n1[0]), d0), __fdividef(round_bf16(n1[1]), d0));
      const uint32_t r3 = pack_bf16(__fdividef(round_bf16(n1[2]), d1), __fdividef(round_bf16(n1[3]), d1));
      const int row = lane & 15;
      const int chunk = (h & 3) * 2 + (lane >> 4);
      const uint32_t addr = buf + (h >> 2) * 2048 + row * 128 + ((chunk ^ (row & 7)) << 4);
      asm volatile("stmatrix.sync.aligned.m8n8.x4.shared.b16 [%0], {%1,%2,%3,%4};" ::"r"(addr), "r"(r0), "r"(r1), "r"(r2), "r"(r3)
                   : "memory");
    }
    fence_proxy_async();
    __syncwarp();
    if (lane == 0) {
      tma_store_2d(mo16, buf, cta * 128, blk16 * 16);
      tma_store_2d(mo16, buf + 2048, cta * 128 + 64, blk16 * 16);
      asm volatile("cp.async.bulk.commit_group;" ::: "memory");
    }
  }
  if (lane == 0) asm volatile("cp.async.bulk.wait_group 0;" ::: "memory");
}

__global__ void __launch_bounds__(512, 1) attn_kernel(const __grid_constant__ CUtensorMap mo16) {
  extern __shared__ uint8_t smem_raw[];
  const uint32_t sbase = (smem_u32(smem_raw) + 1023) & ~1023u;
  const uint32_t bar = sbase + KV_HEAD_BYTES;
  if (threadIdx.x == 0) { PROF_G(1, 30); PROF_T(1, 0); }
  if (threadIdx.x == 0) {
    for (int i = 0; i < 4; i++) mbar_init(bar + 8 * i, 1);
    fence_barrier_init();
    fence_proxy_async();
  }
  __syncthreads();
  if (blockIdx.x >= 128) {
    linear_attn_cta(smem_raw, sbase, &mo16, blockIdx.x - 128);
    if (threadIdx.x == 0) { PROF_T(1, 5); PROF_G(1, 31); }
    return;
  }
  const int head = blockIdx.x >> 2, qb = blockIdx.x & 3;
  if (threadIdx.x == 0) {
    const uint8_t* img = reinterpret_cast<const uint8_t*>(g_kv) + (size_t)head * KV_HEAD_BYTES;
    mbar_expect_tx(bar, 32768 + 24576);
    bulk_load(sbase, img, 32768, bar);
    bulk_load(sbase + KV_K_BYTES, img + KV_K_BYTES, 24576, bar);
    for (int i = 1; i < 4; i++) {
      mbar_expect_tx(bar + 8 * i, (i < 3 ? 16384 : 0) + 24576);
      if (i < 3) bulk_load(sbase + (i + 1) * 16384, img + (i + 1) * 16384, 16384, bar + 8 * i);
      bulk_load(sbase + KV_K_BYTES + i * 24576, img + KV_K_BYTES + i * 24576, 24576, bar + 8 * i);
    }
  }
  const int lane = threadIdx.x & 31;
  bool safe_path;
  {
    float4 n = make_float4(0.f, 0.f, 0.f, 0.f);
    if (lane < 16) n = *reinterpret_cast<const float4*>(&g_nrm[(head * 16 + lane) * 4]);
    uint32_t qm = ((lane >> 2) == qb) ? __float_as_uint(n.x) : 0u;
    qm = __reduce_max_sync(0xffffffffu, qm);
    const uint32_t km = __reduce_max_sync(0xffffffffu, __float_as_uint(n.y));
    const uint32_t vm = __reduce_max_sync(0xffffffffu, __float_as_uint(n.z));
    const float b2 = __uint_as_float(qm) * (QSCALE * QSCALE) * __uint_as_float(km) * 1.02f;
    const float vmax = __uint_as_float(vm);
    const bool ok = (b2 <= 21.5f * 21.5f) && (vmax <= 1.0e24f) && (vmax >= 1.0e-18f || vmax == 0.f);
    safe_path = !ok;
  }
  const int wg = threadIdx.x >> 7, warp = (threadIdx.x >> 5) & 3;
  uint32_t zero;
  asm volatile("mov.u32 %0, %%smid;" : "=r"(zero));
  zero >>= 16;
  const ExpC ec{0x3C003C00u + zero, 0x00070000u + zero, 7u + zero, 0x2cfd2cfdu + zero};
  const uint64_t dK = mkdesc(sbase, 128, 256, 0);
  const uint64_t dV = mkdesc(sbase + KV_K_BYTES, 384, 128, 0);
#pragma unroll 1
  for (int t = 0; t < 2; t++) {
    const int tile64 = qb * 8 + wg * 2 + t;
    const uint4 qf = g_qfrag[(head * 32 + tile64) * 128 + (threadIdx.x & 127)];
    uint32_t r[4];
    if (threadIdx.x == 0) PROF_T(1, 1 + t);
    if (!safe_path) attn_tile<false>(dK, dV, bar, qf, ec, r);
    else attn_tile<true>(dK, dV, bar, qf, ec, r);
    store_o(g_o + (size_t)S_LEN * DM, tile64 * 64 + warp * 16, head, lane, r);
  }
  if (threadIdx.x == 0) { PROF_T(1, 5); PROF_G(1, 31); }
}

constexpr int K3_STAGES = 6;
constexpr int K3_STAGE_BYTES = 16384 + 2 * 8192;
constexpr int K3_SMEM = K3_STAGES * K3_STAGE_BYTES + 1024 + 256;

__global__ void __launch_bounds__(288, 1)
out_gemm_kernel(const __grid_constant__ CUtensorMap mo, const __grid_constant__ CUtensorMap mwA,
                const __grid_constant__ CUtensorMap mwB, const __grid_constant__ CUtensorMap mout) {
  extern __shared__ uint8_t smem_raw[];
  const uint32_t sbase = (smem_u32(smem_raw) + 1023) & ~1023u;
  const uint32_t bar_full = sbase + K3_STAGES * K3_STAGE_BYTES;
  const uint32_t bar_empty = bar_full + 8 * K3_STAGES;
  const int branch = blockIdx.x >> 6;
  const int rt = (blockIdx.x & 63) >> 2;
  const int ct = blockIdx.x & 3;
  const int warp = threadIdx.x >> 5;
  if (threadIdx.x == 0) { PROF_G(2, 30); PROF_T(2, 0); }
  if (threadIdx.x == 0) {
    for (int i = 0; i < K3_STAGES; i++) {
      mbar_init(bar_full + 8 * i, 1);
      mbar_init(bar_empty + 8 * i, 2);
    }
    fence_barrier_init();
  }
  __syncthreads();
  if (warp == 8) {
    if ((threadIdx.x & 31) == 0) {
      const CUtensorMap* mw = branch ? &mwB : &mwA;
      for (int kb = 0; kb < 8; kb++) {
        const int s = kb % K3_STAGES;
        if (kb >= K3_STAGES) mbar_wait(bar_empty + 8 * s, ((kb / K3_STAGES) - 1) & 1);
        const uint32_t st = sbase + s * K3_STAGE_BYTES;
        mbar_expect_tx(bar_full + 8 * s, K3_STAGE_BYTES);
        tma_load_2d(st, &mo, kb * 64, branch * S_LEN + rt * 128, bar_full + 8 * s);
        tma_load_2d(st + 16384, mw, ct * 128, kb * 64, bar_full + 8 * s);
        tma_load_2d(st + 16384 + 8192, mw, ct * 128 + 64, kb * 64, bar_full + 8 * s);
      }
    }
  } else {
    const int wg = warp >> 2;
    float acc[64];
    for (int kb = 0; kb < 8; kb++) {
      const int s = kb % K3_STAGES;
      mbar_wait(bar_full + 8 * s, (kb / K3_STAGES) & 1);
      if (threadIdx.x == 0) PROF_T(2, 2 + kb);
      const uint32_t st = sbase + s * K3_STAGE_BYTES;
      const uint64_t dA = mkdesc(st + wg * 8192, 16, 1024, 1);
      const uint64_t dB = mkdesc(st + 16384, 8192, 1024, 1);
      wg_fence();
#pragma unroll
      for (int k = 0; k < 4; k++) wgmma_ss_n128_tb(acc, dA + k * 2, dB + k * 128, (kb | k) != 0);
      wg_commit();
      if (kb > 0) {
        wg_wait<1>();
        if ((threadIdx.x & 127) == 0) mbar_arrive(bar_empty + 8 * ((kb - 1) % K3_STAGES));
      }
    }
    wg_wait<0>();
    fence_regs(acc);
    if (threadIdx.x == 0) PROF_T(2, 10);
    asm volatile("bar.sync 1, 256;" ::: "memory");
    const int lane = threadIdx.x & 31;
    const int rloc = wg * 64 + (warp & 3) * 16 + (lane & 15);
#pragma unroll
    for (int c16 = 0; c16 < 8; c16++) {
      const float* a = &acc[c16 * 8];
      const uint32_t r0 = pack_bf16(a[0], a[1]), r1 = pack_bf16(a[2], a[3]), r2 = pack_bf16(a[4], a[5]), r3 = pack_bf16(a[6], a[7]);
      const int chunk = (c16 & 3) * 2 + (lane >> 4);
      const uint32_t addr = sbase + (c16 >> 2) * 16384 + rloc * 128 + ((chunk ^ (rloc & 7)) << 4);
      asm volatile("stmatrix.sync.aligned.m8n8.x4.shared.b16 [%0], {%1,%2,%3,%4};" ::"r"(addr), "r"(r0), "r"(r1), "r"(r2), "r"(r3)
                   : "memory");
    }
    fence_proxy_async();
    asm volatile("bar.sync 1, 256;" ::: "memory");
    if (threadIdx.x == 0) {
      tma_store_2d(&mout, sbase, branch * DM + ct * 128, rt * 128);
      tma_store_2d(&mout, sbase + 16384, branch * DM + ct * 128 + 64, rt * 128);
      asm volatile("cp.async.bulk.commit_group;" ::: "memory");
      asm volatile("cp.async.bulk.wait_group 0;" ::: "memory");
      PROF_T(2, 12); PROF_G(2, 31);
    }
  }
}

typedef CUresult (*EncodeFn)(CUtensorMap*, CUtensorMapDataType, cuuint32_t, void*, const cuuint64_t*, const cuuint64_t*,
                             const cuuint32_t*, const cuuint32_t*, CUtensorMapInterleave, CUtensorMapSwizzle,
                             CUtensorMapL2promotion, CUtensorMapFloatOOBfill);

void make_map(EncodeFn enc, CUtensorMap* m, const void* ptr, uint64_t inner, uint64_t outer, uint32_t box_inner, uint32_t box_outer) {
  cuuint64_t dims[2] = {inner, outer};
  cuuint64_t strides[1] = {inner * 2};
  cuuint32_t box[2] = {box_inner, box_outer};
  cuuint32_t es[2] = {1, 1};
  enc(m, CU_TENSOR_MAP_DATA_TYPE_BFLOAT16, 2, const_cast<void*>(ptr), dims, strides, box, es, CU_TENSOR_MAP_INTERLEAVE_NONE,
      CU_TENSOR_MAP_SWIZZLE_128B, CU_TENSOR_MAP_L2_PROMOTION_L2_256B, CU_TENSOR_MAP_FLOAT_OOB_FILL_NONE);
}

struct HostState {
  bool init;
  const void* key[7];
  CUtensorMap mxA, mxB, mwA, mwB, mo, mo16, mwoA, mwoB, mout;
};
HostState g_hs;

}

extern "C" void kernel_launch(void* const* d_in, const int* in_sizes, int n_in, void* d_out, int out_size) {
  (void)in_sizes; (void)n_in; (void)out_size;
  HostState& hs = g_hs;
  bool same = hs.init && hs.key[6] == d_out;
  for (int i = 0; i < 6 && same; i++) same = hs.key[i] == d_in[i];
  if (!same) {
    void* fn = nullptr;
    cudaDriverEntryPointQueryResult qr;
    cudaGetDriverEntryPoint("cuTensorMapEncodeTiled", &fn, cudaEnableDefault, &qr);
    EncodeFn enc = (EncodeFn)fn;
    void* go = nullptr;
    cudaGetSymbolAddress(&go, g_o);
    make_map(enc, &hs.mxA, d_in[0], 512, 2048, 64, 128);
    make_map(enc, &hs.mwA, d_in[1], 1536, 512, 64, 32);
    make_map(enc, &hs.mwoA, d_in[2], 512, 512, 64, 64);
    make_map(enc, &hs.mxB, d_in[3], 512, 2048, 64, 128);
    make_map(enc, &hs.mwB, d_in[4], 1536, 512, 64, 32);
    make_map(enc, &hs.mwoB, d_in[5], 512, 512, 64, 64);
    make_map(enc, &hs.mo, go, 512, 4096, 64, 128);
    make_map(enc, &hs.mo16, go, 512, 4096, 64, 16);
    make_map(enc, &hs.mout, d_out, 1024, 2048, 64, 128);
    cudaFuncSetAttribute(qkv_gemm_kernel, cudaFuncAttributeMaxDynamicSharedMemorySize, K1_SMEM);
    cudaFuncSetAttribute(attn_kernel, cudaFuncAttributeMaxDynamicSharedMemorySize, K2_SMEM);
    cudaFuncSetAttribute(out_gemm_kernel, cudaFuncAttributeMaxDynamicSharedMemorySize, K3_SMEM);
    for (int i = 0; i < 6; i++) hs.key[i] = d_in[i];
    hs.key[6] = d_out;
    hs.init = true;
  }
  cudaStream_t st = cudaStreamPerThread;
  {
    cudaLaunchConfig_t cfg = {};
    cfg.gridDim = dim3(128);
    cfg.blockDim = dim3(384);
    cfg.dynamicSmemBytes = K1_SMEM;
    cfg.stream = st;
    cudaLaunchAttribute at[1];
    at[0].id = cudaLaunchAttributeClusterDimension;
    at[0].val.clusterDim.x = 2;
    at[0].val.clusterDim.y = 1;
    at[0].val.clusterDim.z = 1;
    cfg.attrs = at;
    cfg.numAttrs = 1;
    cudaLaunchKernelEx(&cfg, qkv_gemm_kernel, hs.mxA, hs.mxB, hs.mwA, hs.mwB);
  }
  attn_kernel<<<132, 512, K2_SMEM, st>>>(hs.mo16);
  out_gemm_kernel<<<128, 288, K3_SMEM, st>>>(hs.mo, hs.mwoA, hs.mwoB, hs.mout);
}
```

```cpp
#include <cuda_runtime.h>
#include <cuda_bf16.h>
#include <cuda.h>
#include <stdint.h>

namespace {

constexpr int S_LEN = 2048;
constexpr int DM = 512;
constexpr int NH = 32;

constexpr int KV_K_BYTES = 65536;
constexpr int KV_HEAD_BYTES = KV_K_BYTES + 98304;
__device__ uint4 g_qfrag[2 * NH * 32 * 128];
__device__ uint4 g_kv[NH * KV_HEAD_BYTES / 16];
__device__ float g_kvpart[16 * NH * 384];
__device__ float g_nrm[NH * 16 * 4];
__device__ __nv_bfloat16 g_o[2 * S_LEN * DM];

#define PROF_T(k, i) do {} while (0)
#define PROF_G(k, i) do {} while (0)
__device__ __forceinline__ uint32_t smem_u32(const void* p) { return (uint32_t)__cvta_generic_to_shared(p); }
__device__ __forceinline__ void mbar_init(uint32_t bar, int cnt) {
  asm volatile("mbarrier.init.shared::cta.b64 [%0], %1;" ::"r"(bar), "r"(cnt) : "memory");
}
__device__ __forceinline__ void mbar_expect_tx(uint32_t bar, uint32_t bytes) {
  asm volatile("mbarrier.arrive.expect_tx.shared::cta.b64 _, [%0], %1;" ::"r"(bar), "r"(bytes) : "memory");
}
__device__ __forceinline__ void mbar_arrive(uint32_t bar) {
  asm volatile("mbarrier.arrive.shared::cta.b64 _, [%0];" ::"r"(bar) : "memory");
}
__device__ __forceinline__ void mbar_arrive_cluster(uint32_t bar, uint32_t cta) {
  asm volatile(
      "{\n.reg .b32 ra;\nmapa.shared::cluster.u32 ra, %0, %1;\n"
      "mbarrier.arrive.shared::cluster.b64 _, [ra];\n}" ::"r"(bar), "r"(cta) : "memory");
}
__device__ __forceinline__ void mbar_wait(uint32_t bar, uint32_t parity) {
  asm volatile(
      "{\n.reg .pred p;\n"
      "WAIT_LOOP:\n"
      "mbarrier.try_wait.parity.shared::cta.b64 p, [%0], %1, 0x989680;\n"
      "@p bra WAIT_DONE;\n"
      "bra WAIT_LOOP;\n"
      "WAIT_DONE:\n}" ::"r"(bar), "r"(parity) : "memory");
}
__device__ __forceinline__ void mbar_wait_cluster(uint32_t bar, uint32_t parity) {
  asm volatile(
      "{\n.reg .pred p;\n"
      "WAIT_LOOP:\n"
      "mbarrier.try_wait.parity.acquire.cluster.shared::cta.b64 p, [%0], %1, 0x989680;\n"
      "@p bra WAIT_DONE;\n"
      "bra WAIT_LOOP;\n"
      "WAIT_DONE:\n}" ::"r"(bar), "r"(parity) : "memory");
}
__device__ __forceinline__ void fence_barrier_init() {
  asm volatile("fence.mbarrier_init.release.cluster;" ::: "memory");
}
__device__ __forceinline__ void fence_proxy_async() { asm volatile("fence.proxy.async.shared::cta;" ::: "memory"); }
__device__ __forceinline__ void cluster_sync_relaxed() {
  asm volatile("barrier.cluster.arrive.relaxed.aligned;\nbarrier.cluster.wait.aligned;" ::: "memory");
}
__device__ __forceinline__ void tma_load_2d(uint32_t dst, const CUtensorMap* m, int x, int y, uint32_t bar) {
  asm volatile(
      "cp.async.bulk.tensor.2d.shared::cluster.global.mbarrier::complete_tx::bytes [%0], [%1, {%3, %4}], [%2];" ::"r"(dst),
      "l"(m), "r"(bar), "r"(x), "r"(y)
      : "memory");
}
__device__ __forceinline__ void tma_load_2d_mc(uint32_t dst, const CUtensorMap* m, int x, int y, uint32_t bar, uint16_t mask) {
  asm volatile(
      "cp.async.bulk.tensor.2d.shared::cluster.global.mbarrier::complete_tx::bytes.multicast::cluster [%0], [%1, {%3, %4}], "
      "[%2], %5;" ::"r"(dst),
      "l"(m), "r"(bar), "r"(x), "r"(y), "h"(mask)
      : "memory");
}
__device__ __forceinline__ void tma_store_2d(const CUtensorMap* m, uint32_t src, int x, int y) {
  asm volatile("cp.async.bulk.tensor.2d.global.shared::cta.bulk_group [%0, {%2, %3}], [%1];" ::"l"(m), "r"(src), "r"(x),
               "r"(y)
               : "memory");
}
__device__ __forceinline__ void bulk_load(uint32_t dst, const void* src, uint32_t bytes, uint32_t bar) {
  asm volatile("cp.async.bulk.shared::cluster.global.mbarrier::complete_tx::bytes [%0], [%1], %2, [%3];" ::"r"(dst),
               "l"(src), "r"(bytes), "r"(bar)
               : "memory");
}
__device__ __forceinline__ void wg_fence() { asm volatile("wgmma.fence.sync.aligned;" ::: "memory"); }
__device__ __forceinline__ void wg_commit() { asm volatile("wgmma.commit_group.sync.aligned;" ::: "memory"); }
template <int N>
__device__ __forceinline__ void wg_wait() {
  asm volatile("wgmma.wait_group.sync.aligned %0;" ::"n"(N) : "memory");
}
template <int M>
__device__ __forceinline__ void fence_regs(float (&r)[M]) {
#pragma unroll
  for (int i = 0; i < M; i++) asm volatile("" : "+f"(r[i])::"memory");
}
__device__ __forceinline__ uint64_t mkdesc(uint32_t addr, uint32_t lbo, uint32_t sbo, uint32_t layout) {
  return (uint64_t)((addr & 0x3FFFF) >> 4) | ((uint64_t)(lbo >> 4) << 16) | ((uint64_t)(sbo >> 4) << 32) |
         ((uint64_t)layout << 62);
}
__device__ __forceinline__ uint32_t pack_bf16(float lo, float hi) {
  uint32_t r;
  asm("cvt.rn.bf16x2.f32 %0, %1, %2;" : "=r"(r) : "f"(hi), "f"(lo));
  return r;
}
__device__ __forceinline__ float bf_lo(uint32_t v) { return __uint_as_float(v << 16); }
__device__ __forceinline__ float bf_hi(uint32_t v) { return __uint_as_float(v & 0xFFFF0000u); }
__device__ __forceinline__ float round_bf16(float x) { return bf_lo(pack_bf16(x, 0.f)); }
__device__ __forceinline__ float ex2f(float x) {
  float y;
  asm("ex2.approx.ftz.f32 %0, %1;" : "=f"(y) : "f"(x));
  return y;
}

__device__ __forceinline__ void wgmma_rs_n24_tb(float (&d)[12], uint32_t a0, uint32_t a1, uint32_t a2, uint32_t a3, uint64_t descB, int scaleD) {
  asm volatile("{\n.reg .pred p;\nsetp.ne.b32 p, %17, 0;\n"
    "wgmma.mma_async.sync.aligned.m64n24k16.f32.bf16.bf16 "
    "{%0, %1, %2, %3, %4, %5, %6, %7, %8, %9, %10, %11}, {%12, %13, %14, %15}, %16, p, 1, 1, 1;\n}\n"
    : "+f"(d[0]), "+f"(d[1]), "+f"(d[2]), "+f"(d[3]), "+f"(d[4]), "+f"(d[5]), "+f"(d[6]), "+f"(d[7]),
      "+f"(d[8]), "+f"(d[9]), "+f"(d[10]), "+f"(d[11])
    : "r"(a0), "r"(a1), "r"(a2), "r"(a3), "l"(descB), "r"(scaleD));
}
__device__ __forceinline__ void wgmma_rs_n64_z(float (&d)[32], uint32_t a0, uint32_t a1, uint32_t a2, uint32_t a3, uint64_t descB) {
  asm volatile("{\n.reg .pred p;\nsetp.ne.b32 p, %37, 0;\n"
    "wgmma.mma_async.sync.aligned.m64n64k16.f32.bf16.bf16 "
    "{%0, %1, %2, %3, %4, %5, %6, %7, %8, %9, %10, %11, %12, %13, %14, %15, %16, %17, %18, %19, %20, %21, %22, %23, %24, %25, %26, %27, %28, %29, %30, %31}, {%32, %33, %34, %35}, %36, p, 1, 1, 0;\n}\n"
    : "=f"(d[0]), "=f"(d[1]), "=f"(d[2]), "=f"(d[3]), "=f"(d[4]), "=f"(d[5]), "=f"(d[6]), "=f"(d[7]),
      "=f"(d[8]), "=f"(d[9]), "=f"(d[10]), "=f"(d[11]), "=f"(d[12]), "=f"(d[13]), "=f"(d[14]), "=f"(d[15]),
      "=f"(d[16]), "=f"(d[17]), "=f"(d[18]), "=f"(d[19]), "=f"(d[20]), "=f"(d[21]), "=f"(d[22]), "=f"(d[23]),
      "=f"(d[24]), "=f"(d[25]), "=f"(d[26]), "=f"(d[27]), "=f"(d[28]), "=f"(d[29]), "=f"(d[30]), "=f"(d[31])
    : "r"(a0), "r"(a1), "r"(a2), "r"(a3), "l"(descB), "n"(0));
}
__device__ __forceinline__ void wgmma_ss_n128_tb(float (&d)[64], uint64_t descA, uint64_t descB, int scaleD) {
  asm volatile("{\n.reg .pred p;\nsetp.ne.b32 p, %66, 0;\n"
    "wgmma.mma_async.sync.aligned.m64n128k16.f32.bf16.bf16 "
    "{%0, %1, %2, %3, %4, %5, %6, %7, %8, %9, %10, %11, %12, %13, %14, %15, %16, %17, %18, %19, %20, %21, %22, %23, %24, %25, %26, %27, %28, %29, %30, %31, %32, %33, %34, %35, %36, %37, %38, %39, %40, %41, %42, %43, %44, %45, %46, %47, %48, %49, %50, %51, %52, %53, %54, %55, %56, %57, %58, %59, %60, %61, %62, %63}, %64, %65, p, 1, 1, 0, 1;\n}\n"
    : "+f"(d[0]), "+f"(d[1]), "+f"(d[2]), "+f"(d[3]), "+f"(d[4]), "+f"(d[5]), "+f"(d[6]), "+f"(d[7]),
      "+f"(d[8]), "+f"(d[9]), "+f"(d[10]), "+f"(d[11]), "+f"(d[12]), "+f"(d[13]), "+f"(d[14]), "+f"(d[15]),
      "+f"(d[16]), "+f"(d[17]), "+f"(d[18]), "+f"(d[19]), "+f"(d[20]), "+f"(d[21]), "+f"(d[22]), "+f"(d[23]),
      "+f"(d[24]), "+f"(d[25]), "+f"(d[26]), "+f"(d[27]), "+f"(d[28]), "+f"(d[29]), "+f"(d[30]), "+f"(d[31]),
      "+f"(d[32]), "+f"(d[33]), "+f"(d[34]), "+f"(d[35]), "+f"(d[36]), "+f"(d[37]), "+f"(d[38]), "+f"(d[39]),
      "+f"(d[40]), "+f"(d[41]), "+f"(d[42]), "+f"(d[43]), "+f"(d[44]), "+f"(d[45]), "+f"(d[46]), "+f"(d[47]),
      "+f"(d[48]), "+f"(d[49]), "+f"(d[50]), "+f"(d[51]), "+f"(d[52]), "+f"(d[53]), "+f"(d[54]), "+f"(d[55]),
      "+f"(d[56]), "+f"(d[57]), "+f"(d[58]), "+f"(d[59]), "+f"(d[60]), "+f"(d[61]), "+f"(d[62]), "+f"(d[63])
    : "l"(descA), "l"(descB), "r"(scaleD));
}
__device__ __forceinline__ void wgmma_ss_n192_tb(float (&d)[96], uint64_t descA, uint64_t descB, int scaleD) {
  asm volatile("{\n.reg .pred p;\nsetp.ne.b32 p, %98, 0;\n"
    "wgmma.mma_async.sync.aligned.m64n192k16.f32.bf16.bf16 "
    "{%0, %1, %2, %3, %4, %5, %6, %7, %8, %9, %10, %11, %12, %13, %14, %15, %16, %17, %18, %19, %20, %21, %22, %23, %24, %25, %26, %27, %28, %29, %30, %31, %32, %33, %34, %35, %36, %37, %38, %39, %40, %41, %42, %43, %44, %45, %46, %47, %48, %49, %50, %51, %52, %53, %54, %55, %56, %57, %58, %59, %60, %61, %62, %63, %64, %65, %66, %67, %68, %69, %70, %71, %72, %73, %74, %75, %76, %77, %78, %79, %80, %81, %82, %83, %84, %85, %86, %87, %88, %89, %90, %91, %92, %93, %94, %95}, %96, %97, p, 1, 1, 0, 1;\n}\n"
    : "+f"(d[0]), "+f"(d[1]), "+f"(d[2]), "+f"(d[3]), "+f"(d[4]), "+f"(d[5]), "+f"(d[6]), "+f"(d[7]),
      "+f"(d[8]), "+f"(d[9]), "+f"(d[10]), "+f"(d[11]), "+f"(d[12]), "+f"(d[13]), "+f"(d[14]), "+f"(d[15]),
      "+f"(d[16]), "+f"(d[17]), "+f"(d[18]), "+f"(d[19]), "+f"(d[20]), "+f"(d[21]), "+f"(d[22]), "+f"(d[23]),
      "+f"(d[24]), "+f"(d[25]), "+f"(d[26]), "+f"(d[27]), "+f"(d[28]), "+f"(d[29]), "+f"(d[30]), "+f"(d[31]),
      "+f"(d[32]), "+f"(d[33]), "+f"(d[34]), "+f"(d[35]), "+f"(d[36]), "+f"(d[37]), "+f"(d[38]), "+f"(d[39]),
      "+f"(d[40]), "+f"(d[41]), "+f"(d[42]), "+f"(d[43]), "+f"(d[44]), "+f"(d[45]), "+f"(d[46]), "+f"(d[47]),
      "+f"(d[48]), "+f"(d[49]), "+f"(d[50]), "+f"(d[51]), "+f"(d[52]), "+f"(d[53]), "+f"(d[54]), "+f"(d[55]),
      "+f"(d[56]), "+f"(d[57]), "+f"(d[58]), "+f"(d[59]), "+f"(d[60]), "+f"(d[61]), "+f"(d[62]), "+f"(d[63]),
      "+f"(d[64]), "+f"(d[65]), "+f"(d[66]), "+f"(d[67]), "+f"(d[68]), "+f"(d[69]), "+f"(d[70]), "+f"(d[71]),
      "+f"(d[72]), "+f"(d[73]), "+f"(d[74]), "+f"(d[75]), "+f"(d[76]), "+f"(d[77]), "+f"(d[78]), "+f"(d[79]),
      "+f"(d[80]), "+f"(d[81]), "+f"(d[82]), "+f"(d[83]), "+f"(d[84]), "+f"(d[85]), "+f"(d[86]), "+f"(d[87]),
      "+f"(d[88]), "+f"(d[89]), "+f"(d[90]), "+f"(d[91]), "+f"(d[92]), "+f"(d[93]), "+f"(d[94]), "+f"(d[95])
    : "l"(descA), "l"(descB), "r"(scaleD));
}

__device__ __forceinline__ void ldsm4t(uint32_t (&b)[4], uint32_t addr) {
  asm volatile("ldmatrix.sync.aligned.m8n8.x4.trans.shared.b16 {%0,%1,%2,%3}, [%4];"
               : "=r"(b[0]), "=r"(b[1]), "=r"(b[2]), "=r"(b[3])
               : "r"(addr));
}
__device__ __forceinline__ void hmma(float (&c)[4], uint32_t a0, uint32_t a1, uint32_t a2, uint32_t a3, uint32_t b0, uint32_t b1) {
  asm("mma.sync.aligned.m16n8k16.row.col.f32.bf16.bf16.f32 {%0,%1,%2,%3}, {%4,%5,%6,%7}, {%8,%9}, {%0,%1,%2,%3};"
      : "+f"(c[0]), "+f"(c[1]), "+f"(c[2]), "+f"(c[3])
      : "r"(a0), "r"(a1), "r"(a2), "r"(a3), "r"(b0), "r"(b1));
}

__device__ __forceinline__ uint32_t movm(uint32_t a) {
  uint32_t d;
  asm volatile("movmatrix.sync.aligned.m8n8.trans.b16 %0, %1;" : "=r"(d) : "r"(a));
  return d;
}

constexpr int K1_STAGES = 4;
constexpr int K1_W_BYTES = 3 * 8192;
constexpr int K1_X_BYTES = 8 * 16384;
constexpr int K1_BAR_OFF = K1_X_BYTES + K1_STAGES * K1_W_BYTES;
constexpr int K1_SMEM = K1_BAR_OFF + 192 + 1024;
constexpr float QSCALE = 0.25f * 1.4426950408889634f;

__device__ __forceinline__ uint32_t phi2(uint32_t t2) {
  uint32_t a2, mask, r2, o2;
  asm("add.rn.bf16x2 %0, %1, %2;" : "=r"(a2) : "r"(t2), "r"(0x3F803F80u));
  const uint32_t e2 = pack_bf16(ex2f(bf_lo(t2) * 1.4426950408889634f), ex2f(bf_hi(t2) * 1.4426950408889634f));
  asm("set.gt.u32.bf16x2 %0, %1, %2;" : "=r"(mask) : "r"(t2), "r"(0u));
  r2 = (a2 & mask) | (e2 & ~mask);
  asm("add.rn.bf16x2 %0, %1, %2;" : "=r"(o2) : "r"(r2), "r"(0x35863586u));
  return o2;
}

#define K1_SLOT_KB(h) ((h) < 4 ? 2 * (h) : 2 * ((h) - 4) + 1)
struct EpiCtx {
  uint4* qf;
  uint32_t* kp;
  uint32_t* vp;
  uint32_t* s_red;
  float* red;
  int lane;
};

template <bool LINEAR, int J, int HH, int PART>
__device__ __forceinline__ void epi_slice(const float (&acc)[96], const EpiCtx& c, uint32_t (&pk)[4], float& vmax) {
  constexpr int h = J * 4 + HH;
  const float* a = &acc[HH * 8];
  const float* k = &acc[32 + HH * 8];
  const float* v = &acc[64 + HH * 8];
  if (!LINEAR) {
    if (PART == 0) {
      c.qf[h * 32 * 128] = make_uint4(pack_bf16(a[0] * QSCALE, a[1] * QSCALE), pack_bf16(a[2] * QSCALE, a[3] * QSCALE),
                                      pack_bf16(a[4] * QSCALE, a[5] * QSCALE), pack_bf16(a[6] * QSCALE, a[7] * QSCALE));
      uint32_t* kh = c.kp + h * (KV_HEAD_BYTES / 4);
      kh[0] = pack_bf16(k[0], k[1]);
      kh[64] = pack_bf16(k[2], k[3]);
      kh[32] = pack_bf16(k[4], k[5]);
      kh[96] = pack_bf16(k[6], k[7]);
      float q0 = a[0] * a[0] + a[1] * a[1] + a[4] * a[4] + a[5] * a[5];
      float q1 = a[2] * a[2] + a[3] * a[3] + a[6] * a[6] + a[7] * a[7];
      float k0 = k[0] * k[0] + k[1] * k[1] + k[4] * k[4] + k[5] * k[5];
      float k1 = k[2] * k[2] + k[3] * k[3] + k[6] * k[6] + k[7] * k[7];
#pragma unroll
      for (int o = 1; o <= 2; o <<= 1) {
        q0 += __shfl_xor_sync(0xffffffffu, q0, o);
        q1 += __shfl_xor_sync(0xffffffffu, q1, o);
        k0 += __shfl_xor_sync(0xffffffffu, k0, o);
        k1 += __shfl_xor_sync(0xffffffffu, k1, o);
      }
      const uint32_t qm = __reduce_max_sync(0xffffffffu, max(__float_as_uint(q0) & 0x7FFFFFFFu, __float_as_uint(q1) & 0x7FFFFFFFu));
      const uint32_t km = __reduce_max_sync(0xffffffffu, max(__float_as_uint(k0) & 0x7FFFFFFFu, __float_as_uint(k1) & 0x7FFFFFFFu));
      if (c.lane == 0) {
        atomicMax(&c.s_red[h * 2 + 0], qm);
        atomicMax(&c.s_red[h * 2 + 1], km);
      }
    } else {
      uint32_t* vh = c.vp + h * (KV_HEAD_BYTES / 4);
      vh[0] = pack_bf16(v[0], v[1]);
      vh[96] = pack_bf16(v[2], v[3]);
      vh[32] = pack_bf16(v[4], v[5]);
      vh[128] = pack_bf16(v[6], v[7]);
      vh[64] = 0x3F803F80u;
      vh[160] = 0x3F803F80u;
#pragma unroll
      for (int i = 0; i < 8; i++) asm("max.NaN.f32 %0, %0, %1;" : "+f"(vmax) : "f"(fabsf(v[i])));
    }
  } else {
    if (PART == 0) {
      c.qf[h * 32 * 128] = make_uint4(phi2(pack_bf16(a[0], a[1])), phi2(pack_bf16(a[2], a[3])), phi2(pack_bf16(a[4], a[5])),
                                      phi2(pack_bf16(a[6], a[7])));
      pk[0] = movm(phi2(pack_bf16(k[0], k[1])));
      pk[2] = movm(phi2(pack_bf16(k[2], k[3])));
      pk[1] = movm(phi2(pack_bf16(k[4], k[5])));
      pk[3] = movm(phi2(pack_bf16(k[6], k[7])));
    } else {
      const uint32_t b0 = movm(pack_bf16(v[0], v[1]));
      const uint32_t b1 = movm(pack_bf16(v[2], v[3]));
      const uint32_t b2 = movm(pack_bf16(v[4], v[5]));
      const uint32_t b3 = movm(pack_bf16(v[6], v[7]));
      float c0[4] = {0, 0, 0, 0}, c1[4] = {0, 0, 0, 0}, c2[4] = {0, 0, 0, 0};
      hmma(c0, pk[0], pk[1], pk[2], pk[3], b0, b1);
      hmma(c1, pk[0], pk[1], pk[2], pk[3], b2, b3);
      hmma(c2, pk[0], pk[1], pk[2], pk[3], 0x3F803F80u, 0x3F803F80u);
      float* slot = c.red + K1_SLOT_KB(h) * 4096;
#pragma unroll
      for (int i = 0; i < 4; i++) {
        slot[i * 32] = c0[i];
        slot[(4 + i) * 32] = c1[i];
        slot[(8 + i) * 32] = c2[i];
      }
    }
  }
}

template <bool LINEAR>
__device__ __forceinline__ void qkv_consumer(uint32_t sbase, uint8_t* smem_gen, uint32_t* s_red, int cp, int rt) {
  const uint32_t bar_full = sbase + K1_BAR_OFF;
  const uint32_t bar_empty = bar_full + 8 * K1_STAGES;
  const int warp = threadIdx.x >> 5;
  const int wg = warp >> 2;
  const int lane = threadIdx.x & 31;
  float acc0[96], acc1[96];
#pragma unroll 1
  for (int kb = 0; kb < 8; kb++) {
    const int s = kb % K1_STAGES;
    mbar_wait(bar_full + 8 * s, (kb / K1_STAGES) & 1);
    if (threadIdx.x == 0) PROF_T(0, 2 + (kb >> 1));
    const uint64_t dA = mkdesc(sbase + kb * 16384 + wg * 8192, 16, 1024, 1);
    const uint64_t dB = mkdesc(sbase + K1_X_BYTES + s * K1_W_BYTES, 8192, 1024, 1);
    wg_fence();
#pragma unroll
    for (int k = 0; k < 4; k++) wgmma_ss_n192_tb(acc0, dA + k * 2, dB + k * 128, (kb | k) != 0);
    wg_commit();
    if (kb > 0) {
      wg_wait<1>();
      if ((threadIdx.x & 127) == 0) {
        const int sp = (kb - 1) % K1_STAGES;
        mbar_arrive_cluster(bar_empty + 8 * sp, 0);
        mbar_arrive_cluster(bar_empty + 8 * sp, 1);
      }
    }
  }
  wg_wait<0>();
  fence_regs(acc0);
  if ((threadIdx.x & 127) == 0) {
    mbar_arrive_cluster(bar_empty + 8 * (7 % K1_STAGES), 0);
    mbar_arrive_cluster(bar_empty + 8 * (7 % K1_STAGES), 1);
  }
  if (threadIdx.x == 0) PROF_T(0, 6);

  EpiCtx c;
  {
    const int row0 = rt * 128 + wg * 64 + (warp & 3) * 16;
    c.qf = g_qfrag + ((size_t)((LINEAR ? NH : 0) + cp * 8) * 32 + (rt * 2 + wg)) * 128 + (threadIdx.x & 127);
    uint32_t* img = reinterpret_cast<uint32_t*>(reinterpret_cast<uint8_t*>(g_kv) + (size_t)(cp * 8) * KV_HEAD_BYTES);
    c.kp = img + (row0 >> 3) * 64 + lane;
    c.vp = img + KV_K_BYTES / 4 + (row0 >> 3) * 96 + lane;
    c.s_red = s_red;
    c.red = reinterpret_cast<float*>(smem_gen + wg * 8192) + (warp & 3) * 384 + lane;
    c.lane = lane;
  }
  uint32_t pk[4];
  float vmax = 0.f;
#define K1_T1_STEP(KB)                                                                           \
  {                                                                                              \
    constexpr int g = 8 + KB;                                                                    \
    constexpr int s = g % K1_STAGES;                                                             \
    mbar_wait(bar_full + 8 * s, (g / K1_STAGES) & 1);                                            \
    const uint64_t dA = mkdesc(sbase + KB * 16384 + wg * 8192, 16, 1024, 1);                     \
    const uint64_t dB = mkdesc(sbase + K1_X_BYTES + s * K1_W_BYTES, 8192, 1024, 1);              \
    wg_fence();                                                                                  \
    _Pragma("unroll") for (int k = 0; k < 4; k++) wgmma_ss_n192_tb(acc1, dA + k * 2, dB + k * 128, (KB | k) != 0); \
    wg_commit();                                                                                 \
    epi_slice<LINEAR, 0, KB / 2, KB & 1>(acc0, c, pk, vmax);                                     \
    wg_wait<0>();                                                                                \
    if (KB + K1_STAGES < 8 && (threadIdx.x & 127) == 0) {                                        \
      mbar_arrive_cluster(bar_empty + 8 * s, 0);                                                 \
      mbar_arrive_cluster(bar_empty + 8 * s, 1);                                                 \
    }                                                                                            \
  }
  K1_T1_STEP(0) K1_T1_STEP(1) K1_T1_STEP(2) K1_T1_STEP(3) K1_T1_STEP(4) K1_T1_STEP(5) K1_T1_STEP(6) K1_T1_STEP(7)
#undef K1_T1_STEP
  fence_regs(acc1);
  if (threadIdx.x == 0) PROF_T(0, 10);
  epi_slice<LINEAR, 1, 0, 0>(acc1, c, pk, vmax);
  epi_slice<LINEAR, 1, 0, 1>(acc1, c, pk, vmax);
  epi_slice<LINEAR, 1, 1, 0>(acc1, c, pk, vmax);
  epi_slice<LINEAR, 1, 1, 1>(acc1, c, pk, vmax);
  epi_slice<LINEAR, 1, 2, 0>(acc1, c, pk, vmax);
  epi_slice<LINEAR, 1, 2, 1>(acc1, c, pk, vmax);
  epi_slice<LINEAR, 1, 3, 0>(acc1, c, pk, vmax);
  epi_slice<LINEAR, 1, 3, 1>(acc1, c, pk, vmax);
  if (!LINEAR) {
    const uint32_t vm = __reduce_max_sync(0xffffffffu, __float_as_uint(vmax) & 0x7FFFFFFFu);
    if (lane == 0) atomicMax(&s_red[16], vm);
    asm volatile("bar.sync 1, 256;" ::: "memory");
    if (threadIdx.x < 8) {
      *reinterpret_cast<float4*>(&g_nrm[((cp * 8 + threadIdx.x) * 16 + rt) * 4]) =
          make_float4(__uint_as_float(s_red[threadIdx.x * 2]), __uint_as_float(s_red[threadIdx.x * 2 + 1]), __uint_as_float(s_red[16]), 0.f);
    }
  } else {
    asm volatile("bar.sync 1, 256;" ::: "memory");
    float* dst = g_kvpart + ((size_t)rt * NH + cp * 8) * 384;
#pragma unroll
    for (int i = 0; i < 12; i++) {
      const int o = threadIdx.x + i * 256;
      const int h = o / 384, e = o - h * 384;
      const float* src = reinterpret_cast<const float*>(smem_gen) + K1_SLOT_KB(h) * 4096 + e;
      float sum = 0.f;
#pragma unroll
      for (int w = 0; w < 8; w++) sum += src[(w >> 2) * 2048 + (w & 3) * 384];
      dst[o] = sum;
    }
  }
}

__global__ void __launch_bounds__(384, 1)
qkv_gemm_kernel(const __grid_constant__ CUtensorMap mxA, const __grid_constant__ CUtensorMap mxB,
                const __grid_constant__ CUtensorMap mwA, const __grid_constant__ CUtensorMap mwB) {
  extern __shared__ uint8_t smem_raw[];
  const uint32_t sbase = (smem_u32(smem_raw) + 1023) & ~1023u;
  uint8_t* smem_gen = smem_raw + (sbase - smem_u32(smem_raw));
  const uint32_t bar_full = sbase + K1_BAR_OFF;
  const uint32_t bar_empty = bar_full + 8 * K1_STAGES;
  uint32_t* s_red = reinterpret_cast<uint32_t*>(smem_gen + K1_BAR_OFF + 64);

  const int rank = blockIdx.x & 1;
  const int pair = blockIdx.x >> 1;
  const int branch = pair >> 5;
  const int rp = (pair & 31) >> 2;
  const int cp = pair & 3;
  const int rt = rp * 2 + rank;
  const int warp = threadIdx.x >> 5;
  if (threadIdx.x == 0) { PROF_G(0, 30); PROF_T(0, 0); }
  const CUtensorMap* mx = branch ? &mxA : &mxB;
  const CUtensorMap* mw = branch ? &mwA : &mwB;

  if (threadIdx.x == 256) {
    asm volatile("prefetch.tensormap [%0];" ::"l"(mx) : "memory");
    asm volatile("prefetch.tensormap [%0];" ::"l"(mw) : "memory");
    for (int i = 0; i < K1_STAGES; i++) {
      mbar_init(bar_full + 8 * i, 1);
      mbar_init(bar_empty + 8 * i, 4);
    }
    fence_barrier_init();
    fence_proxy_async();
    for (int kb = 0; kb < K1_STAGES; kb++) {
      mbar_expect_tx(bar_full + 8 * kb, 16384 + K1_W_BYTES);
      tma_load_2d(sbase + kb * 16384, mx, kb * 64, rt * 128, bar_full + 8 * kb);
    }
  }
  if (threadIdx.x < 32) s_red[threadIdx.x] = 0;
  __syncthreads();
  cluster_sync_relaxed();
  if (threadIdx.x == 0) PROF_T(0, 1);

  if (warp >= 8) {
    asm volatile("setmaxnreg.dec.sync.aligned.u32 40;");
    if (threadIdx.x == 256) {
      for (int g = 0; g < 16; g++) {
        const int s = g % K1_STAGES;
        const int kb = g & 7;
        if (g >= K1_STAGES) {
          mbar_wait(bar_empty + 8 * s, ((g / K1_STAGES) - 1) & 1);
          mbar_expect_tx(bar_full + 8 * s, (g < 8 ? 16384 : 0) + K1_W_BYTES);
          if (g < 8) tma_load_2d(sbase + kb * 16384, mx, kb * 64, rt * 128, bar_full + 8 * s);
        }
        const int h0 = cp * 8 + (g >> 3) * 4;
        const uint32_t st = sbase + K1_X_BYTES + s * K1_W_BYTES + rank * 4096;
#pragma unroll
        for (int p = 0; p < 3; p++)
          tma_load_2d_mc(st + p * 8192, mw, p * 512 + h0 * 16, kb * 64 + rank * 32, bar_full + 8 * s, (uint16_t)3);
      }
    }
    __syncwarp();
    cluster_sync_relaxed();
  } else {
    asm volatile("setmaxnreg.inc.sync.aligned.u32 232;");
    if (branch == 0) qkv_consumer<false>(sbase, smem_gen, s_red, cp, rt);
    else qkv_consumer<true>(sbase, smem_gen, s_red, cp, rt);
    if (threadIdx.x == 0) PROF_T(0, 11);
    __syncwarp();
    cluster_sync_relaxed();
    if (threadIdx.x == 0) { PROF_T(0, 12); PROF_G(0, 31); }
  }
}

constexpr int K2_SMEM = KV_HEAD_BYTES + 1024 + 256;

struct ExpC {
  uint32_t k3c00, kmask, seven, c3;
};
__device__ __forceinline__ uint32_t hfma2(uint32_t a, uint32_t b, uint32_t c) {
  uint32_t r;
  asm("fma.rn.f16x2 %0, %1, %2, %3;" : "=r"(r) : "r"(a), "r"(b), "r"(c));
  return r;
}
__device__ __forceinline__ uint32_t exp2_poly_pair(float t0, float t1, const ExpC& c) {
  uint32_t u;
  asm("prmt.b32 %0, %1, %2, 0x5410;" : "=r"(u) : "r"(__float_as_uint(t0)), "r"(__float_as_uint(t1)));
  uint32_t m;
  asm("lop3.b32 %0, %1, 0x03FF03FF, %2, 0xEA;" : "=r"(m) : "r"(u), "r"(c.k3c00));
  uint32_t p = hfma2(m, c.c3, 0x9fe09fe0u);
  p = hfma2(p, m, 0x37a137a1u);
  p = hfma2(p, m, 0x4ab94abau);
  uint32_t mu;
  asm("lop3.b32 %0, %1, 0xFC00FC00, %2, 0xEA;" : "=r"(mu) : "r"(u), "r"(c.kmask));
  uint32_t r;
  asm("{.reg .b32 t; shf.r.wrap.b32 t, %1, %2, 3; add.u32 %0, t, %3;}" : "=r"(r) : "r"(mu), "r"(c.seven), "r"(p));
  return r;
}
__device__ __forceinline__ float gadd(float x, float M, uint32_t g) {
  float r = x;
  asm("{.reg .pred p; setp.ne.b32 p, %2, -1; @p add.f32 %0, %0, %1;}" : "+f"(r) : "f"(M), "r"(g));
  return r;
}
__device__ __forceinline__ float gex2(float x, uint32_t g) {
  float r = x;
  asm("{.reg .pred p; setp.ne.b32 p, %1, -1; @p ex2.approx.ftz.f32 %0, %0;}" : "+f"(r) : "r"(g));
  return r;
}
template <int NPOLY, int NPAIR, int CH, int D>
__device__ __forceinline__ void exp_tile(const float (&s)[2 * NPAIR], uint32_t (&p)[NPAIR], const ExpC& c) {
#pragma unroll
  for (int i = 0; i < NPAIR; i++) {
    const bool isPoly = ((i + 1) * NPOLY / 32) != (i * NPOLY / 32);
    const int ch = i / CH;
    const bool gated = ch >= D;
    int gi = (ch - D) * CH + CH - 1;
    if (gated) {
      while (gi > (ch - D) * CH && !(((gi + 1) * NPOLY / 32) != (gi * NPOLY / 32))) gi--;
    }
    const uint32_t g = gated ? p[gi] : 0;
    if (!isPoly) {
      if (gated) p[i] = pack_bf16(gex2(s[2 * i], g), gex2(s[2 * i + 1], g));
      else p[i] = pack_bf16(ex2f(s[2 * i]), ex2f(s[2 * i + 1]));
    } else {
      if (gated) p[i] = exp2_poly_pair(gadd(s[2 * i], 12329.f, g), gadd(s[2 * i + 1], 12329.f, g), c);
      else p[i] = exp2_poly_pair(s[2 * i] + 12329.f, s[2 * i + 1] + 12329.f, c);
    }
  }
}

__device__ __forceinline__ void store_o(__nv_bfloat16* o, int row0, int head, int lane, const uint32_t (&r)[4]) {
  const int g = lane >> 2, t = lane & 3;
  uint32_t* p0 = reinterpret_cast<uint32_t*>(o + (size_t)(row0 + g) * DM + head * 16) + t;
  uint32_t* p1 = reinterpret_cast<uint32_t*>(o + (size_t)(row0 + g + 8) * DM + head * 16) + t;
  p0[0] = r[0];
  p1[0] = r[1];
  p0[4] = r[2];
  p1[4] = r[3];
}

template <bool SAFE>
__device__ __forceinline__ void attn_step(float (&s)[32], float (&o)[12], float& m0, float& m1, const uint4& qf, uint64_t dKn,
                                          uint64_t dV, const ExpC& ec) {
  uint32_t p[16];
  wg_wait<0>();
  fence_regs(s);
  if (!SAFE) {
    exp_tile<16, 16, 4, 2>(s, p, ec);
  } else {
    fence_regs(o);
    float x0 = s[0], x1 = s[2];
#pragma unroll
    for (int i = 0; i < 8; i++) {
      x0 = fmaxf(x0, fmaxf(s[4 * i], s[4 * i + 1]));
      x1 = fmaxf(x1, fmaxf(s[4 * i + 2], s[4 * i + 3]));
    }
    x0 = fmaxf(x0, __shfl_xor_sync(0xffffffffu, x0, 1));
    x1 = fmaxf(x1, __shfl_xor_sync(0xffffffffu, x1, 1));
    x0 = fmaxf(x0, __shfl_xor_sync(0xffffffffu, x0, 2));
    x1 = fmaxf(x1, __shfl_xor_sync(0xffffffffu, x1, 2));
    const float n0 = fmaxf(m0, x0), n1 = fmaxf(m1, x1);
    const float c0 = ex2f(m0 - n0), c1 = ex2f(m1 - n1);
    m0 = n0;
    m1 = n1;
#pragma unroll
    for (int i = 0; i < 3; i++) {
      o[4 * i] *= c0;
      o[4 * i + 1] *= c0;
      o[4 * i + 2] *= c1;
      o[4 * i + 3] *= c1;
    }
#pragma unroll
    for (int i = 0; i < 8; i++) {
      p[2 * i] = pack_bf16(ex2f(s[4 * i] - n0), ex2f(s[4 * i + 1] - n0));
      p[2 * i + 1] = pack_bf16(ex2f(s[4 * i + 2] - n1), ex2f(s[4 * i + 3] - n1));
    }
  }
  wg_fence();
  wgmma_rs_n64_z(s, qf.x, qf.y, qf.z, qf.w, dKn);
#pragma unroll
  for (int k = 0; k < 4; k++) wgmma_rs_n24_tb(o, p[4 * k], p[4 * k + 1], p[4 * k + 2], p[4 * k + 3], dV + k * 48, 1);
  wg_commit();
}

template <bool SAFE>
__device__ __forceinline__ void attn_tile(uint64_t dK, uint64_t dV, uint32_t bar, const uint4 qf, const ExpC& ec, uint32_t (&outp)[4]) {
  float s[32];
  float o[12];
#pragma unroll
  for (int i = 0; i < 12; i++) asm volatile("mov.f32 %0, 0f00000000;" : "=f"(o[i]));
  float m0 = -INFINITY, m1 = -INFINITY;
  mbar_wait(bar, 0);
  wg_fence();
  wgmma_rs_n64_z(s, qf.x, qf.y, qf.z, qf.w, dK);
  wg_commit();
#pragma unroll 1
  for (int c = 0; c < 4; c++) {
    if (c > 0) mbar_wait(bar + 8 * c, 0);
#pragma unroll 1
    for (int j = 0; j < 4; j++) {
      attn_step<SAFE>(s, o, m0, m1, qf, dK + 128, dV, ec);
      attn_step<SAFE>(s, o, m0, m1, qf, dK + 256, dV + 192, ec);
      dK += 256;
      dV += 384;
    }
  }
  wg_wait<0>();
  fence_regs(o);
  fence_regs(s);
  const float r0 = 1.0f / o[8], r1 = 1.0f / o[10];
  outp[0] = pack_bf16(o[0] * r0, o[1] * r0);
  outp[1] = pack_bf16(o[2] * r1, o[3] * r1);
  outp[2] = pack_bf16(o[4] * r0, o[5] * r0);
  outp[3] = pack_bf16(o[6] * r1, o[7] * r1);
}

__device__ __forceinline__ void linear_attn_cta(uint8_t* smem_raw, uint32_t sbase, const CUtensorMap* mo16, int cta) {
  const int warp = threadIdx.x >> 5, lane = threadIdx.x & 31;
  float* red = reinterpret_cast<float*>(smem_raw + (sbase - smem_u32(smem_raw)) + 131072);
  {
    const float* src = g_kvpart + (size_t)cta * 8 * 384;
    float sum[6];
#pragma unroll
    for (int i = 0; i < 6; i++) sum[i] = 0.f;
#pragma unroll
    for (int r = 0; r < 16; r++) {
#pragma unroll
      for (int i = 0; i < 6; i++) sum[i] += src[(size_t)r * NH * 384 + threadIdx.x + i * 512];
    }
#pragma unroll
    for (int i = 0; i < 6; i++) red[threadIdx.x + i * 512] = round_bf16(sum[i]);
  }
  __syncthreads();
  uint32_t bf[8][6];
  {
    const int g = lane >> 2, t = lane & 3;
#pragma unroll
    for (int h = 0; h < 8; h++) {
#pragma unroll
      for (int f = 0; f < 6; f++) {
        const int blk = f >> 1, half = f & 1;
        const int e = (blk == 2) ? 0 : g;
        const int d = 2 * t + 8 * half;
        const int base = h * 384 + (blk * 4 + half * 2 + (e & 1)) * 32 + (e >> 1);
        bf[h][f] = pack_bf16(red[base + (d & 7) * 4], red[base + ((d + 1) & 7) * 4]);
      }
    }
  }
  const uint32_t stg = sbase + warp * 8192;
#pragma unroll 1
  for (int rb = 0; rb < 8; rb++) {
    const int blk16 = rb * 16 + warp;
    const uint4* qp = g_qfrag + ((size_t)(NH + cta * 8) * 32 + (blk16 >> 2)) * 128 + (blk16 & 3) * 32 + lane;
    uint4 q[8];
#pragma unroll
    for (int h = 0; h < 8; h++) q[h] = qp[h * 32 * 128];
    const uint32_t buf = stg + (rb & 1) * 4096;
    if (rb >= 2) {
      if (lane == 0) asm volatile("cp.async.bulk.wait_group.read 1;" ::: "memory");
      __syncwarp();
    }
#pragma unroll
    for (int h = 0; h < 8; h++) {
      float n0[4] = {0, 0, 0, 0}, n1[4] = {0, 0, 0, 0}, dn[4] = {0, 0, 0, 0};
      hmma(n0, q[h].x, q[h].y, q[h].z, q[h].w, bf[h][0], bf[h][1]);
      hmma(n1, q[h].x, q[h].y, q[h].z, q[h].w, bf[h][2], bf[h][3]);
      hmma(dn, q[h].x, q[h].y, q[h].z, q[h].w, bf[h][4], bf[h][5]);
      const float d0 = round_bf16(round_bf16(dn[0]) + 1e-6f), d1 = round_bf16(round_bf16(dn[2]) + 1e-6f);
      const uint32_t r0 = pack_bf16(__fdividef(round_bf16(n0[0]), d0), __fdividef(round_bf16(n0[1]), d0));
      const uint32_t r1 = pack_bf16(__fdividef(round_bf16(n0[2]), d1), __fdividef(round_bf16(n0[3]), d1));
      const uint32_t r2 = pack_bf16(__fdividef(round_bf16(n1[0]), d0), __fdividef(round_bf16(n1[1]), d0));
      const uint32_t r3 = pack_bf16(__fdividef(round_bf16(n1[2]), d1), __fdividef(round_bf16(n1[3]), d1));
      const int row = lane & 15;
      const int chunk = (h & 3) * 2 + (lane >> 4);
      const uint32_t addr = buf + (h >> 2) * 2048 + row * 128 + ((chunk ^ (row & 7)) << 4);
      asm volatile("stmatrix.sync.aligned.m8n8.x4.shared.b16 [%0], {%1,%2,%3,%4};" ::"r"(addr), "r"(r0), "r"(r1), "r"(r2), "r"(r3)
                   : "memory");
    }
    fence_proxy_async();
    __syncwarp();
    if (lane == 0) {
      tma_store_2d(mo16, buf, cta * 128, blk16 * 16);
      tma_store_2d(mo16, buf + 2048, cta * 128 + 64, blk16 * 16);
      asm volatile("cp.async.bulk.commit_group;" ::: "memory");
    }
  }
  if (lane == 0) asm volatile("cp.async.bulk.wait_group 0;" ::: "memory");
}

__global__ void __launch_bounds__(512, 1) attn_kernel(const __grid_constant__ CUtensorMap mo16) {
  extern __shared__ uint8_t smem_raw[];
  const uint32_t sbase = (smem_u32(smem_raw) + 1023) & ~1023u;
  const uint32_t bar = sbase + KV_HEAD_BYTES;
  if (threadIdx.x == 0) { PROF_G(1, 30); PROF_T(1, 0); }
  if (threadIdx.x == 0) {
    for (int i = 0; i < 4; i++) mbar_init(bar + 8 * i, 1);
    fence_barrier_init();
    fence_proxy_async();
  }
  __syncthreads();
  if (blockIdx.x >= 128) {
    linear_attn_cta(smem_raw, sbase, &mo16, blockIdx.x - 128);
    if (threadIdx.x == 0) { PROF_T(1, 5); PROF_G(1, 31); }
    return;
  }
  const int head = blockIdx.x >> 2, qb = blockIdx.x & 3;
  if (threadIdx.x == 0) {
    const uint8_t* img = reinterpret_cast<const uint8_t*>(g_kv) + (size_t)head * KV_HEAD_BYTES;
    mbar_expect_tx(bar, 32768 + 24576);
    bulk_load(sbase, img, 32768, bar);
    bulk_load(sbase + KV_K_BYTES, img + KV_K_BYTES, 24576, bar);
    for (int i = 1; i < 4; i++) {
      mbar_expect_tx(bar + 8 * i, (i < 3 ? 16384 : 0) + 24576);
      if (i < 3) bulk_load(sbase + (i + 1) * 16384, img + (i + 1) * 16384, 16384, bar + 8 * i);
      bulk_load(sbase + KV_K_BYTES + i * 24576, img + KV_K_BYTES + i * 24576, 24576, bar + 8 * i);
    }
  }
  const int lane = threadIdx.x & 31;
  bool safe_path;
  {
    float4 n = make_float4(0.f, 0.f, 0.f, 0.f);
    if (lane < 16) n = *reinterpret_cast<const float4*>(&g_nrm[(head * 16 + lane) * 4]);
    uint32_t qm = ((lane >> 2) == qb) ? __float_as_uint(n.x) : 0u;
    qm = __reduce_max_sync(0xffffffffu, qm);
    const uint32_t km = __reduce_max_sync(0xffffffffu, __float_as_uint(n.y));
    const uint32_t vm = __reduce_max_sync(0xffffffffu, __float_as_uint(n.z));
    const float b2 = __uint_as_float(qm) * (QSCALE * QSCALE) * __uint_as_float(km) * 1.02f;
    const float vmax = __uint_as_float(vm);
    const bool ok = (b2 <= 21.5f * 21.5f) && (vmax <= 1.0e24f) && (vmax >= 1.0e-18f || vmax == 0.f);
    safe_path = !ok;
  }
  const int wg = threadIdx.x >> 7, warp = (threadIdx.x >> 5) & 3;
  uint32_t zero;
  asm volatile("mov.u32 %0, %%smid;" : "=r"(zero));
  zero >>= 16;
  const ExpC ec{0x3C003C00u + zero, 0x00070000u + zero, 7u + zero, 0x2cfd2cfdu + zero};
  const uint64_t dK = mkdesc(sbase, 128, 256, 0);
  const uint64_t dV = mkdesc(sbase + KV_K_BYTES, 384, 128, 0);
#pragma unroll 1
  for (int t = 0; t < 2; t++) {
    const int tile64 = qb * 8 + wg * 2 + t;
    const uint4 qf = g_qfrag[(head * 32 + tile64) * 128 + (threadIdx.x & 127)];
    uint32_t r[4];
    if (threadIdx.x == 0) PROF_T(1, 1 + t);
    if (!safe_path) attn_tile<false>(dK, dV, bar, qf, ec, r);
    else attn_tile<true>(dK, dV, bar, qf, ec, r);
    store_o(g_o + (size_t)S_LEN * DM, tile64 * 64 + warp * 16, head, lane, r);
  }
  if (threadIdx.x == 0) { PROF_T(1, 5); PROF_G(1, 31); }
}

constexpr int K3_STAGES = 6;
constexpr int K3_STAGE_BYTES = 16384 + 2 * 8192;
constexpr int K3_SMEM = K3_STAGES * K3_STAGE_BYTES + 1024 + 256;

__global__ void __launch_bounds__(288, 1)
out_gemm_kernel(const __grid_constant__ CUtensorMap mo, const __grid_constant__ CUtensorMap mwA,
                const __grid_constant__ CUtensorMap mwB, const __grid_constant__ CUtensorMap mout) {
  extern __shared__ uint8_t smem_raw[];
  const uint32_t sbase = (smem_u32(smem_raw) + 1023) & ~1023u;
  const uint32_t bar_full = sbase + K3_STAGES * K3_STAGE_BYTES;
  const uint32_t bar_empty = bar_full + 8 * K3_STAGES;
  const int branch = blockIdx.x >> 6;
  const int rt = (blockIdx.x & 63) >> 2;
  const int ct = blockIdx.x & 3;
  const int warp = threadIdx.x >> 5;
  if (threadIdx.x == 0) { PROF_G(2, 30); PROF_T(2, 0); }
  if (threadIdx.x == 0) {
    for (int i = 0; i < K3_STAGES; i++) {
      mbar_init(bar_full + 8 * i, 1);
      mbar_init(bar_empty + 8 * i, 2);
    }
    fence_barrier_init();
  }
  __syncthreads();
  if (warp == 8) {
    if ((threadIdx.x & 31) == 0) {
      const CUtensorMap* mw = branch ? &mwB : &mwA;
      for (int kb = 0; kb < 8; kb++) {
        const int s = kb % K3_STAGES;
        if (kb >= K3_STAGES) mbar_wait(bar_empty + 8 * s, ((kb / K3_STAGES) - 1) & 1);
        const uint32_t st = sbase + s * K3_STAGE_BYTES;
        mbar_expect_tx(bar_full + 8 * s, K3_STAGE_BYTES);
        tma_load_2d(st, &mo, kb * 64, branch * S_LEN + rt * 128, bar_full + 8 * s);
        tma_load_2d(st + 16384, mw, ct * 128, kb * 64, bar_full + 8 * s);
        tma_load_2d(st + 16384 + 8192, mw, ct * 128 + 64, kb * 64, bar_full + 8 * s);
      }
    }
  } else {
    const int wg = warp >> 2;
    float acc[64];
    for (int kb = 0; kb < 8; kb++) {
      const int s = kb % K3_STAGES;
      mbar_wait(bar_full + 8 * s, (kb / K3_STAGES) & 1);
      if (threadIdx.x == 0) PROF_T(2, 2 + kb);
      const uint32_t st = sbase + s * K3_STAGE_BYTES;
      const uint64_t dA = mkdesc(st + wg * 8192, 16, 1024, 1);
      const uint64_t dB = mkdesc(st + 16384, 8192, 1024, 1);
      wg_fence();
#pragma unroll
      for (int k = 0; k < 4; k++) wgmma_ss_n128_tb(acc, dA + k * 2, dB + k * 128, (kb | k) != 0);
      wg_commit();
      if (kb > 0) {
        wg_wait<1>();
        if ((threadIdx.x & 127) == 0) mbar_arrive(bar_empty + 8 * ((kb - 1) % K3_STAGES));
      }
    }
    wg_wait<0>();
    fence_regs(acc);
    if (threadIdx.x == 0) PROF_T(2, 10);
    asm volatile("bar.sync 1, 256;" ::: "memory");
    const int lane = threadIdx.x & 31;
    const int rloc = wg * 64 + (warp & 3) * 16 + (lane & 15);
#pragma unroll
    for (int c16 = 0; c16 < 8; c16++) {
      const float* a = &acc[c16 * 8];
      const uint32_t r0 = pack_bf16(a[0], a[1]), r1 = pack_bf16(a[2], a[3]), r2 = pack_bf16(a[4], a[5]), r3 = pack_bf16(a[6], a[7]);
      const int chunk = (c16 & 3) * 2 + (lane >> 4);
      const uint32_t addr = sbase + (c16 >> 2) * 16384 + rloc * 128 + ((chunk ^ (rloc & 7)) << 4);
      asm volatile("stmatrix.sync.aligned.m8n8.x4.shared.b16 [%0], {%1,%2,%3,%4};" ::"r"(addr), "r"(r0), "r"(r1), "r"(r2), "r"(r3)
                   : "memory");
    }
    fence_proxy_async();
    asm volatile("bar.sync 1, 256;" ::: "memory");
    if (threadIdx.x == 0) {
      tma_store_2d(&mout, sbase, branch * DM + ct * 128, rt * 128);
      tma_store_2d(&mout, sbase + 16384, branch * DM + ct * 128 + 64, rt * 128);
      asm volatile("cp.async.bulk.commit_group;" ::: "memory");
      asm volatile("cp.async.bulk.wait_group 0;" ::: "memory");
      PROF_T(2, 12); PROF_G(2, 31);
    }
  }
}

typedef CUresult (*EncodeFn)(CUtensorMap*, CUtensorMapDataType, cuuint32_t, void*, const cuuint64_t*, const cuuint64_t*,
                             const cuuint32_t*, const cuuint32_t*, CUtensorMapInterleave, CUtensorMapSwizzle,
                             CUtensorMapL2promotion, CUtensorMapFloatOOBfill);

void make_map(EncodeFn enc, CUtensorMap* m, const void* ptr, uint64_t inner, uint64_t outer, uint32_t box_inner, uint32_t box_outer) {
  cuuint64_t dims[2] = {inner, outer};
  cuuint64_t strides[1] = {inner * 2};
  cuuint32_t box[2] = {box_inner, box_outer};
  cuuint32_t es[2] = {1, 1};
  enc(m, CU_TENSOR_MAP_DATA_TYPE_BFLOAT16, 2, const_cast<void*>(ptr), dims, strides, box, es, CU_TENSOR_MAP_INTERLEAVE_NONE,
      CU_TENSOR_MAP_SWIZZLE_128B, CU_TENSOR_MAP_L2_PROMOTION_L2_256B, CU_TENSOR_MAP_FLOAT_OOB_FILL_NONE);
}

struct HostState {
  bool init;
  const void* key[7];
  CUtensorMap mxA, mxB, mwA, mwB, mo, mo16, mwoA, mwoB, mout;
};
HostState g_hs;

}

extern "C" void kernel_launch(void* const* d_in, const int* in_sizes, int n_in, void* d_out, int out_size) {
  (void)in_sizes; (void)n_in; (void)out_size;
  HostState& hs = g_hs;
  bool same = hs.init && hs.key[6] == d_out;
  for (int i = 0; i < 6 && same; i++) same = hs.key[i] == d_in[i];
  if (!same) {
    void* fn = nullptr;
    cudaDriverEntryPointQueryResult qr;
    cudaGetDriverEntryPoint("cuTensorMapEncodeTiled", &fn, cudaEnableDefault, &qr);
    EncodeFn enc = (EncodeFn)fn;
    void* go = nullptr;
    cudaGetSymbolAddress(&go, g_o);
    make_map(enc, &hs.mxA, d_in[0], 512, 2048, 64, 128);
    make_map(enc, &hs.mwA, d_in[1], 1536, 512, 64, 32);
    make_map(enc, &hs.mwoA, d_in[2], 512, 512, 64, 64);
    make_map(enc, &hs.mxB, d_in[3], 512, 2048, 64, 128);
    make_map(enc, &hs.mwB, d_in[4], 1536, 512, 64, 32);
    make_map(enc, &hs.mwoB, d_in[5], 512, 512, 64, 64);
    make_map(enc, &hs.mo, go, 512, 4096, 64, 128);
    make_map(enc, &hs.mo16, go, 512, 4096, 64, 16);
    make_map(enc, &hs.mout, d_out, 1024, 2048, 64, 128);
    cudaFuncSetAttribute(qkv_gemm_kernel, cudaFuncAttributeMaxDynamicSharedMemorySize, K1_SMEM);
    cudaFuncSetAttribute(attn_kernel, cudaFuncAttributeMaxDynamicSharedMemorySize, K2_SMEM);
    cudaFuncSetAttribute(out_gemm_kernel, cudaFuncAttributeMaxDynamicSharedMemorySize, K3_SMEM);
    for (int i = 0; i < 6; i++) hs.key[i] = d_in[i];
    hs.key[6] = d_out;
    hs.init = true;
  }
  cudaStream_t st = cudaStreamPerThread;
  {
    cudaLaunchConfig_t cfg = {};
    cfg.gridDim = dim3(128);
    cfg.blockDim = dim3(384);
    cfg.dynamicSmemBytes = K1_SMEM;
    cfg.stream = st;
    cudaLaunchAttribute at[1];
    at[0].id = cudaLaunchAttributeClusterDimension;
    at[0].val.clusterDim.x = 2;
    at[0].val.clusterDim.y = 1;
    at[0].val.clusterDim.z = 1;
    cfg.attrs = at;
    cfg.numAttrs = 1;
    cudaLaunchKernelEx(&cfg, qkv_gemm_kernel, hs.mxA, hs.mxB, hs.mwA, hs.mwB);
  }
  attn_kernel<<<132, 512, K2_SMEM, st>>>(hs.mo16);
  out_gemm_kernel<<<128, 288, K3_SMEM, st>>>(hs.mo, hs.mwoA, hs.mwoB, hs.mout);
}
```

```cpp
#include <cuda_runtime.h>
#include <cuda_bf16.h>
#include <cuda.h>
#include <stdint.h>

namespace {

constexpr int S_LEN = 2048;
constexpr int DM = 512;
constexpr int NH = 32;

constexpr int KV_K_BYTES = 65536;
constexpr int KV_HEAD_BYTES = KV_K_BYTES + 98304;
__device__ uint4 g_qfrag[2 * NH * 32 * 128];
__device__ uint4 g_kv[NH * KV_HEAD_BYTES / 16];
__device__ float g_kvpart[16 * NH * 384];
__device__ float g_nrm[NH * 16 * 4];
__device__ __nv_bfloat16 g_o[2 * S_LEN * DM];

#define PROF_T(k, i) do {} while (0)
#define PROF_G(k, i) do {} while (0)
__device__ __forceinline__ uint32_t smem_u32(const void* p) { return (uint32_t)__cvta_generic_to_shared(p); }
__device__ __forceinline__ void mbar_init(uint32_t bar, int cnt) {
  asm volatile("mbarrier.init.shared::cta.b64 [%0], %1;" ::"r"(bar), "r"(cnt) : "memory");
}
__device__ __forceinline__ void mbar_expect_tx(uint32_t bar, uint32_t bytes) {
  asm volatile("mbarrier.arrive.expect_tx.shared::cta.b64 _, [%0], %1;" ::"r"(bar), "r"(bytes) : "memory");
}
__device__ __forceinline__ void mbar_arrive(uint32_t bar) {
  asm volatile("mbarrier.arrive.shared::cta.b64 _, [%0];" ::"r"(bar) : "memory");
}
__device__ __forceinline__ void mbar_arrive_cluster(uint32_t bar, uint32_t cta) {
  asm volatile(
      "{\n.reg .b32 ra;\nmapa.shared::cluster.u32 ra, %0, %1;\n"
      "mbarrier.arrive.shared::cluster.b64 _, [ra];\n}" ::"r"(bar), "r"(cta) : "memory");
}
__device__ __forceinline__ void mbar_wait(uint32_t bar, uint32_t parity) {
  asm volatile(
      "{\n.reg .pred p;\n"
      "WAIT_LOOP:\n"
      "mbarrier.try_wait.parity.shared::cta.b64 p, [%0], %1, 0x989680;\n"
      "@p bra WAIT_DONE;\n"
      "bra WAIT_LOOP;\n"
      "WAIT_DONE:\n}" ::"r"(bar), "r"(parity) : "memory");
}
__device__ __forceinline__ void mbar_wait_cluster(uint32_t bar, uint32_t parity) {
  asm volatile(
      "{\n.reg .pred p;\n"
      "WAIT_LOOP:\n"
      "mbarrier.try_wait.parity.acquire.cluster.shared::cta.b64 p, [%0], %1, 0x989680;\n"
      "@p bra WAIT_DONE;\n"
      "bra WAIT_LOOP;\n"
      "WAIT_DONE:\n}" ::"r"(bar), "r"(parity) : "memory");
}
__device__ __forceinline__ void fence_barrier_init() {
  asm volatile("fence.mbarrier_init.release.cluster;" ::: "memory");
}
__device__ __forceinline__ void fence_proxy_async() { asm volatile("fence.proxy.async.shared::cta;" ::: "memory"); }
__device__ __forceinline__ void cluster_sync_relaxed() {
  asm volatile("barrier.cluster.arrive.relaxed.aligned;\nbarrier.cluster.wait.aligned;" ::: "memory");
}
__device__ __forceinline__ void tma_load_2d(uint32_t dst, const CUtensorMap* m, int x, int y, uint32_t bar) {
  asm volatile(
      "cp.async.bulk.tensor.2d.shared::cluster.global.mbarrier::complete_tx::bytes [%0], [%1, {%3, %4}], [%2];" ::"r"(dst),
      "l"(m), "r"(bar), "r"(x), "r"(y)
      : "memory");
}
__device__ __forceinline__ void tma_load_2d_mc(uint32_t dst, const CUtensorMap* m, int x, int y, uint32_t bar, uint16_t mask) {
  asm volatile(
      "cp.async.bulk.tensor.2d.shared::cluster.global.mbarrier::complete_tx::bytes.multicast::cluster [%0], [%1, {%3, %4}], "
      "[%2], %5;" ::"r"(dst),
      "l"(m), "r"(bar), "r"(x), "r"(y), "h"(mask)
      : "memory");
}
__device__ __forceinline__ void tma_store_2d(const CUtensorMap* m, uint32_t src, int x, int y) {
  asm volatile("cp.async.bulk.tensor.2d.global.shared::cta.bulk_group [%0, {%2, %3}], [%1];" ::"l"(m), "r"(src), "r"(x),
               "r"(y)
               : "memory");
}
__device__ __forceinline__ void bulk_load(uint32_t dst, const void* src, uint32_t bytes, uint32_t bar) {
  asm volatile("cp.async.bulk.shared::cluster.global.mbarrier::complete_tx::bytes [%0], [%1], %2, [%3];" ::"r"(dst),
               "l"(src), "r"(bytes), "r"(bar)
               : "memory");
}
__device__ __forceinline__ void pdl_launch_dependents() { asm volatile("griddepcontrol.launch_dependents;" ::: "memory"); }
__device__ __forceinline__ void pdl_wait() { asm volatile("griddepcontrol.wait;" ::: "memory"); }
__device__ __forceinline__ void wg_fence() { asm volatile("wgmma.fence.sync.aligned;" ::: "memory"); }
__device__ __forceinline__ void wg_commit() { asm volatile("wgmma.commit_group.sync.aligned;" ::: "memory"); }
template <int N>
__device__ __forceinline__ void wg_wait() {
  asm volatile("wgmma.wait_group.sync.aligned %0;" ::"n"(N) : "memory");
}
template <int M>
__device__ __forceinline__ void fence_regs(float (&r)[M]) {
#pragma unroll
  for (int i = 0; i < M; i++) asm volatile("" : "+f"(r[i])::"memory");
}
__device__ __forceinline__ uint64_t mkdesc(uint32_t addr, uint32_t lbo, uint32_t sbo, uint32_t layout) {
  return (uint64_t)((addr & 0x3FFFF) >> 4) | ((uint64_t)(lbo >> 4) << 16) | ((uint64_t)(sbo >> 4) << 32) |
         ((uint64_t)layout << 62);
}
__device__ __forceinline__ uint32_t pack_bf16(float lo, float hi) {
  uint32_t r;
  asm("cvt.rn.bf16x2.f32 %0, %1, %2;" : "=r"(r) : "f"(hi), "f"(lo));
  return r;
}
__device__ __forceinline__ float bf_lo(uint32_t v) { return __uint_as_float(v << 16); }
__device__ __forceinline__ float bf_hi(uint32_t v) { return __uint_as_float(v & 0xFFFF0000u); }
__device__ __forceinline__ float round_bf16(float x) { return bf_lo(pack_bf16(x, 0.f)); }
__device__ __forceinline__ float ex2f(float x) {
  float y;
  asm("ex2.approx.ftz.f32 %0, %1;" : "=f"(y) : "f"(x));
  return y;
}

__device__ __forceinline__ void wgmma_rs_n24_tb(float (&d)[12], uint32_t a0, uint32_t a1, uint32_t a2, uint32_t a3, uint64_t descB, int scaleD) {
  asm volatile("{\n.reg .pred p;\nsetp.ne.b32 p, %17, 0;\n"
    "wgmma.mma_async.sync.aligned.m64n24k16.f32.bf16.bf16 "
    "{%0, %1, %2, %3, %4, %5, %6, %7, %8, %9, %10, %11}, {%12, %13, %14, %15}, %16, p, 1, 1, 1;\n}\n"
    : "+f"(d[0]), "+f"(d[1]), "+f"(d[2]), "+f"(d[3]), "+f"(d[4]), "+f"(d[5]), "+f"(d[6]), "+f"(d[7]),
      "+f"(d[8]), "+f"(d[9]), "+f"(d[10]), "+f"(d[11])
    : "r"(a0), "r"(a1), "r"(a2), "r"(a3), "l"(descB), "r"(scaleD));
}
__device__ __forceinline__ void wgmma_rs_n64_z(float (&d)[32], uint32_t a0, uint32_t a1, uint32_t a2, uint32_t a3, uint64_t descB) {
  asm volatile("{\n.reg .pred p;\nsetp.ne.b32 p, %37, 0;\n"
    "wgmma.mma_async.sync.aligned.m64n64k16.f32.bf16.bf16 "
    "{%0, %1, %2, %3, %4, %5, %6, %7, %8, %9, %10, %11, %12, %13, %14, %15, %16, %17, %18, %19, %20, %21, %22, %23, %24, %25, %26, %27, %28, %29, %30, %31}, {%32, %33, %34, %35}, %36, p, 1, 1, 0;\n}\n"
    : "=f"(d[0]), "=f"(d[1]), "=f"(d[2]), "=f"(d[3]), "=f"(d[4]), "=f"(d[5]), "=f"(d[6]), "=f"(d[7]),
      "=f"(d[8]), "=f"(d[9]), "=f"(d[10]), "=f"(d[11]), "=f"(d[12]), "=f"(d[13]), "=f"(d[14]), "=f"(d[15]),
      "=f"(d[16]), "=f"(d[17]), "=f"(d[18]), "=f"(d[19]), "=f"(d[20]), "=f"(d[21]), "=f"(d[22]), "=f"(d[23]),
      "=f"(d[24]), "=f"(d[25]), "=f"(d[26]), "=f"(d[27]), "=f"(d[28]), "=f"(d[29]), "=f"(d[30]), "=f"(d[31])
    : "r"(a0), "r"(a1), "r"(a2), "r"(a3), "l"(descB), "n"(0));
}
__device__ __forceinline__ void wgmma_ss_n128_tb(float (&d)[64], uint64_t descA, uint64_t descB, int scaleD) {
  asm volatile("{\n.reg .pred p;\nsetp.ne.b32 p, %66, 0;\n"
    "wgmma.mma_async.sync.aligned.m64n128k16.f32.bf16.bf16 "
    "{%0, %1, %2, %3, %4, %5, %6, %7, %8, %9, %10, %11, %12, %13, %14, %15, %16, %17, %18, %19, %20, %21, %22, %23, %24, %25, %26, %27, %28, %29, %30, %31, %32, %33, %34, %35, %36, %37, %38, %39, %40, %41, %42, %43, %44, %45, %46, %47, %48, %49, %50, %51, %52, %53, %54, %55, %56, %57, %58, %59, %60, %61, %62, %63}, %64, %65, p, 1, 1, 0, 1;\n}\n"
    : "+f"(d[0]), "+f"(d[1]), "+f"(d[2]), "+f"(d[3]), "+f"(d[4]), "+f"(d[5]), "+f"(d[6]), "+f"(d[7]),
      "+f"(d[8]), "+f"(d[9]), "+f"(d[10]), "+f"(d[11]), "+f"(d[12]), "+f"(d[13]), "+f"(d[14]), "+f"(d[15]),
      "+f"(d[16]), "+f"(d[17]), "+f"(d[18]), "+f"(d[19]), "+f"(d[20]), "+f"(d[21]), "+f"(d[22]), "+f"(d[23]),
      "+f"(d[24]), "+f"(d[25]), "+f"(d[26]), "+f"(d[27]), "+f"(d[28]), "+f"(d[29]), "+f"(d[30]), "+f"(d[31]),
      "+f"(d[32]), "+f"(d[33]), "+f"(d[34]), "+f"(d[35]), "+f"(d[36]), "+f"(d[37]), "+f"(d[38]), "+f"(d[39]),
      "+f"(d[40]), "+f"(d[41]), "+f"(d[42]), "+f"(d[43]), "+f"(d[44]), "+f"(d[45]), "+f"(d[46]), "+f"(d[47]),
      "+f"(d[48]), "+f"(d[49]), "+f"(d[50]), "+f"(d[51]), "+f"(d[52]), "+f"(d[53]), "+f"(d[54]), "+f"(d[55]),
      "+f"(d[56]), "+f"(d[57]), "+f"(d[58]), "+f"(d[59]), "+f"(d[60]), "+f"(d[61]), "+f"(d[62]), "+f"(d[63])
    : "l"(descA), "l"(descB), "r"(scaleD));
}
__device__ __forceinline__ void wgmma_ss_n192_tb(float (&d)[96], uint64_t descA, uint64_t descB, int scaleD) {
  asm volatile("{\n.reg .pred p;\nsetp.ne.b32 p, %98, 0;\n"
    "wgmma.mma_async.sync.aligned.m64n192k16.f32.bf16.bf16 "
    "{%0, %1, %2, %3, %4, %5, %6, %7, %8, %9, %10, %11, %12, %13, %14, %15, %16, %17, %18, %19, %20, %21, %22, %23, %24, %25, %26, %27, %28, %29, %30, %31, %32, %33, %34, %35, %36, %37, %38, %39, %40, %41, %42, %43, %44, %45, %46, %47, %48, %49, %50, %51, %52, %53, %54, %55, %56, %57, %58, %59, %60, %61, %62, %63, %64, %65, %66, %67, %68, %69, %70, %71, %72, %73, %74, %75, %76, %77, %78, %79, %80, %81, %82, %83, %84, %85, %86, %87, %88, %89, %90, %91, %92, %93, %94, %95}, %96, %97, p, 1, 1, 0, 1;\n}\n"
    : "+f"(d[0]), "+f"(d[1]), "+f"(d[2]), "+f"(d[3]), "+f"(d[4]), "+f"(d[5]), "+f"(d[6]), "+f"(d[7]),
      "+f"(d[8]), "+f"(d[9]), "+f"(d[10]), "+f"(d[11]), "+f"(d[12]), "+f"(d[13]), "+f"(d[14]), "+f"(d[15]),
      "+f"(d[16]), "+f"(d[17]), "+f"(d[18]), "+f"(d[19]), "+f"(d[20]), "+f"(d[21]), "+f"(d[22]), "+f"(d[23]),
      "+f"(d[24]), "+f"(d[25]), "+f"(d[26]), "+f"(d[27]), "+f"(d[28]), "+f"(d[29]), "+f"(d[30]), "+f"(d[31]),
      "+f"(d[32]), "+f"(d[33]), "+f"(d[34]), "+f"(d[35]), "+f"(d[36]), "+f"(d[37]), "+f"(d[38]), "+f"(d[39]),
      "+f"(d[40]), "+f"(d[41]), "+f"(d[42]), "+f"(d[43]), "+f"(d[44]), "+f"(d[45]), "+f"(d[46]), "+f"(d[47]),
      "+f"(d[48]), "+f"(d[49]), "+f"(d[50]), "+f"(d[51]), "+f"(d[52]), "+f"(d[53]), "+f"(d[54]), "+f"(d[55]),
      "+f"(d[56]), "+f"(d[57]), "+f"(d[58]), "+f"(d[59]), "+f"(d[60]), "+f"(d[61]), "+f"(d[62]), "+f"(d[63]),
      "+f"(d[64]), "+f"(d[65]), "+f"(d[66]), "+f"(d[67]), "+f"(d[68]), "+f"(d[69]), "+f"(d[70]), "+f"(d[71]),
      "+f"(d[72]), "+f"(d[73]), "+f"(d[74]), "+f"(d[75]), "+f"(d[76]), "+f"(d[77]), "+f"(d[78]), "+f"(d[79]),
      "+f"(d[80]), "+f"(d[81]), "+f"(d[82]), "+f"(d[83]), "+f"(d[84]), "+f"(d[85]), "+f"(d[86]), "+f"(d[87]),
      "+f"(d[88]), "+f"(d[89]), "+f"(d[90]), "+f"(d[91]), "+f"(d[92]), "+f"(d[93]), "+f"(d[94]), "+f"(d[95])
    : "l"(descA), "l"(descB), "r"(scaleD));
}

__device__ __forceinline__ void ldsm4t(uint32_t (&b)[4], uint32_t addr) {
  asm volatile("ldmatrix.sync.aligned.m8n8.x4.trans.shared.b16 {%0,%1,%2,%3}, [%4];"
               : "=r"(b[0]), "=r"(b[1]), "=r"(b[2]), "=r"(b[3])
               : "r"(addr));
}
__device__ __forceinline__ void hmma(float (&c)[4], uint32_t a0, uint32_t a1, uint32_t a2, uint32_t a3, uint32_t b0, uint32_t b1) {
  asm("mma.sync.aligned.m16n8k16.row.col.f32.bf16.bf16.f32 {%0,%1,%2,%3}, {%4,%5,%6,%7}, {%8,%9}, {%0,%1,%2,%3};"
      : "+f"(c[0]), "+f"(c[1]), "+f"(c[2]), "+f"(c[3])
      : "r"(a0), "r"(a1), "r"(a2), "r"(a3), "r"(b0), "r"(b1));
}

__device__ __forceinline__ uint32_t movm(uint32_t a) {
  uint32_t d;
  asm volatile("movmatrix.sync.aligned.m8n8.trans.b16 %0, %1;" : "=r"(d) : "r"(a));
  return d;
}

constexpr int K1_STAGES = 4;
constexpr int K1_W_BYTES = 3 * 8192;
constexpr int K1_X_BYTES = 8 * 16384;
constexpr int K1_BAR_OFF = K1_X_BYTES + K1_STAGES * K1_W_BYTES;
constexpr int K1_SMEM = K1_BAR_OFF + 192 + 1024;
constexpr float QSCALE = 0.25f * 1.4426950408889634f;

__device__ __forceinline__ uint32_t phi2(uint32_t t2) {
  uint32_t a2, mask, r2, o2;
  asm("add.rn.bf16x2 %0, %1, %2;" : "=r"(a2) : "r"(t2), "r"(0x3F803F80u));
  const uint32_t e2 = pack_bf16(ex2f(bf_lo(t2) * 1.4426950408889634f), ex2f(bf_hi(t2) * 1.4426950408889634f));
  asm("set.gt.u32.bf16x2 %0, %1, %2;" : "=r"(mask) : "r"(t2), "r"(0u));
  r2 = (a2 & mask) | (e2 & ~mask);
  asm("add.rn.bf16x2 %0, %1, %2;" : "=r"(o2) : "r"(r2), "r"(0x35863586u));
  return o2;
}

#define K1_SLOT_KB(h) ((h) < 4 ? 2 * (h) : 2 * ((h) - 4) + 1)
struct EpiCtx {
  uint4* qf;
  uint32_t* kp;
  uint32_t* vp;
  uint32_t* s_red;
  float* red;
  int lane;
};

template <bool LINEAR, int J, int HH, int PART>
__device__ __forceinline__ void epi_slice(const float (&acc)[96], const EpiCtx& c, uint32_t (&pk)[4], float& vmax) {
  constexpr int h = J * 4 + HH;
  const float* a = &acc[HH * 8];
  const float* k = &acc[32 + HH * 8];
  const float* v = &acc[64 + HH * 8];
  if (!LINEAR) {
    if (PART == 0) {
      c.qf[h * 32 * 128] = make_uint4(pack_bf16(a[0] * QSCALE, a[1] * QSCALE), pack_bf16(a[2] * QSCALE, a[3] * QSCALE),
                                      pack_bf16(a[4] * QSCALE, a[5] * QSCALE), pack_bf16(a[6] * QSCALE, a[7] * QSCALE));
      uint32_t* kh = c.kp + h * (KV_HEAD_BYTES / 4);
      kh[0] = pack_bf16(k[0], k[1]);
      kh[64] = pack_bf16(k[2], k[3]);
      kh[32] = pack_bf16(k[4], k[5]);
      kh[96] = pack_bf16(k[6], k[7]);
      float q0 = a[0] * a[0] + a[1] * a[1] + a[4] * a[4] + a[5] * a[5];
      float q1 = a[2] * a[2] + a[3] * a[3] + a[6] * a[6] + a[7] * a[7];
      float k0 = k[0] * k[0] + k[1] * k[1] + k[4] * k[4] + k[5] * k[5];
      float k1 = k[2] * k[2] + k[3] * k[3] + k[6] * k[6] + k[7] * k[7];
#pragma unroll
      for (int o = 1; o <= 2; o <<= 1) {
        q0 += __shfl_xor_sync(0xffffffffu, q0, o);
        q1 += __shfl_xor_sync(0xffffffffu, q1, o);
        k0 += __shfl_xor_sync(0xffffffffu, k0, o);
        k1 += __shfl_xor_sync(0xffffffffu, k1, o);
      }
      const uint32_t qm = __reduce_max_sync(0xffffffffu, max(__float_as_uint(q0) & 0x7FFFFFFFu, __float_as_uint(q1) & 0x7FFFFFFFu));
      const uint32_t km = __reduce_max_sync(0xffffffffu, max(__float_as_uint(k0) & 0x7FFFFFFFu, __float_as_uint(k1) & 0x7FFFFFFFu));
      if (c.lane == 0) {
        atomicMax(&c.s_red[h * 2 + 0], qm);
        atomicMax(&c.s_red[h * 2 + 1], km);
      }
    } else {
      uint32_t* vh = c.vp + h * (KV_HEAD_BYTES / 4);
      vh[0] = pack_bf16(v[0], v[1]);
      vh[96] = pack_bf16(v[2], v[3]);
      vh[32] = pack_bf16(v[4], v[5]);
      vh[128] = pack_bf16(v[6], v[7]);
      vh[64] = 0x3F803F80u;
      vh[160] = 0x3F803F80u;
#pragma unroll
      for (int i = 0; i < 8; i++) asm("max.NaN.f32 %0, %0, %1;" : "+f"(vmax) : "f"(fabsf(v[i])));
    }
  } else {
    if (PART == 0) {
      c.qf[h * 32 * 128] = make_uint4(phi2(pack_bf16(a[0], a[1])), phi2(pack_bf16(a[2], a[3])), phi2(pack_bf16(a[4], a[5])),
                                      phi2(pack_bf16(a[6], a[7])));
      pk[0] = movm(phi2(pack_bf16(k[0], k[1])));
      pk[2] = movm(phi2(pack_bf16(k[2], k[3])));
      pk[1] = movm(phi2(pack_bf16(k[4], k[5])));
      pk[3] = movm(phi2(pack_bf16(k[6], k[7])));
    } else {
      const uint32_t b0 = movm(pack_bf16(v[0], v[1]));
      const uint32_t b1 = movm(pack_bf16(v[2], v[3]));
      const uint32_t b2 = movm(pack_bf16(v[4], v[5]));
      const uint32_t b3 = movm(pack_bf16(v[6], v[7]));
      float c0[4] = {0, 0, 0, 0}, c1[4] = {0, 0, 0, 0}, c2[4] = {0, 0, 0, 0};
      hmma(c0, pk[0], pk[1], pk[2], pk[3], b0, b1);
      hmma(c1, pk[0], pk[1], pk[2], pk[3], b2, b3);
      hmma(c2, pk[0], pk[1], pk[2], pk[3], 0x3F803F80u, 0x3F803F80u);
      float* slot = c.red + K1_SLOT_KB(h) * 4096;
#pragma unroll
      for (int i = 0; i < 4; i++) {
        slot[i * 32] = c0[i];
        slot[(4 + i) * 32] = c1[i];
        slot[(8 + i) * 32] = c2[i];
      }
    }
  }
}

template <bool LINEAR>
__device__ __forceinline__ void qkv_consumer(uint32_t sbase, uint8_t* smem_gen, uint32_t* s_red, int cp, int rt) {
  const uint32_t bar_full = sbase + K1_BAR_OFF;
  const uint32_t bar_empty = bar_full + 8 * K1_STAGES;
  const int warp = threadIdx.x >> 5;
  const int wg = warp >> 2;
  const int lane = threadIdx.x & 31;
  float acc0[96], acc1[96];
#pragma unroll 1
  for (int kb = 0; kb < 8; kb++) {
    const int s = kb % K1_STAGES;
    mbar_wait(bar_full + 8 * s, (kb / K1_STAGES) & 1);
    if (threadIdx.x == 0) PROF_T(0, 2 + (kb >> 1));
    const uint64_t dA = mkdesc(sbase + kb * 16384 + wg * 8192, 16, 1024, 1);
    const uint64_t dB = mkdesc(sbase + K1_X_BYTES + s * K1_W_BYTES, 8192, 1024, 1);
    wg_fence();
#pragma unroll
    for (int k = 0; k < 4; k++) wgmma_ss_n192_tb(acc0, dA + k * 2, dB + k * 128, (kb | k) != 0);
    wg_commit();
    if (kb > 0) {
      wg_wait<1>();
      if ((threadIdx.x & 127) == 0) {
        const int sp = (kb - 1) % K1_STAGES;
        mbar_arrive_cluster(bar_empty + 8 * sp, 0);
        mbar_arrive_cluster(bar_empty + 8 * sp, 1);
      }
    }
  }
  wg_wait<0>();
  fence_regs(acc0);
  if ((threadIdx.x & 127) == 0) {
    mbar_arrive_cluster(bar_empty + 8 * (7 % K1_STAGES), 0);
    mbar_arrive_cluster(bar_empty + 8 * (7 % K1_STAGES), 1);
  }
  if (threadIdx.x == 0) PROF_T(0, 6);

  EpiCtx c;
  {
    const int row0 = rt * 128 + wg * 64 + (warp & 3) * 16;
    c.qf = g_qfrag + ((size_t)((LINEAR ? NH : 0) + cp * 8) * 32 + (rt * 2 + wg)) * 128 + (threadIdx.x & 127);
    uint32_t* img = reinterpret_cast<uint32_t*>(reinterpret_cast<uint8_t*>(g_kv) + (size_t)(cp * 8) * KV_HEAD_BYTES);
    c.kp = img + (row0 >> 3) * 64 + lane;
    c.vp = img + KV_K_BYTES / 4 + (row0 >> 3) * 96 + lane;
    c.s_red = s_red;
    c.red = reinterpret_cast<float*>(smem_gen + wg * 8192) + (warp & 3) * 384 + lane;
    c.lane = lane;
  }
  uint32_t pk[4];
  float vmax = 0.f;
#define K1_T1_STEP(KB)                                                                           \
  {                                                                                              \
    constexpr int g = 8 + KB;                                                                    \
    constexpr int s = g % K1_STAGES;                                                             \
    mbar_wait(bar_full + 8 * s, (g / K1_STAGES) & 1);                                            \
    const uint64_t dA = mkdesc(sbase + KB * 16384 + wg * 8192, 16, 1024, 1);                     \
    const uint64_t dB = mkdesc(sbase + K1_X_BYTES + s * K1_W_BYTES, 8192, 1024, 1);              \
    wg_fence();                                                                                  \
    _Pragma("unroll") for (int k = 0; k < 4; k++) wgmma_ss_n192_tb(acc1, dA + k * 2, dB + k * 128, (KB | k) != 0); \
    wg_commit();                                                                                 \
    epi_slice<LINEAR, 0, KB / 2, KB & 1>(acc0, c, pk, vmax);                                     \
    wg_wait<0>();                                                                                \
    if (KB + K1_STAGES < 8 && (threadIdx.x & 127) == 0) {                                        \
      mbar_arrive_cluster(bar_empty + 8 * s, 0);                                                 \
      mbar_arrive_cluster(bar_empty + 8 * s, 1);                                                 \
    }                                                                                            \
  }
  K1_T1_STEP(0) K1_T1_STEP(1) K1_T1_STEP(2) K1_T1_STEP(3) K1_T1_STEP(4) K1_T1_STEP(5) K1_T1_STEP(6) K1_T1_STEP(7)
#undef K1_T1_STEP
  fence_regs(acc1);
  if (threadIdx.x == 0) PROF_T(0, 10);
  epi_slice<LINEAR, 1, 0, 0>(acc1, c, pk, vmax);
  epi_slice<LINEAR, 1, 0, 1>(acc1, c, pk, vmax);
  epi_slice<LINEAR, 1, 1, 0>(acc1, c, pk, vmax);
  epi_slice<LINEAR, 1, 1, 1>(acc1, c, pk, vmax);
  epi_slice<LINEAR, 1, 2, 0>(acc1, c, pk, vmax);
  epi_slice<LINEAR, 1, 2, 1>(acc1, c, pk, vmax);
  epi_slice<LINEAR, 1, 3, 0>(acc1, c, pk, vmax);
  epi_slice<LINEAR, 1, 3, 1>(acc1, c, pk, vmax);
  if (!LINEAR) {
    const uint32_t vm = __reduce_max_sync(0xffffffffu, __float_as_uint(vmax) & 0x7FFFFFFFu);
    if (lane == 0) atomicMax(&s_red[16], vm);
    asm volatile("bar.sync 1, 256;" ::: "memory");
    if (threadIdx.x < 8) {
      *reinterpret_cast<float4*>(&g_nrm[((cp * 8 + threadIdx.x) * 16 + rt) * 4]) =
          make_float4(__uint_as_float(s_red[threadIdx.x * 2]), __uint_as_float(s_red[threadIdx.x * 2 + 1]), __uint_as_float(s_red[16]), 0.f);
    }
  } else {
    asm volatile("bar.sync 1, 256;" ::: "memory");
    float* dst = g_kvpart + ((size_t)rt * NH + cp * 8) * 384;
#pragma unroll
    for (int i = 0; i < 12; i++) {
      const int o = threadIdx.x + i * 256;
      const int h = o / 384, e = o - h * 384;
      const float* src = reinterpret_cast<const float*>(smem_gen) + K1_SLOT_KB(h) * 4096 + e;
      float sum = 0.f;
#pragma unroll
      for (int w = 0; w < 8; w++) sum += src[(w >> 2) * 2048 + (w & 3) * 384];
      dst[o] = sum;
    }
  }
}

__global__ void __launch_bounds__(384, 1)
qkv_gemm_kernel(const __grid_constant__ CUtensorMap mxA, const __grid_constant__ CUtensorMap mxB,
                const __grid_constant__ CUtensorMap mwA, const __grid_constant__ CUtensorMap mwB) {
  extern __shared__ uint8_t smem_raw[];
  const uint32_t sbase = (smem_u32(smem_raw) + 1023) & ~1023u;
  uint8_t* smem_gen = smem_raw + (sbase - smem_u32(smem_raw));
  const uint32_t bar_full = sbase + K1_BAR_OFF;
  const uint32_t bar_empty = bar_full + 8 * K1_STAGES;
  uint32_t* s_red = reinterpret_cast<uint32_t*>(smem_gen + K1_BAR_OFF + 64);

  const int rank = blockIdx.x & 1;
  const int pair = blockIdx.x >> 1;
  const int branch = pair >> 5;
  const int rp = (pair & 31) >> 2;
  const int cp = pair & 3;
  const int rt = rp * 2 + rank;
  const int warp = threadIdx.x >> 5;
  if (threadIdx.x == 0) { PROF_G(0, 30); PROF_T(0, 0); }
  const CUtensorMap* mx = branch ? &mxA : &mxB;
  const CUtensorMap* mw = branch ? &mwA : &mwB;

  if (threadIdx.x == 256) {
    asm volatile("prefetch.tensormap [%0];" ::"l"(mx) : "memory");
    asm volatile("prefetch.tensormap [%0];" ::"l"(mw) : "memory");
    for (int i = 0; i < K1_STAGES; i++) {
      mbar_init(bar_full + 8 * i, 1);
      mbar_init(bar_empty + 8 * i, 4);
    }
    fence_barrier_init();
    fence_proxy_async();
    for (int kb = 0; kb < K1_STAGES; kb++) mbar_expect_tx(bar_full + 8 * kb, 16384 + K1_W_BYTES);
    tma_load_2d(sbase, mx, 0, rt * 128, bar_full);
  }
  pdl_launch_dependents();
  if (threadIdx.x < 32) s_red[threadIdx.x] = 0;
  __syncthreads();
  cluster_sync_relaxed();
  if (threadIdx.x == 0) PROF_T(0, 1);

  if (warp >= 8) {
    asm volatile("setmaxnreg.dec.sync.aligned.u32 40;");
    if (threadIdx.x == 256) {
      for (int g = 0; g < 16; g++) {
        const int s = g % K1_STAGES;
        const int kb = g & 7;
        if (g >= K1_STAGES) {
          mbar_wait(bar_empty + 8 * s, ((g / K1_STAGES) - 1) & 1);
          mbar_expect_tx(bar_full + 8 * s, (g < 8 ? 16384 : 0) + K1_W_BYTES);
        }
        if (g > 0 && g < 8) tma_load_2d(sbase + kb * 16384, mx, kb * 64, rt * 128, bar_full + 8 * s);
        const int h0 = cp * 8 + (g >> 3) * 4;
        const uint32_t st = sbase + K1_X_BYTES + s * K1_W_BYTES + rank * 4096;
#pragma unroll
        for (int p = 0; p < 3; p++)
          tma_load_2d_mc(st + p * 8192, mw, p * 512 + h0 * 16, kb * 64 + rank * 32, bar_full + 8 * s, (uint16_t)3);
      }
    }
    __syncwarp();
    cluster_sync_relaxed();
  } else {
    asm volatile("setmaxnreg.inc.sync.aligned.u32 232;");
    if (branch == 0) qkv_consumer<false>(sbase, smem_gen, s_red, cp, rt);
    else qkv_consumer<true>(sbase, smem_gen, s_red, cp, rt);
    if (threadIdx.x == 0) PROF_T(0, 11);
    __syncwarp();
    cluster_sync_relaxed();
    if (threadIdx.x == 0) { PROF_T(0, 12); PROF_G(0, 31); }
  }
}

constexpr int K2_SMEM = KV_HEAD_BYTES + 1024 + 256;

struct ExpC {
  uint32_t k3c00, kmask, seven, c3;
};
__device__ __forceinline__ uint32_t hfma2(uint32_t a, uint32_t b, uint32_t c) {
  uint32_t r;
  asm("fma.rn.f16x2 %0, %1, %2, %3;" : "=r"(r) : "r"(a), "r"(b), "r"(c));
  return r;
}
__device__ __forceinline__ uint32_t exp2_poly_pair(float t0, float t1, const ExpC& c) {
  uint32_t u;
  asm("prmt.b32 %0, %1, %2, 0x5410;" : "=r"(u) : "r"(__float_as_uint(t0)), "r"(__float_as_uint(t1)));
  uint32_t m;
  asm("lop3.b32 %0, %1, 0x03FF03FF, %2, 0xEA;" : "=r"(m) : "r"(u), "r"(c.k3c00));
  uint32_t p = hfma2(m, c.c3, 0x9fe09fe0u);
  p = hfma2(p, m, 0x37a137a1u);
  p = hfma2(p, m, 0x4ab94abau);
  uint32_t mu;
  asm("lop3.b32 %0, %1, 0xFC00FC00, %2, 0xEA;" : "=r"(mu) : "r"(u), "r"(c.kmask));
  uint32_t r;
  asm("{.reg .b32 t; shf.r.wrap.b32 t, %1, %2, 3; add.u32 %0, t, %3;}" : "=r"(r) : "r"(mu), "r"(c.seven), "r"(p));
  return r;
}
__device__ __forceinline__ float gadd(float x, float M, uint32_t g) {
  float r = x;
  asm("{.reg .pred p; setp.ne.b32 p, %2, -1; @p add.f32 %0, %0, %1;}" : "+f"(r) : "f"(M), "r"(g));
  return r;
}
__device__ __forceinline__ float gex2(float x, uint32_t g) {
  float r = x;
  asm("{.reg .pred p; setp.ne.b32 p, %1, -1; @p ex2.approx.ftz.f32 %0, %0;}" : "+f"(r) : "r"(g));
  return r;
}
template <int NPOLY, int NPAIR, int CH, int D>
__device__ __forceinline__ void exp_tile(const float (&s)[2 * NPAIR], uint32_t (&p)[NPAIR], const ExpC& c) {
#pragma unroll
  for (int i = 0; i < NPAIR; i++) {
    const bool isPoly = ((i + 1) * NPOLY / 32) != (i * NPOLY / 32);
    const int ch = i / CH;
    const bool gated = ch >= D;
    int gi = (ch - D) * CH + CH - 1;
    if (gated) {
      while (gi > (ch - D) * CH && !(((gi + 1) * NPOLY / 32) != (gi * NPOLY / 32))) gi--;
    }
    const uint32_t g = gated ? p[gi] : 0;
    if (!isPoly) {
      if (gated) p[i] = pack_bf16(gex2(s[2 * i], g), gex2(s[2 * i + 1], g));
      else p[i] = pack_bf16(ex2f(s[2 * i]), ex2f(s[2 * i + 1]));
    } else {
      if (gated) p[i] = exp2_poly_pair(gadd(s[2 * i], 12329.f, g), gadd(s[2 * i + 1], 12329.f, g), c);
      else p[i] = exp2_poly_pair(s[2 * i] + 12329.f, s[2 * i + 1] + 12329.f, c);
    }
  }
}

__device__ __forceinline__ void store_o(__nv_bfloat16* o, int row0, int head, int lane, const uint32_t (&r)[4]) {
  const int g = lane >> 2, t = lane & 3;
  uint32_t* p0 = reinterpret_cast<uint32_t*>(o + (size_t)(row0 + g) * DM + head * 16) + t;
  uint32_t* p1 = reinterpret_cast<uint32_t*>(o + (size_t)(row0 + g + 8) * DM + head * 16) + t;
  p0[0] = r[0];
  p1[0] = r[1];
  p0[4] = r[2];
  p1[4] = r[3];
}

template <bool SAFE>
__device__ __forceinline__ void attn_step(float (&s)[32], float (&o)[12], float& m0, float& m1, const uint4& qf, uint64_t dKn,
                                          uint64_t dV, const ExpC& ec) {
  uint32_t p[16];
  wg_wait<0>();
  fence_regs(s);
  if (!SAFE) {
    exp_tile<16, 16, 4, 2>(s, p, ec);
  } else {
    fence_regs(o);
    float x0 = s[0], x1 = s[2];
#pragma unroll
    for (int i = 0; i < 8; i++) {
      x0 = fmaxf(x0, fmaxf(s[4 * i], s[4 * i + 1]));
      x1 = fmaxf(x1, fmaxf(s[4 * i + 2], s[4 * i + 3]));
    }
    x0 = fmaxf(x0, __shfl_xor_sync(0xffffffffu, x0, 1));
    x1 = fmaxf(x1, __shfl_xor_sync(0xffffffffu, x1, 1));
    x0 = fmaxf(x0, __shfl_xor_sync(0xffffffffu, x0, 2));
    x1 = fmaxf(x1, __shfl_xor_sync(0xffffffffu, x1, 2));
    const float n0 = fmaxf(m0, x0), n1 = fmaxf(m1, x1);
    const float c0 = ex2f(m0 - n0), c1 = ex2f(m1 - n1);
    m0 = n0;
    m1 = n1;
#pragma unroll
    for (int i = 0; i < 3; i++) {
      o[4 * i] *= c0;
      o[4 * i + 1] *= c0;
      o[4 * i + 2] *= c1;
      o[4 * i + 3] *= c1;
    }
#pragma unroll
    for (int i = 0; i < 8; i++) {
      p[2 * i] = pack_bf16(ex2f(s[4 * i] - n0), ex2f(s[4 * i + 1] - n0));
      p[2 * i + 1] = pack_bf16(ex2f(s[4 * i + 2] - n1), ex2f(s[4 * i + 3] - n1));
    }
  }
  wg_fence();
  wgmma_rs_n64_z(s, qf.x, qf.y, qf.z, qf.w, dKn);
#pragma unroll
  for (int k = 0; k < 4; k++) wgmma_rs_n24_tb(o, p[4 * k], p[4 * k + 1], p[4 * k + 2], p[4 * k + 3], dV + k * 48, 1);
  wg_commit();
}

template <bool SAFE>
__device__ __forceinline__ void attn_tile(uint64_t dK, uint64_t dV, uint32_t bar, const uint4 qf, const ExpC& ec, uint32_t (&outp)[4]) {
  float s[32];
  float o[12];
#pragma unroll
  for (int i = 0; i < 12; i++) asm volatile("mov.f32 %0, 0f00000000;" : "=f"(o[i]));
  float m0 = -INFINITY, m1 = -INFINITY;
  mbar_wait(bar, 0);
  wg_fence();
  wgmma_rs_n64_z(s, qf.x, qf.y, qf.z, qf.w, dK);
  wg_commit();
#pragma unroll 1
  for (int c = 0; c < 4; c++) {
    if (c > 0) mbar_wait(bar + 8 * c, 0);
#pragma unroll 1
    for (int j = 0; j < 4; j++) {
      attn_step<SAFE>(s, o, m0, m1, qf, dK + 128, dV, ec);
      attn_step<SAFE>(s, o, m0, m1, qf, dK + 256, dV + 192, ec);
      dK += 256;
      dV += 384;
    }
  }
  wg_wait<0>();
  fence_regs(o);
  fence_regs(s);
  const float r0 = 1.0f / o[8], r1 = 1.0f / o[10];
  outp[0] = pack_bf16(o[0] * r0, o[1] * r0);
  outp[1] = pack_bf16(o[2] * r1, o[3] * r1);
  outp[2] = pack_bf16(o[4] * r0, o[5] * r0);
  outp[3] = pack_bf16(o[6] * r1, o[7] * r1);
}

__device__ __forceinline__ void linear_attn_cta(uint8_t* smem_raw, uint32_t sbase, const CUtensorMap* mo16, int cta) {
  const int warp = threadIdx.x >> 5, lane = threadIdx.x & 31;
  float* red = reinterpret_cast<float*>(smem_raw + (sbase - smem_u32(smem_raw)) + 131072);
  {
    const float* src = g_kvpart + (size_t)cta * 8 * 384;
    float sum[6];
#pragma unroll
    for (int i = 0; i < 6; i++) sum[i] = 0.f;
#pragma unroll
    for (int r = 0; r < 16; r++) {
#pragma unroll
      for (int i = 0; i < 6; i++) sum[i] += src[(size_t)r * NH * 384 + threadIdx.x + i * 512];
    }
#pragma unroll
    for (int i = 0; i < 6; i++) red[threadIdx.x + i * 512] = round_bf16(sum[i]);
  }
  __syncthreads();
  uint32_t bf[8][6];
  {
    const int g = lane >> 2, t = lane & 3;
#pragma unroll
    for (int h = 0; h < 8; h++) {
#pragma unroll
      for (int f = 0; f < 6; f++) {
        const int blk = f >> 1, half = f & 1;
        const int e = (blk == 2) ? 0 : g;
        const int d = 2 * t + 8 * half;
        const int base = h * 384 + (blk * 4 + half * 2 + (e & 1)) * 32 + (e >> 1);
        bf[h][f] = pack_bf16(red[base + (d & 7) * 4], red[base + ((d + 1) & 7) * 4]);
      }
    }
  }
  const uint32_t stg = sbase + warp * 8192;
#pragma unroll 1
  for (int rb = 0; rb < 8; rb++) {
    const int blk16 = rb * 16 + warp;
    const uint4* qp = g_qfrag + ((size_t)(NH + cta * 8) * 32 + (blk16 >> 2)) * 128 + (blk16 & 3) * 32 + lane;
    uint4 q[8];
#pragma unroll
    for (int h = 0; h < 8; h++) q[h] = qp[h * 32 * 128];
    const uint32_t buf = stg + (rb & 1) * 4096;
    if (rb >= 2) {
      if (lane == 0) asm volatile("cp.async.bulk.wait_group.read 1;" ::: "memory");
      __syncwarp();
    }
#pragma unroll
    for (int h = 0; h < 8; h++) {
      float n0[4] = {0, 0, 0, 0}, n1[4] = {0, 0, 0, 0}, dn[4] = {0, 0, 0, 0};
      hmma(n0, q[h].x, q[h].y, q[h].z, q[h].w, bf[h][0], bf[h][1]);
      hmma(n1, q[h].x, q[h].y, q[h].z, q[h].w, bf[h][2], bf[h][3]);
      hmma(dn, q[h].x, q[h].y, q[h].z, q[h].w, bf[h][4], bf[h][5]);
      const float d0 = round_bf16(round_bf16(dn[0]) + 1e-6f), d1 = round_bf16(round_bf16(dn[2]) + 1e-6f);
      const uint32_t r0 = pack_bf16(__fdividef(round_bf16(n0[0]), d0), __fdividef(round_bf16(n0[1]), d0));
      const uint32_t r1 = pack_bf16(__fdividef(round_bf16(n0[2]), d1), __fdividef(round_bf16(n0[3]), d1));
      const uint32_t r2 = pack_bf16(__fdividef(round_bf16(n1[0]), d0), __fdividef(round_bf16(n1[1]), d0));
      const uint32_t r3 = pack_bf16(__fdividef(round_bf16(n1[2]), d1), __fdividef(round_bf16(n1[3]), d1));
      const int row = lane & 15;
      const int chunk = (h & 3) * 2 + (lane >> 4);
      const uint32_t addr = buf + (h >> 2) * 2048 + row * 128 + ((chunk ^ (row & 7)) << 4);
      asm volatile("stmatrix.sync.aligned.m8n8.x4.shared.b16 [%0], {%1,%2,%3,%4};" ::"r"(addr), "r"(r0), "r"(r1), "r"(r2), "r"(r3)
                   : "memory");
    }
    fence_proxy_async();
    __syncwarp();
    if (lane == 0) {
      tma_store_2d(mo16, buf, cta * 128, blk16 * 16);
      tma_store_2d(mo16, buf + 2048, cta * 128 + 64, blk16 * 16);
      asm volatile("cp.async.bulk.commit_group;" ::: "memory");
    }
  }
  if (lane == 0) asm volatile("cp.async.bulk.wait_group 0;" ::: "memory");
}

__global__ void __launch_bounds__(512, 1) attn_kernel(const __grid_constant__ CUtensorMap mo16) {
  extern __shared__ uint8_t smem_raw[];
  const uint32_t sbase = (smem_u32(smem_raw) + 1023) & ~1023u;
  const uint32_t bar = sbase + KV_HEAD_BYTES;
  if (threadIdx.x == 0) { PROF_G(1, 30); PROF_T(1, 0); }
  if (threadIdx.x == 0) {
    for (int i = 0; i < 4; i++) mbar_init(bar + 8 * i, 1);
    fence_barrier_init();
    fence_proxy_async();
  }
  __syncthreads();
  pdl_launch_dependents();
  pdl_wait();
  if (blockIdx.x >= 128) {
    linear_attn_cta(smem_raw, sbase, &mo16, blockIdx.x - 128);
    if (threadIdx.x == 0) { PROF_T(1, 5); PROF_G(1, 31); }
    return;
  }
  const int head = blockIdx.x >> 2, qb = blockIdx.x & 3;
  if (threadIdx.x == 0) {
    const uint8_t* img = reinterpret_cast<const uint8_t*>(g_kv) + (size_t)head * KV_HEAD_BYTES;
    mbar_expect_tx(bar, 32768 + 24576);
    bulk_load(sbase, img, 32768, bar);
    bulk_load(sbase + KV_K_BYTES, img + KV_K_BYTES, 24576, bar);
    for (int i = 1; i < 4; i++) {
      mbar_expect_tx(bar + 8 * i, (i < 3 ? 16384 : 0) + 24576);
      if (i < 3) bulk_load(sbase + (i + 1) * 16384, img + (i + 1) * 16384, 16384, bar + 8 * i);
      bulk_load(sbase + KV_K_BYTES + i * 24576, img + KV_K_BYTES + i * 24576, 24576, bar + 8 * i);
    }
  }
  const int lane = threadIdx.x & 31;
  bool safe_path;
  {
    float4 n = make_float4(0.f, 0.f, 0.f, 0.f);
    if (lane < 16) n = *reinterpret_cast<const float4*>(&g_nrm[(head * 16 + lane) * 4]);
    uint32_t qm = ((lane >> 2) == qb) ? __float_as_uint(n.x) : 0u;
    qm = __reduce_max_sync(0xffffffffu, qm);
    const uint32_t km = __reduce_max_sync(0xffffffffu, __float_as_uint(n.y));
    const uint32_t vm = __reduce_max_sync(0xffffffffu, __float_as_uint(n.z));
    const float b2 = __uint_as_float(qm) * (QSCALE * QSCALE) * __uint_as_float(km) * 1.02f;
    const float vmax = __uint_as_float(vm);
    const bool ok = (b2 <= 21.5f * 21.5f) && (vmax <= 1.0e24f) && (vmax >= 1.0e-18f || vmax == 0.f);
    safe_path = !ok;
  }
  const int wg = threadIdx.x >> 7, warp = (threadIdx.x >> 5) & 3;
  uint32_t zero;
  asm volatile("mov.u32 %0, %%smid;" : "=r"(zero));
  zero >>= 16;
  const ExpC ec{0x3C003C00u + zero, 0x00070000u + zero, 7u + zero, 0x2cfd2cfdu + zero};
  const uint64_t dK = mkdesc(sbase, 128, 256, 0);
  const uint64_t dV = mkdesc(sbase + KV_K_BYTES, 384, 128, 0);
#pragma unroll 1
  for (int t = 0; t < 2; t++) {
    const int tile64 = qb * 8 + wg * 2 + t;
    const uint4 qf = g_qfrag[(head * 32 + tile64) * 128 + (threadIdx.x & 127)];
    uint32_t r[4];
    if (threadIdx.x == 0) PROF_T(1, 1 + t);
    if (!safe_path) attn_tile<false>(dK, dV, bar, qf, ec, r);
    else attn_tile<true>(dK, dV, bar, qf, ec, r);
    store_o(g_o + (size_t)S_LEN * DM, tile64 * 64 + warp * 16, head, lane, r);
  }
  if (threadIdx.x == 0) { PROF_T(1, 5); PROF_G(1, 31); }
}

constexpr int K3_STAGES = 5;
constexpr int K3_W_BYTES = 8 * 16384;
constexpr int K3_BAR_OFF = K3_W_BYTES + K3_STAGES * 16384;
constexpr int K3_SMEM = K3_BAR_OFF + 256 + 1024;

__global__ void __launch_bounds__(288, 1)
out_gemm_kernel(const __grid_constant__ CUtensorMap mo, const __grid_constant__ CUtensorMap mwA,
                const __grid_constant__ CUtensorMap mwB, const __grid_constant__ CUtensorMap mout) {
  extern __shared__ uint8_t smem_raw[];
  const uint32_t sbase = (smem_u32(smem_raw) + 1023) & ~1023u;
  const uint32_t bar_full = sbase + K3_BAR_OFF;
  const uint32_t bar_empty = bar_full + 8 * K3_STAGES;
  const uint32_t bar_w = bar_empty + 8 * K3_STAGES;
  const int branch = blockIdx.x >> 6;
  const int rt = (blockIdx.x & 63) >> 2;
  const int ct = blockIdx.x & 3;
  const int warp = threadIdx.x >> 5;
  if (threadIdx.x == 0) { PROF_G(2, 30); PROF_T(2, 0); }
  if (threadIdx.x == 256) {
    const CUtensorMap* mw = branch ? &mwB : &mwA;
    asm volatile("prefetch.tensormap [%0];" ::"l"(mw) : "memory");
    asm volatile("prefetch.tensormap [%0];" ::"l"(&mo) : "memory");
    asm volatile("prefetch.tensormap [%0];" ::"l"(&mout) : "memory");
    for (int i = 0; i < K3_STAGES; i++) {
      mbar_init(bar_full + 8 * i, 1);
      mbar_init(bar_empty + 8 * i, 2);
    }
    for (int i = 0; i < 8; i++) mbar_init(bar_w + 8 * i, 1);
    fence_barrier_init();
    fence_proxy_async();
    for (int kb = 0; kb < 8; kb++) {
      mbar_expect_tx(bar_w + 8 * kb, 16384);
      tma_load_2d(sbase + kb * 16384, mw, ct * 128, kb * 64, bar_w + 8 * kb);
      tma_load_2d(sbase + kb * 16384 + 8192, mw, ct * 128 + 64, kb * 64, bar_w + 8 * kb);
    }
  }
  __syncthreads();
  if (warp == 8) {
    if ((threadIdx.x & 31) == 0) {
      pdl_wait();
      PROF_T(2, 1);
      for (int kb = 0; kb < 8; kb++) {
        const int s = kb % K3_STAGES;
        if (kb >= K3_STAGES) mbar_wait(bar_empty + 8 * s, ((kb / K3_STAGES) - 1) & 1);
        mbar_expect_tx(bar_full + 8 * s, 16384);
        tma_load_2d(sbase + K3_W_BYTES + s * 16384, &mo, kb * 64, branch * S_LEN + rt * 128, bar_full + 8 * s);
      }
    }
  } else {
    const int wg = warp >> 2;
    float acc[64];
    for (int kb = 0; kb < 8; kb++) {
      const int s = kb % K3_STAGES;
      mbar_wait(bar_w + 8 * kb, 0);
      mbar_wait(bar_full + 8 * s, (kb / K3_STAGES) & 1);
      if (threadIdx.x == 0) PROF_T(2, 2 + kb);
      const uint64_t dA = mkdesc(sbase + K3_W_BYTES + s * 16384 + wg * 8192, 16, 1024, 1);
      const uint64_t dB = mkdesc(sbase + kb * 16384, 8192, 1024, 1);
      wg_fence();
#pragma unroll
      for (int k = 0; k < 4; k++) wgmma_ss_n128_tb(acc, dA + k * 2, dB + k * 128, (kb | k) != 0);
      wg_commit();
      if (kb > 0) {
        wg_wait<1>();
        if ((threadIdx.x & 127) == 0) mbar_arrive(bar_empty + 8 * ((kb - 1) % K3_STAGES));
      }
    }
    wg_wait<0>();
    fence_regs(acc);
    if (threadIdx.x == 0) PROF_T(2, 10);
    const uint32_t stg = sbase + K3_W_BYTES + wg * 8192;
    asm volatile("bar.sync 1, 256;" ::: "memory");
    const int lane = threadIdx.x & 31;
    const int rloc = (warp & 3) * 16 + (lane & 15);
#pragma unroll
    for (int c16 = 0; c16 < 8; c16++) {
      const float* a = &acc[c16 * 8];
      const uint32_t r0 = pack_bf16(a[0], a[1]), r1 = pack_bf16(a[2], a[3]), r2 = pack_bf16(a[4], a[5]), r3 = pack_bf16(a[6], a[7]);
      const int chunk = (c16 & 3) * 2 + (lane >> 4);
      const uint32_t addr = stg + (c16 >> 2) * 16384 + rloc * 128 + ((chunk ^ (rloc & 7)) << 4);
      asm volatile("stmatrix.sync.aligned.m8n8.x4.shared.b16 [%0], {%1,%2,%3,%4};" ::"r"(addr), "r"(r0), "r"(r1), "r"(r2), "r"(r3)
                   : "memory");
    }
    fence_proxy_async();
    asm volatile("bar.sync %0, 128;" ::"r"(2 + wg) : "memory");
    if ((threadIdx.x & 127) == 0) {
      tma_store_2d(&mout, stg, branch * DM + ct * 128, rt * 128 + wg * 64);
      tma_store_2d(&mout, stg + 16384, branch * DM + ct * 128 + 64, rt * 128 + wg * 64);
      asm volatile("cp.async.bulk.commit_group;" ::: "memory");
      asm volatile("cp.async.bulk.wait_group.read 0;" ::: "memory");
      if (threadIdx.x == 0) { PROF_T(2, 12); PROF_G(2, 31); }
    }
  }
}

typedef CUresult (*EncodeFn)(CUtensorMap*, CUtensorMapDataType, cuuint32_t, void*, const cuuint64_t*, const cuuint64_t*,
                             const cuuint32_t*, const cuuint32_t*, CUtensorMapInterleave, CUtensorMapSwizzle,
                             CUtensorMapL2promotion, CUtensorMapFloatOOBfill);

void make_map(EncodeFn enc, CUtensorMap* m, const void* ptr, uint64_t inner, uint64_t outer, uint32_t box_inner, uint32_t box_outer) {
  cuuint64_t dims[2] = {inner, outer};
  cuuint64_t strides[1] = {inner * 2};
  cuuint32_t box[2] = {box_inner, box_outer};
  cuuint32_t es[2] = {1, 1};
  enc(m, CU_TENSOR_MAP_DATA_TYPE_BFLOAT16, 2, const_cast<void*>(ptr), dims, strides, box, es, CU_TENSOR_MAP_INTERLEAVE_NONE,
      CU_TENSOR_MAP_SWIZZLE_128B, CU_TENSOR_MAP_L2_PROMOTION_L2_256B, CU_TENSOR_MAP_FLOAT_OOB_FILL_NONE);
}

struct HostState {
  bool init;
  const void* key[7];
  CUtensorMap mxA, mxB, mwA, mwB, mo, mo16, mwoA, mwoB, mout;
};
HostState g_hs;

}

extern "C" void kernel_launch(void* const* d_in, const int* in_sizes, int n_in, void* d_out, int out_size) {
  (void)in_sizes; (void)n_in; (void)out_size;
  HostState& hs = g_hs;
  bool same = hs.init && hs.key[6] == d_out;
  for (int i = 0; i < 6 && same; i++) same = hs.key[i] == d_in[i];
  if (!same) {
    void* fn = nullptr;
    cudaDriverEntryPointQueryResult qr;
    cudaGetDriverEntryPoint("cuTensorMapEncodeTiled", &fn, cudaEnableDefault, &qr);
    EncodeFn enc = (EncodeFn)fn;
    void* go = nullptr;
    cudaGetSymbolAddress(&go, g_o);
    make_map(enc, &hs.mxA, d_in[0], 512, 2048, 64, 128);
    make_map(enc, &hs.mwA, d_in[1], 1536, 512, 64, 32);
    make_map(enc, &hs.mwoA, d_in[2], 512, 512, 64, 64);
    make_map(enc, &hs.mxB, d_in[3], 512, 2048, 64, 128);
    make_map(enc, &hs.mwB, d_in[4], 1536, 512, 64, 32);
    make_map(enc, &hs.mwoB, d_in[5], 512, 512, 64, 64);
    make_map(enc, &hs.mo, go, 512, 4096, 64, 128);
    make_map(enc, &hs.mo16, go, 512, 4096, 64, 16);
    make_map(enc, &hs.mout, d_out, 1024, 2048, 64, 64);
    cudaFuncSetAttribute(qkv_gemm_kernel, cudaFuncAttributeMaxDynamicSharedMemorySize, K1_SMEM);
    cudaFuncSetAttribute(attn_kernel, cudaFuncAttributeMaxDynamicSharedMemorySize, K2_SMEM);
    cudaFuncSetAttribute(out_gemm_kernel, cudaFuncAttributeMaxDynamicSharedMemorySize, K3_SMEM);
    for (int i = 0; i < 6; i++) hs.key[i] = d_in[i];
    hs.key[6] = d_out;
    hs.init = true;
  }
  cudaStream_t st = cudaStreamPerThread;
  {
    cudaLaunchConfig_t cfg = {};
    cfg.gridDim = dim3(128);
    cfg.blockDim = dim3(384);
    cfg.dynamicSmemBytes = K1_SMEM;
    cfg.stream = st;
    cudaLaunchAttribute at[1];
    at[0].id = cudaLaunchAttributeClusterDimension;
    at[0].val.clusterDim.x = 2;
    at[0].val.clusterDim.y = 1;
    at[0].val.clusterDim.z = 1;
    cfg.attrs = at;
    cfg.numAttrs = 1;
    cudaLaunchKernelEx(&cfg, qkv_gemm_kernel, hs.mxA, hs.mxB, hs.mwA, hs.mwB);
  }
  {
    cudaLaunchConfig_t cfg = {};
    cfg.gridDim = dim3(132);
    cfg.blockDim = dim3(512);
    cfg.dynamicSmemBytes = K2_SMEM;
    cfg.stream = st;
    cudaLaunchAttribute at[1];
    at[0].id = cudaLaunchAttributeProgrammaticStreamSerialization;
    at[0].val.programmaticStreamSerializationAllowed = 1;
    cfg.attrs = at;
    cfg.numAttrs = 1;
    cudaLaunchKernelEx(&cfg, attn_kernel, hs.mo16);
    cfg.gridDim = dim3(128);
    cfg.blockDim = dim3(288);
    cfg.dynamicSmemBytes = K3_SMEM;
    cudaLaunchKernelEx(&cfg, out_gemm_kernel, hs.mo, hs.mwoA, hs.mwoB, hs.mout);
  }
}
```

```cpp
#include <cuda_runtime.h>
#include <cuda_bf16.h>
#include <cuda.h>
#include <stdint.h>

namespace {

constexpr int S_LEN = 2048;
constexpr int DM = 512;
constexpr int NH = 32;

constexpr int KV_K_BYTES = 65536;
constexpr int KV_HEAD_BYTES = KV_K_BYTES + 98304;
__device__ uint4 g_qfrag[2 * NH * 32 * 128];
__device__ uint4 g_kv[NH * KV_HEAD_BYTES / 16];
__device__ float g_kvpart[16 * NH * 384];
__device__ float g_nrm[NH * 16 * 4];
__device__ __nv_bfloat16 g_o[2 * S_LEN * DM];

#define PROF_T(k, i) do {} while (0)
#define PROF_G(k, i) do {} while (0)
__device__ __forceinline__ uint32_t smem_u32(const void* p) { return (uint32_t)__cvta_generic_to_shared(p); }
__device__ __forceinline__ void mbar_init(uint32_t bar, int cnt) {
  asm volatile("mbarrier.init.shared::cta.b64 [%0], %1;" ::"r"(bar), "r"(cnt) : "memory");
}
__device__ __forceinline__ void mbar_expect_tx(uint32_t bar, uint32_t bytes) {
  asm volatile("mbarrier.arrive.expect_tx.shared::cta.b64 _, [%0], %1;" ::"r"(bar), "r"(bytes) : "memory");
}
__device__ __forceinline__ void mbar_arrive(uint32_t bar) {
  asm volatile("mbarrier.arrive.shared::cta.b64 _, [%0];" ::"r"(bar) : "memory");
}
__device__ __forceinline__ void mbar_arrive_cluster(uint32_t bar, uint32_t cta) {
  asm volatile(
      "{\n.reg .b32 ra;\nmapa.shared::cluster.u32 ra, %0, %1;\n"
      "mbarrier.arrive.shared::cluster.b64 _, [ra];\n}" ::"r"(bar), "r"(cta) : "memory");
}
__device__ __forceinline__ void mbar_wait(uint32_t bar, uint32_t parity) {
  asm volatile(
      "{\n.reg .pred p;\n"
      "WAIT_LOOP:\n"
      "mbarrier.try_wait.parity.shared::cta.b64 p, [%0], %1, 0x989680;\n"
      "@p bra WAIT_DONE;\n"
      "bra WAIT_LOOP;\n"
      "WAIT_DONE:\n}" ::"r"(bar), "r"(parity) : "memory");
}
__device__ __forceinline__ void mbar_wait_cluster(uint32_t bar, uint32_t parity) {
  asm volatile(
      "{\n.reg .pred p;\n"
      "WAIT_LOOP:\n"
      "mbarrier.try_wait.parity.acquire.cluster.shared::cta.b64 p, [%0], %1, 0x989680;\n"
      "@p bra WAIT_DONE;\n"
      "bra WAIT_LOOP;\n"
      "WAIT_DONE:\n}" ::"r"(bar), "r"(parity) : "memory");
}
__device__ __forceinline__ void fence_barrier_init() {
  asm volatile("fence.mbarrier_init.release.cluster;" ::: "memory");
}
__device__ __forceinline__ void fence_proxy_async() { asm volatile("fence.proxy.async.shared::cta;" ::: "memory"); }
__device__ __forceinline__ void cluster_sync_relaxed() {
  asm volatile("barrier.cluster.arrive.relaxed.aligned;\nbarrier.cluster.wait.aligned;" ::: "memory");
}
__device__ __forceinline__ void tma_load_2d(uint32_t dst, const CUtensorMap* m, int x, int y, uint32_t bar) {
  asm volatile(
      "cp.async.bulk.tensor.2d.shared::cluster.global.mbarrier::complete_tx::bytes [%0], [%1, {%3, %4}], [%2];" ::"r"(dst),
      "l"(m), "r"(bar), "r"(x), "r"(y)
      : "memory");
}
__device__ __forceinline__ void tma_load_2d_mc(uint32_t dst, const CUtensorMap* m, int x, int y, uint32_t bar, uint16_t mask) {
  asm volatile(
      "cp.async.bulk.tensor.2d.shared::cluster.global.mbarrier::complete_tx::bytes.multicast::cluster [%0], [%1, {%3, %4}], "
      "[%2], %5;" ::"r"(dst),
      "l"(m), "r"(bar), "r"(x), "r"(y), "h"(mask)
      : "memory");
}
__device__ __forceinline__ void tma_store_2d(const CUtensorMap* m, uint32_t src, int x, int y) {
  asm volatile("cp.async.bulk.tensor.2d.global.shared::cta.bulk_group [%0, {%2, %3}], [%1];" ::"l"(m), "r"(src), "r"(x),
               "r"(y)
               : "memory");
}
__device__ __forceinline__ void bulk_load(uint32_t dst, const void* src, uint32_t bytes, uint32_t bar) {
  asm volatile("cp.async.bulk.shared::cluster.global.mbarrier::complete_tx::bytes [%0], [%1], %2, [%3];" ::"r"(dst),
               "l"(src), "r"(bytes), "r"(bar)
               : "memory");
}
__device__ __forceinline__ void pdl_launch_dependents() { asm volatile("griddepcontrol.launch_dependents;" ::: "memory"); }
__device__ __forceinline__ void pdl_wait() { asm volatile("griddepcontrol.wait;" ::: "memory"); }
__device__ __forceinline__ void wg_fence() { asm volatile("wgmma.fence.sync.aligned;" ::: "memory"); }
__device__ __forceinline__ void wg_commit() { asm volatile("wgmma.commit_group.sync.aligned;" ::: "memory"); }
template <int N>
__device__ __forceinline__ void wg_wait() {
  asm volatile("wgmma.wait_group.sync.aligned %0;" ::"n"(N) : "memory");
}
template <int M>
__device__ __forceinline__ void fence_regs(float (&r)[M]) {
#pragma unroll
  for (int i = 0; i < M; i++) asm volatile("" : "+f"(r[i])::"memory");
}
__device__ __forceinline__ uint64_t mkdesc(uint32_t addr, uint32_t lbo, uint32_t sbo, uint32_t layout) {
  return (uint64_t)((addr & 0x3FFFF) >> 4) | ((uint64_t)(lbo >> 4) << 16) | ((uint64_t)(sbo >> 4) << 32) |
         ((uint64_t)layout << 62);
}
__device__ __forceinline__ uint32_t pack_bf16(float lo, float hi) {
  uint32_t r;
  asm("cvt.rn.bf16x2.f32 %0, %1, %2;" : "=r"(r) : "f"(hi), "f"(lo));
  return r;
}
__device__ __forceinline__ float bf_lo(uint32_t v) { return __uint_as_float(v << 16); }
__device__ __forceinline__ float bf_hi(uint32_t v) { return __uint_as_float(v & 0xFFFF0000u); }
__device__ __forceinline__ float round_bf16(float x) { return bf_lo(pack_bf16(x, 0.f)); }
__device__ __forceinline__ float ex2f(float x) {
  float y;
  asm("ex2.approx.ftz.f32 %0, %1;" : "=f"(y) : "f"(x));
  return y;
}

__device__ __forceinline__ void wgmma_rs_n128_z(float (&d)[64], uint32_t a0, uint32_t a1, uint32_t a2, uint32_t a3, uint64_t descB) {
  asm volatile("{\n.reg .pred p;\nsetp.ne.b32 p, %69, 0;\n"
    "wgmma.mma_async.sync.aligned.m64n128k16.f32.bf16.bf16 "
    "{%0, %1, %2, %3, %4, %5, %6, %7, %8, %9, %10, %11, %12, %13, %14, %15, %16, %17, %18, %19, %20, %21, %22, %23, %24, %25, %26, %27, %28, %29, %30, %31, %32, %33, %34, %35, %36, %37, %38, %39, %40, %41, %42, %43, %44, %45, %46, %47, %48, %49, %50, %51, %52, %53, %54, %55, %56, %57, %58, %59, %60, %61, %62, %63}, {%64, %65, %66, %67}, %68, p, 1, 1, 0;\n}\n"
    : "=f"(d[0]), "=f"(d[1]), "=f"(d[2]), "=f"(d[3]), "=f"(d[4]), "=f"(d[5]), "=f"(d[6]), "=f"(d[7]),
      "=f"(d[8]), "=f"(d[9]), "=f"(d[10]), "=f"(d[11]), "=f"(d[12]), "=f"(d[13]), "=f"(d[14]), "=f"(d[15]),
      "=f"(d[16]), "=f"(d[17]), "=f"(d[18]), "=f"(d[19]), "=f"(d[20]), "=f"(d[21]), "=f"(d[22]), "=f"(d[23]),
      "=f"(d[24]), "=f"(d[25]), "=f"(d[26]), "=f"(d[27]), "=f"(d[28]), "=f"(d[29]), "=f"(d[30]), "=f"(d[31]),
      "=f"(d[32]), "=f"(d[33]), "=f"(d[34]), "=f"(d[35]), "=f"(d[36]), "=f"(d[37]), "=f"(d[38]), "=f"(d[39]),
      "=f"(d[40]), "=f"(d[41]), "=f"(d[42]), "=f"(d[43]), "=f"(d[44]), "=f"(d[45]), "=f"(d[46]), "=f"(d[47]),
      "=f"(d[48]), "=f"(d[49]), "=f"(d[50]), "=f"(d[51]), "=f"(d[52]), "=f"(d[53]), "=f"(d[54]), "=f"(d[55]),
      "=f"(d[56]), "=f"(d[57]), "=f"(d[58]), "=f"(d[59]), "=f"(d[60]), "=f"(d[61]), "=f"(d[62]), "=f"(d[63])
    : "r"(a0), "r"(a1), "r"(a2), "r"(a3), "l"(descB), "n"(0));
}
__device__ __forceinline__ void wgmma_rs_n24_tb(float (&d)[12], uint32_t a0, uint32_t a1, uint32_t a2, uint32_t a3, uint64_t descB, int scaleD) {
  asm volatile("{\n.reg .pred p;\nsetp.ne.b32 p, %17, 0;\n"
    "wgmma.mma_async.sync.aligned.m64n24k16.f32.bf16.bf16 "
    "{%0, %1, %2, %3, %4, %5, %6, %7, %8, %9, %10, %11}, {%12, %13, %14, %15}, %16, p, 1, 1, 1;\n}\n"
    : "+f"(d[0]), "+f"(d[1]), "+f"(d[2]), "+f"(d[3]), "+f"(d[4]), "+f"(d[5]), "+f"(d[6]), "+f"(d[7]),
      "+f"(d[8]), "+f"(d[9]), "+f"(d[10]), "+f"(d[11])
    : "r"(a0), "r"(a1), "r"(a2), "r"(a3), "l"(descB), "r"(scaleD));
}
__device__ __forceinline__ void wgmma_ss_n128_tb(float (&d)[64], uint64_t descA, uint64_t descB, int scaleD) {
  asm volatile("{\n.reg .pred p;\nsetp.ne.b32 p, %66, 0;\n"
    "wgmma.mma_async.sync.aligned.m64n128k16.f32.bf16.bf16 "
    "{%0, %1, %2, %3, %4, %5, %6, %7, %8, %9, %10, %11, %12, %13, %14, %15, %16, %17, %18, %19, %20, %21, %22, %23, %24, %25, %26, %27, %28, %29, %30, %31, %32, %33, %34, %35, %36, %37, %38, %39, %40, %41, %42, %43, %44, %45, %46, %47, %48, %49, %50, %51, %52, %53, %54, %55, %56, %57, %58, %59, %60, %61, %62, %63}, %64, %65, p, 1, 1, 0, 1;\n}\n"
    : "+f"(d[0]), "+f"(d[1]), "+f"(d[2]), "+f"(d[3]), "+f"(d[4]), "+f"(d[5]), "+f"(d[6]), "+f"(d[7]),
      "+f"(d[8]), "+f"(d[9]), "+f"(d[10]), "+f"(d[11]), "+f"(d[12]), "+f"(d[13]), "+f"(d[14]), "+f"(d[15]),
      "+f"(d[16]), "+f"(d[17]), "+f"(d[18]), "+f"(d[19]), "+f"(d[20]), "+f"(d[21]), "+f"(d[22]), "+f"(d[23]),
      "+f"(d[24]), "+f"(d[25]), "+f"(d[26]), "+f"(d[27]), "+f"(d[28]), "+f"(d[29]), "+f"(d[30]), "+f"(d[31]),
      "+f"(d[32]), "+f"(d[33]), "+f"(d[34]), "+f"(d[35]), "+f"(d[36]), "+f"(d[37]), "+f"(d[38]), "+f"(d[39]),
      "+f"(d[40]), "+f"(d[41]), "+f"(d[42]), "+f"(d[43]), "+f"(d[44]), "+f"(d[45]), "+f"(d[46]), "+f"(d[47]),
      "+f"(d[48]), "+f"(d[49]), "+f"(d[50]), "+f"(d[51]), "+f"(d[52]), "+f"(d[53]), "+f"(d[54]), "+f"(d[55]),
      "+f"(d[56]), "+f"(d[57]), "+f"(d[58]), "+f"(d[59]), "+f"(d[60]), "+f"(d[61]), "+f"(d[62]), "+f"(d[63])
    : "l"(descA), "l"(descB), "r"(scaleD));
}
__device__ __forceinline__ void wgmma_ss_n192_tb(float (&d)[96], uint64_t descA, uint64_t descB, int scaleD) {
  asm volatile("{\n.reg .pred p;\nsetp.ne.b32 p, %98, 0;\n"
    "wgmma.mma_async.sync.aligned.m64n192k16.f32.bf16.bf16 "
    "{%0, %1, %2, %3, %4, %5, %6, %7, %8, %9, %10, %11, %12, %13, %14, %15, %16, %17, %18, %19, %20, %21, %22, %23, %24, %25, %26, %27, %28, %29, %30, %31, %32, %33, %34, %35, %36, %37, %38, %39, %40, %41, %42, %43, %44, %45, %46, %47, %48, %49, %50, %51, %52, %53, %54, %55, %56, %57, %58, %59, %60, %61, %62, %63, %64, %65, %66, %67, %68, %69, %70, %71, %72, %73, %74, %75, %76, %77, %78, %79, %80, %81, %82, %83, %84, %85, %86, %87, %88, %89, %90, %91, %92, %93, %94, %95}, %96, %97, p, 1, 1, 0, 1;\n}\n"
    : "+f"(d[0]), "+f"(d[1]), "+f"(d[2]), "+f"(d[3]), "+f"(d[4]), "+f"(d[5]), "+f"(d[6]), "+f"(d[7]),
      "+f"(d[8]), "+f"(d[9]), "+f"(d[10]), "+f"(d[11]), "+f"(d[12]), "+f"(d[13]), "+f"(d[14]), "+f"(d[15]),
      "+f"(d[16]), "+f"(d[17]), "+f"(d[18]), "+f"(d[19]), "+f"(d[20]), "+f"(d[21]), "+f"(d[22]), "+f"(d[23]),
      "+f"(d[24]), "+f"(d[25]), "+f"(d[26]), "+f"(d[27]), "+f"(d[28]), "+f"(d[29]), "+f"(d[30]), "+f"(d[31]),
      "+f"(d[32]), "+f"(d[33]), "+f"(d[34]), "+f"(d[35]), "+f"(d[36]), "+f"(d[37]), "+f"(d[38]), "+f"(d[39]),
      "+f"(d[40]), "+f"(d[41]), "+f"(d[42]), "+f"(d[43]), "+f"(d[44]), "+f"(d[45]), "+f"(d[46]), "+f"(d[47]),
      "+f"(d[48]), "+f"(d[49]), "+f"(d[50]), "+f"(d[51]), "+f"(d[52]), "+f"(d[53]), "+f"(d[54]), "+f"(d[55]),
      "+f"(d[56]), "+f"(d[57]), "+f"(d[58]), "+f"(d[59]), "+f"(d[60]), "+f"(d[61]), "+f"(d[62]), "+f"(d[63]),
      "+f"(d[64]), "+f"(d[65]), "+f"(d[66]), "+f"(d[67]), "+f"(d[68]), "+f"(d[69]), "+f"(d[70]), "+f"(d[71]),
      "+f"(d[72]), "+f"(d[73]), "+f"(d[74]), "+f"(d[75]), "+f"(d[76]), "+f"(d[77]), "+f"(d[78]), "+f"(d[79]),
      "+f"(d[80]), "+f"(d[81]), "+f"(d[82]), "+f"(d[83]), "+f"(d[84]), "+f"(d[85]), "+f"(d[86]), "+f"(d[87]),
      "+f"(d[88]), "+f"(d[89]), "+f"(d[90]), "+f"(d[91]), "+f"(d[92]), "+f"(d[93]), "+f"(d[94]), "+f"(d[95])
    : "l"(descA), "l"(descB), "r"(scaleD));
}

__device__ __forceinline__ void ldsm4t(uint32_t (&b)[4], uint32_t addr) {
  asm volatile("ldmatrix.sync.aligned.m8n8.x4.trans.shared.b16 {%0,%1,%2,%3}, [%4];"
               : "=r"(b[0]), "=r"(b[1]), "=r"(b[2]), "=r"(b[3])
               : "r"(addr));
}
__device__ __forceinline__ void hmma(float (&c)[4], uint32_t a0, uint32_t a1, uint32_t a2, uint32_t a3, uint32_t b0, uint32_t b1) {
  asm("mma.sync.aligned.m16n8k16.row.col.f32.bf16.bf16.f32 {%0,%1,%2,%3}, {%4,%5,%6,%7}, {%8,%9}, {%0,%1,%2,%3};"
      : "+f"(c[0]), "+f"(c[1]), "+f"(c[2]), "+f"(c[3])
      : "r"(a0), "r"(a1), "r"(a2), "r"(a3), "r"(b0), "r"(b1));
}

__device__ __forceinline__ uint32_t movm(uint32_t a) {
  uint32_t d;
  asm volatile("movmatrix.sync.aligned.m8n8.trans.b16 %0, %1;" : "=r"(d) : "r"(a));
  return d;
}

constexpr int K1_STAGES = 4;
constexpr int K1_W_BYTES = 3 * 8192;
constexpr int K1_X_BYTES = 8 * 16384;
constexpr int K1_BAR_OFF = K1_X_BYTES + K1_STAGES * K1_W_BYTES;
constexpr int K1_SMEM = K1_BAR_OFF + 192 + 1024;
constexpr float QSCALE = 0.25f * 1.4426950408889634f;

__device__ __forceinline__ uint32_t phi2(uint32_t t2) {
  uint32_t a2, mask, r2, o2;
  asm("add.rn.bf16x2 %0, %1, %2;" : "=r"(a2) : "r"(t2), "r"(0x3F803F80u));
  const uint32_t e2 = pack_bf16(ex2f(bf_lo(t2) * 1.4426950408889634f), ex2f(bf_hi(t2) * 1.4426950408889634f));
  asm("set.gt.u32.bf16x2 %0, %1, %2;" : "=r"(mask) : "r"(t2), "r"(0u));
  r2 = (a2 & mask) | (e2 & ~mask);
  asm("add.rn.bf16x2 %0, %1, %2;" : "=r"(o2) : "r"(r2), "r"(0x35863586u));
  return o2;
}

#define K1_SLOT_KB(h) ((h) < 4 ? 2 * (h) : 2 * ((h) - 4) + 1)
struct EpiCtx {
  uint4* qf;
  uint32_t* kp;
  uint32_t* vp;
  uint32_t* s_red;
  float* red;
  int lane;
};

template <bool LINEAR, int J, int HH, int PART>
__device__ __forceinline__ void epi_slice(const float (&acc)[96], const EpiCtx& c, uint32_t (&pk)[4], float& vmax) {
  constexpr int h = J * 4 + HH;
  const float* a = &acc[HH * 8];
  const float* k = &acc[32 + HH * 8];
  const float* v = &acc[64 + HH * 8];
  if (!LINEAR) {
    if (PART == 0) {
      c.qf[h * 32 * 128] = make_uint4(pack_bf16(a[0] * QSCALE, a[1] * QSCALE), pack_bf16(a[2] * QSCALE, a[3] * QSCALE),
                                      pack_bf16(a[4] * QSCALE, a[5] * QSCALE), pack_bf16(a[6] * QSCALE, a[7] * QSCALE));
      uint32_t* kh = c.kp + h * (KV_HEAD_BYTES / 4);
      kh[0] = pack_bf16(k[0], k[1]);
      kh[64] = pack_bf16(k[2], k[3]);
      kh[32] = pack_bf16(k[4], k[5]);
      kh[96] = pack_bf16(k[6], k[7]);
      float q0 = a[0] * a[0] + a[1] * a[1] + a[4] * a[4] + a[5] * a[5];
      float q1 = a[2] * a[2] + a[3] * a[3] + a[6] * a[6] + a[7] * a[7];
      float k0 = k[0] * k[0] + k[1] * k[1] + k[4] * k[4] + k[5] * k[5];
      float k1 = k[2] * k[2] + k[3] * k[3] + k[6] * k[6] + k[7] * k[7];
#pragma unroll
      for (int o = 1; o <= 2; o <<= 1) {
        q0 += __shfl_xor_sync(0xffffffffu, q0, o);
        q1 += __shfl_xor_sync(0xffffffffu, q1, o);
        k0 += __shfl_xor_sync(0xffffffffu, k0, o);
        k1 += __shfl_xor_sync(0xffffffffu, k1, o);
      }
      const uint32_t qm = __reduce_max_sync(0xffffffffu, max(__float_as_uint(q0) & 0x7FFFFFFFu, __float_as_uint(q1) & 0x7FFFFFFFu));
      const uint32_t km = __reduce_max_sync(0xffffffffu, max(__float_as_uint(k0) & 0x7FFFFFFFu, __float_as_uint(k1) & 0x7FFFFFFFu));
      if (c.lane == 0) {
        atomicMax(&c.s_red[h * 2 + 0], qm);
        atomicMax(&c.s_red[h * 2 + 1], km);
      }
    } else {
      uint32_t* vh = c.vp + h * (KV_HEAD_BYTES / 4);
      vh[0] = pack_bf16(v[0], v[1]);
      vh[96] = pack_bf16(v[2], v[3]);
      vh[32] = pack_bf16(v[4], v[5]);
      vh[128] = pack_bf16(v[6], v[7]);
      vh[64] = 0x3F803F80u;
      vh[160] = 0x3F803F80u;
#pragma unroll
      for (int i = 0; i < 8; i++) asm("max.NaN.f32 %0, %0, %1;" : "+f"(vmax) : "f"(fabsf(v[i])));
    }
  } else {
    if (PART == 0) {
      c.qf[h * 32 * 128] = make_uint4(phi2(pack_bf16(a[0], a[1])), phi2(pack_bf16(a[2], a[3])), phi2(pack_bf16(a[4], a[5])),
                                      phi2(pack_bf16(a[6], a[7])));
      pk[0] = movm(phi2(pack_bf16(k[0], k[1])));
      pk[2] = movm(phi2(pack_bf16(k[2], k[3])));
      pk[1] = movm(phi2(pack_bf16(k[4], k[5])));
      pk[3] = movm(phi2(pack_bf16(k[6], k[7])));
    } else {
      const uint32_t b0 = movm(pack_bf16(v[0], v[1]));
      const uint32_t b1 = movm(pack_bf16(v[2], v[3]));
      const uint32_t b2 = movm(pack_bf16(v[4], v[5]));
      const uint32_t b3 = movm(pack_bf16(v[6], v[7]));
      float c0[4] = {0, 0, 0, 0}, c1[4] = {0, 0, 0, 0}, c2[4] = {0, 0, 0, 0};
      hmma(c0, pk[0], pk[1], pk[2], pk[3], b0, b1);
      hmma(c1, pk[0], pk[1], pk[2], pk[3], b2, b3);
      hmma(c2, pk[0], pk[1], pk[2], pk[3], 0x3F803F80u, 0x3F803F80u);
      float* slot = c.red + K1_SLOT_KB(h) * 4096;
#pragma unroll
      for (int i = 0; i < 4; i++) {
        slot[i * 32] = c0[i];
        slot[(4 + i) * 32] = c1[i];
        slot[(8 + i) * 32] = c2[i];
      }
    }
  }
}

template <bool LINEAR>
__device__ __forceinline__ void qkv_consumer(uint32_t sbase, uint8_t* smem_gen, uint32_t* s_red, int cp, int rt) {
  const uint32_t bar_full = sbase + K1_BAR_OFF;
  const uint32_t bar_empty = bar_full + 8 * K1_STAGES;
  const int warp = threadIdx.x >> 5;
  const int wg = warp >> 2;
  const int lane = threadIdx.x & 31;
  float acc0[96], acc1[96];
#pragma unroll 1
  for (int kb = 0; kb < 8; kb++) {
    const int s = kb % K1_STAGES;
    mbar_wait(bar_full + 8 * s, (kb / K1_STAGES) & 1);
    if (threadIdx.x == 0) PROF_T(0, 2 + (kb >> 1));
    const uint64_t dA = mkdesc(sbase + kb * 16384 + wg * 8192, 16, 1024, 1);
    const uint64_t dB = mkdesc(sbase + K1_X_BYTES + s * K1_W_BYTES, 8192, 1024, 1);
    wg_fence();
#pragma unroll
    for (int k = 0; k < 4; k++) wgmma_ss_n192_tb(acc0, dA + k * 2, dB + k * 128, (kb | k) != 0);
    wg_commit();
    if (kb > 0) {
      wg_wait<1>();
      if ((threadIdx.x & 127) == 0) {
        const int sp = (kb - 1) % K1_STAGES;
        mbar_arrive_cluster(bar_empty + 8 * sp, 0);
        mbar_arrive_cluster(bar_empty + 8 * sp, 1);
      }
    }
  }
  wg_wait<0>();
  fence_regs(acc0);
  if ((threadIdx.x & 127) == 0) {
    mbar_arrive_cluster(bar_empty + 8 * (7 % K1_STAGES), 0);
    mbar_arrive_cluster(bar_empty + 8 * (7 % K1_STAGES), 1);
  }
  if (threadIdx.x == 0) PROF_T(0, 6);

  EpiCtx c;
  {
    const int row0 = rt * 128 + wg * 64 + (warp & 3) * 16;
    c.qf = g_qfrag + ((size_t)((LINEAR ? NH : 0) + cp * 8) * 32 + (rt * 2 + wg)) * 128 + (threadIdx.x & 127);
    uint32_t* img = reinterpret_cast<uint32_t*>(reinterpret_cast<uint8_t*>(g_kv) + (size_t)(cp * 8) * KV_HEAD_BYTES);
    c.kp = img + (row0 >> 3) * 64 + lane;
    c.vp = img + KV_K_BYTES / 4 + (row0 >> 3) * 96 + lane;
    c.s_red = s_red;
    c.red = reinterpret_cast<float*>(smem_gen + wg * 8192) + (warp & 3) * 384 + lane;
    c.lane = lane;
  }
  uint32_t pk[4];
  float vmax = 0.f;
#define K1_T1_STEP(KB)                                                                           \
  {                                                                                              \
    constexpr int g = 8 + KB;                                                                    \
    constexpr int s = g % K1_STAGES;                                                             \
    mbar_wait(bar_full + 8 * s, (g / K1_STAGES) & 1);                                            \
    const uint64_t dA = mkdesc(sbase + KB * 16384 + wg * 8192, 16, 1024, 1);                     \
    const uint64_t dB = mkdesc(sbase + K1_X_BYTES + s * K1_W_BYTES, 8192, 1024, 1);              \
    wg_fence();                                                                                  \
    _Pragma("unroll") for (int k = 0; k < 4; k++) wgmma_ss_n192_tb(acc1, dA + k * 2, dB + k * 128, (KB | k) != 0); \
    wg_commit();                                                                                 \
    epi_slice<LINEAR, 0, KB / 2, KB & 1>(acc0, c, pk, vmax);                                     \
    wg_wait<0>();                                                                                \
    if (KB + K1_STAGES < 8 && (threadIdx.x & 127) == 0) {                                        \
      mbar_arrive_cluster(bar_empty + 8 * s, 0);                                                 \
      mbar_arrive_cluster(bar_empty + 8 * s, 1);                                                 \
    }                                                                                            \
  }
  K1_T1_STEP(0) K1_T1_STEP(1) K1_T1_STEP(2) K1_T1_STEP(3) K1_T1_STEP(4) K1_T1_STEP(5) K1_T1_STEP(6) K1_T1_STEP(7)
#undef K1_T1_STEP
  fence_regs(acc1);
  if (threadIdx.x == 0) PROF_T(0, 10);
  epi_slice<LINEAR, 1, 0, 0>(acc1, c, pk, vmax);
  epi_slice<LINEAR, 1, 0, 1>(acc1, c, pk, vmax);
  epi_slice<LINEAR, 1, 1, 0>(acc1, c, pk, vmax);
  epi_slice<LINEAR, 1, 1, 1>(acc1, c, pk, vmax);
  epi_slice<LINEAR, 1, 2, 0>(acc1, c, pk, vmax);
  epi_slice<LINEAR, 1, 2, 1>(acc1, c, pk, vmax);
  epi_slice<LINEAR, 1, 3, 0>(acc1, c, pk, vmax);
  epi_slice<LINEAR, 1, 3, 1>(acc1, c, pk, vmax);
  if (!LINEAR) {
    const uint32_t vm = __reduce_max_sync(0xffffffffu, __float_as_uint(vmax) & 0x7FFFFFFFu);
    if (lane == 0) atomicMax(&s_red[16], vm);
    asm volatile("bar.sync 1, 256;" ::: "memory");
    if (threadIdx.x < 8) {
      *reinterpret_cast<float4*>(&g_nrm[((cp * 8 + threadIdx.x) * 16 + rt) * 4]) =
          make_float4(__uint_as_float(s_red[threadIdx.x * 2]), __uint_as_float(s_red[threadIdx.x * 2 + 1]), __uint_as_float(s_red[16]), 0.f);
    }
  } else {
    asm volatile("bar.sync 1, 256;" ::: "memory");
    float* dst = g_kvpart + ((size_t)rt * NH + cp * 8) * 384;
#pragma unroll
    for (int i = 0; i < 12; i++) {
      const int o = threadIdx.x + i * 256;
      const int h = o / 384, e = o - h * 384;
      const float* src = reinterpret_cast<const float*>(smem_gen) + K1_SLOT_KB(h) * 4096 + e;
      float sum = 0.f;
#pragma unroll
      for (int w = 0; w < 8; w++) sum += src[(w >> 2) * 2048 + (w & 3) * 384];
      dst[o] = sum;
    }
  }
}

__global__ void __launch_bounds__(384, 1)
qkv_gemm_kernel(const __grid_constant__ CUtensorMap mxA, const __grid_constant__ CUtensorMap mxB,
                const __grid_constant__ CUtensorMap mwA, const __grid_constant__ CUtensorMap mwB) {
  extern __shared__ uint8_t smem_raw[];
  const uint32_t sbase = (smem_u32(smem_raw) + 1023) & ~1023u;
  uint8_t* smem_gen = smem_raw + (sbase - smem_u32(smem_raw));
  const uint32_t bar_full = sbase + K1_BAR_OFF;
  const uint32_t bar_empty = bar_full + 8 * K1_STAGES;
  uint32_t* s_red = reinterpret_cast<uint32_t*>(smem_gen + K1_BAR_OFF + 64);

  const int rank = blockIdx.x & 1;
  const int pair = blockIdx.x >> 1;
  const int branch = pair >> 5;
  const int rp = (pair & 31) >> 2;
  const int cp = pair & 3;
  const int rt = rp * 2 + rank;
  const int warp = threadIdx.x >> 5;
  if (threadIdx.x == 0) { PROF_G(0, 30); PROF_T(0, 0); }
  const CUtensorMap* mx = branch ? &mxA : &mxB;
  const CUtensorMap* mw = branch ? &mwA : &mwB;

  if (threadIdx.x == 256) {
    asm volatile("prefetch.tensormap [%0];" ::"l"(mx) : "memory");
    asm volatile("prefetch.tensormap [%0];" ::"l"(mw) : "memory");
    for (int i = 0; i < K1_STAGES; i++) {
      mbar_init(bar_full + 8 * i, 1);
      mbar_init(bar_empty + 8 * i, 4);
    }
    fence_barrier_init();
    fence_proxy_async();
    for (int kb = 0; kb < K1_STAGES; kb++) mbar_expect_tx(bar_full + 8 * kb, 16384 + K1_W_BYTES);
    tma_load_2d(sbase, mx, 0, rt * 128, bar_full);
  }
  pdl_launch_dependents();
  if (threadIdx.x < 32) s_red[threadIdx.x] = 0;
  __syncthreads();
  cluster_sync_relaxed();
  if (threadIdx.x == 0) PROF_T(0, 1);

  if (warp >= 8) {
    asm volatile("setmaxnreg.dec.sync.aligned.u32 40;");
    if (threadIdx.x == 256) {
      for (int g = 0; g < 16; g++) {
        const int s = g % K1_STAGES;
        const int kb = g & 7;
        if (g >= K1_STAGES) {
          mbar_wait(bar_empty + 8 * s, ((g / K1_STAGES) - 1) & 1);
          mbar_expect_tx(bar_full + 8 * s, (g < 8 ? 16384 : 0) + K1_W_BYTES);
        }
        if (g > 0 && g < 8) tma_load_2d(sbase + kb * 16384, mx, kb * 64, rt * 128, bar_full + 8 * s);
        const int h0 = cp * 8 + (g >> 3) * 4;
        const uint32_t st = sbase + K1_X_BYTES + s * K1_W_BYTES + rank * 4096;
#pragma unroll
        for (int p = 0; p < 3; p++)
          tma_load_2d_mc(st + p * 8192, mw, p * 512 + h0 * 16, kb * 64 + rank * 32, bar_full + 8 * s, (uint16_t)3);
      }
    }
    __syncwarp();
    cluster_sync_relaxed();
  } else {
    asm volatile("setmaxnreg.inc.sync.aligned.u32 232;");
    if (branch == 0) qkv_consumer<false>(sbase, smem_gen, s_red, cp, rt);
    else qkv_consumer<true>(sbase, smem_gen, s_red, cp, rt);
    if (threadIdx.x == 0) PROF_T(0, 11);
    __syncwarp();
    cluster_sync_relaxed();
    if (threadIdx.x == 0) { PROF_T(0, 12); PROF_G(0, 31); }
  }
}

constexpr int K2_SMEM = KV_HEAD_BYTES + 1024 + 256;

#define ATT_NPOLY 18
#define ATT_CH 4
#define ATT_D 2
#define ATT_GM 1
struct ExpC {
  uint32_t k3c00, kmask, seven, c3;
};
__device__ __forceinline__ uint32_t hfma2(uint32_t a, uint32_t b, uint32_t c) {
  uint32_t r;
  asm("fma.rn.f16x2 %0, %1, %2, %3;" : "=r"(r) : "r"(a), "r"(b), "r"(c));
  return r;
}
__device__ __forceinline__ uint32_t exp2_poly_pair(float t0, float t1, const ExpC& c) {
  uint32_t u;
  asm("prmt.b32 %0, %1, %2, 0x5410;" : "=r"(u) : "r"(__float_as_uint(t0)), "r"(__float_as_uint(t1)));
  uint32_t m;
  asm("lop3.b32 %0, %1, 0x03FF03FF, %2, 0xEA;" : "=r"(m) : "r"(u), "r"(c.k3c00));
  uint32_t p = hfma2(m, c.c3, 0x9fe09fe0u);
  p = hfma2(p, m, 0x37a137a1u);
  p = hfma2(p, m, 0x4ab94abau);
  uint32_t mu;
  asm("lop3.b32 %0, %1, 0xFC00FC00, %2, 0xEA;" : "=r"(mu) : "r"(u), "r"(c.kmask));
  uint32_t r;
  asm("{.reg .b32 t; shf.r.wrap.b32 t, %1, %2, 3; add.u32 %0, t, %3;}" : "=r"(r) : "r"(mu), "r"(c.seven), "r"(p));
  return r;
}
__device__ __forceinline__ float gadd(float x, float M, uint32_t g) {
  float r = x;
  asm("{.reg .pred p; setp.ne.b32 p, %2, -1; @p add.f32 %0, %0, %1;}" : "+f"(r) : "f"(M), "r"(g));
  return r;
}
__device__ __forceinline__ float gex2(float x, uint32_t g) {
  float r = x;
  asm("{.reg .pred p; setp.ne.b32 p, %1, -1; @p ex2.approx.ftz.f32 %0, %0;}" : "+f"(r) : "r"(g));
  return r;
}
template <int NPOLY, int NPAIR, int CH, int D>
__device__ __forceinline__ void exp_tile(const float (&s)[2 * NPAIR], uint32_t (&p)[NPAIR], const ExpC& c) {
#pragma unroll
  for (int i = 0; i < NPAIR; i++) {
    const bool isPoly = ((i + 1) * NPOLY / 32) != (i * NPOLY / 32);
    const int ch = i / CH;
    const bool gated = ch >= D;
    int gi = (ch - D) * CH + CH - 1;
    if (gated) {
      while (gi > (ch - D) * CH && !(((gi + 1) * NPOLY / 32) != (gi * NPOLY / 32))) gi--;
    }
    const uint32_t g = gated ? p[gi] : 0;
    if (!isPoly) {
      if (gated && ATT_GM) p[i] = pack_bf16(gex2(s[2 * i], g), gex2(s[2 * i + 1], g));
      else p[i] = pack_bf16(ex2f(s[2 * i]), ex2f(s[2 * i + 1]));
    } else {
      if (gated) p[i] = exp2_poly_pair(gadd(s[2 * i], 12329.f, g), gadd(s[2 * i + 1], 12329.f, g), c);
      else p[i] = exp2_poly_pair(s[2 * i] + 12329.f, s[2 * i + 1] + 12329.f, c);
    }
  }
}

__device__ __forceinline__ void store_o(__nv_bfloat16* o, int row0, int head, int lane, const uint32_t (&r)[4]) {
  const int g = lane >> 2, t = lane & 3;
  uint32_t* p0 = reinterpret_cast<uint32_t*>(o + (size_t)(row0 + g) * DM + head * 16) + t;
  uint32_t* p1 = reinterpret_cast<uint32_t*>(o + (size_t)(row0 + g + 8) * DM + head * 16) + t;
  p0[0] = r[0];
  p1[0] = r[1];
  p0[4] = r[2];
  p1[4] = r[3];
}

template <bool SAFE>
__device__ __forceinline__ void attn_step(float (&s)[64], float (&o)[12], float& m0, float& m1, const uint4& qf, uint64_t dKn,
                                          uint64_t dV, const ExpC& ec) {
  uint32_t p[32];
  wg_wait<0>();
  fence_regs(s);
  if (!SAFE) {
    exp_tile<ATT_NPOLY, 32, ATT_CH, ATT_D>(s, p, ec);
  } else {
    float x0 = s[0], x1 = s[2];
#pragma unroll
    for (int i = 0; i < 16; i++) {
      x0 = fmaxf(x0, fmaxf(s[4 * i], s[4 * i + 1]));
      x1 = fmaxf(x1, fmaxf(s[4 * i + 2], s[4 * i + 3]));
    }
    x0 = fmaxf(x0, __shfl_xor_sync(0xffffffffu, x0, 1));
    x1 = fmaxf(x1, __shfl_xor_sync(0xffffffffu, x1, 1));
    x0 = fmaxf(x0, __shfl_xor_sync(0xffffffffu, x0, 2));
    x1 = fmaxf(x1, __shfl_xor_sync(0xffffffffu, x1, 2));
    const float n0 = fmaxf(m0, x0), n1 = fmaxf(m1, x1);
    const float c0 = ex2f(m0 - n0), c1 = ex2f(m1 - n1);
    m0 = n0;
    m1 = n1;
#pragma unroll
    for (int i = 0; i < 3; i++) {
      o[4 * i] *= c0;
      o[4 * i + 1] *= c0;
      o[4 * i + 2] *= c1;
      o[4 * i + 3] *= c1;
    }
#pragma unroll
    for (int i = 0; i < 16; i++) {
      p[2 * i] = pack_bf16(ex2f(s[4 * i] - n0), ex2f(s[4 * i + 1] - n0));
      p[2 * i + 1] = pack_bf16(ex2f(s[4 * i + 2] - n1), ex2f(s[4 * i + 3] - n1));
    }
  }
  wg_fence();
#pragma unroll
  for (int k = 0; k < 8; k++) wgmma_rs_n24_tb(o, p[4 * k], p[4 * k + 1], p[4 * k + 2], p[4 * k + 3], dV + k * 48, 1);
  wg_commit();
  wg_wait<0>();
  if (SAFE) fence_regs(o);
  wg_fence();
  wgmma_rs_n128_z(s, qf.x, qf.y, qf.z, qf.w, dKn);
  wg_commit();
}

template <bool SAFE>
__device__ __forceinline__ void attn_tile(uint64_t dK, uint64_t dV, uint32_t bar, const uint4 qf, const ExpC& ec, uint32_t (&outp)[4]) {
  float s[64];
  float o[12];
#pragma unroll
  for (int i = 0; i < 12; i++) asm volatile("mov.f32 %0, 0f00000000;" : "=f"(o[i]));
  float m0 = -INFINITY, m1 = -INFINITY;
  mbar_wait(bar, 0);
  wg_fence();
  wgmma_rs_n128_z(s, qf.x, qf.y, qf.z, qf.w, dK);
  wg_commit();
#pragma unroll 1
  for (int c = 0; c < 4; c++) {
    if (c > 0) mbar_wait(bar + 8 * c, 0);
#pragma unroll 1
    for (int j = 0; j < 4; j++) {
      dK += 256;
      attn_step<SAFE>(s, o, m0, m1, qf, dK, dV, ec);
      dV += 384;
    }
  }
  wg_wait<0>();
  fence_regs(o);
  fence_regs(s);
  const float r0 = 1.0f / o[8], r1 = 1.0f / o[10];
  outp[0] = pack_bf16(o[0] * r0, o[1] * r0);
  outp[1] = pack_bf16(o[2] * r1, o[3] * r1);
  outp[2] = pack_bf16(o[4] * r0, o[5] * r0);
  outp[3] = pack_bf16(o[6] * r1, o[7] * r1);
}

__device__ __forceinline__ void linear_attn_cta(uint8_t* smem_raw, uint32_t sbase, const CUtensorMap* mo16, int cta) {
  const int warp = threadIdx.x >> 5, lane = threadIdx.x & 31;
  float* red = reinterpret_cast<float*>(smem_raw + (sbase - smem_u32(smem_raw)) + 131072);
  {
    const float* src = g_kvpart + (size_t)cta * 8 * 384;
    float sum[6];
#pragma unroll
    for (int i = 0; i < 6; i++) sum[i] = 0.f;
#pragma unroll
    for (int r = 0; r < 16; r++) {
#pragma unroll
      for (int i = 0; i < 6; i++) sum[i] += src[(size_t)r * NH * 384 + threadIdx.x + i * 512];
    }
#pragma unroll
    for (int i = 0; i < 6; i++) red[threadIdx.x + i * 512] = round_bf16(sum[i]);
  }
  __syncthreads();
  uint32_t bf[8][6];
  {
    const int g = lane >> 2, t = lane & 3;
#pragma unroll
    for (int h = 0; h < 8; h++) {
#pragma unroll
      for (int f = 0; f < 6; f++) {
        const int blk = f >> 1, half = f & 1;
        const int e = (blk == 2) ? 0 : g;
        const int d = 2 * t + 8 * half;
        const int base = h * 384 + (blk * 4 + half * 2 + (e & 1)) * 32 + (e >> 1);
        bf[h][f] = pack_bf16(red[base + (d & 7) * 4], red[base + ((d + 1) & 7) * 4]);
      }
    }
  }
  const uint32_t stg = sbase + warp * 8192;
#pragma unroll 1
  for (int rb = 0; rb < 8; rb++) {
    const int blk16 = rb * 16 + warp;
    const uint4* qp = g_qfrag + ((size_t)(NH + cta * 8) * 32 + (blk16 >> 2)) * 128 + (blk16 & 3) * 32 + lane;
    uint4 q[8];
#pragma unroll
    for (int h = 0; h < 8; h++) q[h] = qp[h * 32 * 128];
    const uint32_t buf = stg + (rb & 1) * 4096;
    if (rb >= 2) {
      if (lane == 0) asm volatile("cp.async.bulk.wait_group.read 1;" ::: "memory");
      __syncwarp();
    }
#pragma unroll
    for (int h = 0; h < 8; h++) {
      float n0[4] = {0, 0, 0, 0}, n1[4] = {0, 0, 0, 0}, dn[4] = {0, 0, 0, 0};
      hmma(n0, q[h].x, q[h].y, q[h].z, q[h].w, bf[h][0], bf[h][1]);
      hmma(n1, q[h].x, q[h].y, q[h].z, q[h].w, bf[h][2], bf[h][3]);
      hmma(dn, q[h].x, q[h].y, q[h].z, q[h].w, bf[h][4], bf[h][5]);
      const float d0 = round_bf16(round_bf16(dn[0]) + 1e-6f), d1 = round_bf16(round_bf16(dn[2]) + 1e-6f);
      const uint32_t r0 = pack_bf16(__fdividef(round_bf16(n0[0]), d0), __fdividef(round_bf16(n0[1]), d0));
      const uint32_t r1 = pack_bf16(__fdividef(round_bf16(n0[2]), d1), __fdividef(round_bf16(n0[3]), d1));
      const uint32_t r2 = pack_bf16(__fdividef(round_bf16(n1[0]), d0), __fdividef(round_bf16(n1[1]), d0));
      const uint32_t r3 = pack_bf16(__fdividef(round_bf16(n1[2]), d1), __fdividef(round_bf16(n1[3]), d1));
      const int row = lane & 15;
      const int chunk = (h & 3) * 2 + (lane >> 4);
      const uint32_t addr = buf + (h >> 2) * 2048 + row * 128 + ((chunk ^ (row & 7)) << 4);
      asm volatile("stmatrix.sync.aligned.m8n8.x4.shared.b16 [%0], {%1,%2,%3,%4};" ::"r"(addr), "r"(r0), "r"(r1), "r"(r2), "r"(r3)
                   : "memory");
    }
    fence_proxy_async();
    __syncwarp();
    if (lane == 0) {
      tma_store_2d(mo16, buf, cta * 128, blk16 * 16);
      tma_store_2d(mo16, buf + 2048, cta * 128 + 64, blk16 * 16);
      asm volatile("cp.async.bulk.commit_group;" ::: "memory");
    }
  }
  if (lane == 0) asm volatile("cp.async.bulk.wait_group 0;" ::: "memory");
}

__global__ void __launch_bounds__(512, 1) attn_kernel(const __grid_constant__ CUtensorMap mo16) {
  extern __shared__ uint8_t smem_raw[];
  const uint32_t sbase = (smem_u32(smem_raw) + 1023) & ~1023u;
  const uint32_t bar = sbase + KV_HEAD_BYTES;
  if (threadIdx.x == 0) { PROF_G(1, 30); PROF_T(1, 0); }
  if (threadIdx.x == 0) {
    for (int i = 0; i < 4; i++) mbar_init(bar + 8 * i, 1);
    fence_barrier_init();
    fence_proxy_async();
  }
  __syncthreads();
  pdl_launch_dependents();
  pdl_wait();
  if (blockIdx.x >= 128) {
    linear_attn_cta(smem_raw, sbase, &mo16, blockIdx.x - 128);
    if (threadIdx.x == 0) { PROF_T(1, 5); PROF_G(1, 31); }
    return;
  }
  const int head = blockIdx.x >> 2, qb = blockIdx.x & 3;
  if (threadIdx.x == 0) {
    const uint8_t* img = reinterpret_cast<const uint8_t*>(g_kv) + (size_t)head * KV_HEAD_BYTES;
    mbar_expect_tx(bar, 32768 + 24576);
    bulk_load(sbase, img, 32768, bar);
    bulk_load(sbase + KV_K_BYTES, img + KV_K_BYTES, 24576, bar);
    for (int i = 1; i < 4; i++) {
      mbar_expect_tx(bar + 8 * i, (i < 3 ? 16384 : 0) + 24576);
      if (i < 3) bulk_load(sbase + (i + 1) * 16384, img + (i + 1) * 16384, 16384, bar + 8 * i);
      bulk_load(sbase + KV_K_BYTES + i * 24576, img + KV_K_BYTES + i * 24576, 24576, bar + 8 * i);
    }
  }
  const int lane = threadIdx.x & 31;
  bool safe_path;
  {
    float4 n = make_float4(0.f, 0.f, 0.f, 0.f);
    if (lane < 16) n = *reinterpret_cast<const float4*>(&g_nrm[(head * 16 + lane) * 4]);
    uint32_t qm = ((lane >> 2) == qb) ? __float_as_uint(n.x) : 0u;
    qm = __reduce_max_sync(0xffffffffu, qm);
    const uint32_t km = __reduce_max_sync(0xffffffffu, __float_as_uint(n.y));
    const uint32_t vm = __reduce_max_sync(0xffffffffu, __float_as_uint(n.z));
    const float b2 = __uint_as_float(qm) * (QSCALE * QSCALE) * __uint_as_float(km) * 1.02f;
    const float vmax = __uint_as_float(vm);
    const bool ok = (b2 <= 21.5f * 21.5f) && (vmax <= 1.0e24f) && (vmax >= 1.0e-18f || vmax == 0.f);
    safe_path = !ok;
  }
  const int wg = threadIdx.x >> 7, warp = (threadIdx.x >> 5) & 3;
  uint32_t zero;
  asm volatile("mov.u32 %0, %%smid;" : "=r"(zero));
  zero >>= 16;
  const ExpC ec{0x3C003C00u + zero, 0x00070000u + zero, 7u + zero, 0x2cfd2cfdu + zero};
  const uint64_t dK = mkdesc(sbase, 128, 256, 0);
  const uint64_t dV = mkdesc(sbase + KV_K_BYTES, 384, 128, 0);
#pragma unroll 1
  for (int t = 0; t < 2; t++) {
    const int tile64 = qb * 8 + wg * 2 + t;
    const uint4 qf = g_qfrag[(head * 32 + tile64) * 128 + (threadIdx.x & 127)];
    uint32_t r[4];
    if (threadIdx.x == 0) PROF_T(1, 1 + t);
    if (!safe_path) attn_tile<false>(dK, dV, bar, qf, ec, r);
    else attn_tile<true>(dK, dV, bar, qf, ec, r);
    store_o(g_o + (size_t)S_LEN * DM, tile64 * 64 + warp * 16, head, lane, r);
  }
  if (threadIdx.x == 0) { PROF_T(1, 5); PROF_G(1, 31); }
}

constexpr int K3_STAGES = 5;
constexpr int K3_W_BYTES = 8 * 16384;
constexpr int K3_BAR_OFF = K3_W_BYTES + K3_STAGES * 16384;
constexpr int K3_SMEM = K3_BAR_OFF + 256 + 1024;

__global__ void __launch_bounds__(288, 1)
out_gemm_kernel(const __grid_constant__ CUtensorMap mo, const __grid_constant__ CUtensorMap mwA,
                const __grid_constant__ CUtensorMap mwB, const __grid_constant__ CUtensorMap mout) {
  extern __shared__ uint8_t smem_raw[];
  const uint32_t sbase = (smem_u32(smem_raw) + 1023) & ~1023u;
  const uint32_t bar_full = sbase + K3_BAR_OFF;
  const uint32_t bar_empty = bar_full + 8 * K3_STAGES;
  const uint32_t bar_w = bar_empty + 8 * K3_STAGES;
  const int branch = blockIdx.x >> 6;
  const int rt = (blockIdx.x & 63) >> 2;
  const int ct = blockIdx.x & 3;
  const int warp = threadIdx.x >> 5;
  if (threadIdx.x == 0) { PROF_G(2, 30); PROF_T(2, 0); }
  if (threadIdx.x == 256) {
    const CUtensorMap* mw = branch ? &mwB : &mwA;
    asm volatile("prefetch.tensormap [%0];" ::"l"(mw) : "memory");
    asm volatile("prefetch.tensormap [%0];" ::"l"(&mo) : "memory");
    asm volatile("prefetch.tensormap [%0];" ::"l"(&mout) : "memory");
    for (int i = 0; i < K3_STAGES; i++) {
      mbar_init(bar_full + 8 * i, 1);
      mbar_init(bar_empty + 8 * i, 2);
    }
    for (int i = 0; i < 8; i++) mbar_init(bar_w + 8 * i, 1);
    fence_barrier_init();
    fence_proxy_async();
    for (int kb = 0; kb < 8; kb++) {
      mbar_expect_tx(bar_w + 8 * kb, 16384);
      tma_load_2d(sbase + kb * 16384, mw, ct * 128, kb * 64, bar_w + 8 * kb);
      tma_load_2d(sbase + kb * 16384 + 8192, mw, ct * 128 + 64, kb * 64, bar_w + 8 * kb);
    }
  }
  __syncthreads();
  if (warp == 8) {
    if ((threadIdx.x & 31) == 0) {
      pdl_wait();
      PROF_T(2, 1);
      for (int kb = 0; kb < 8; kb++) {
        const int s = kb % K3_STAGES;
        if (kb >= K3_STAGES) mbar_wait(bar_empty + 8 * s, ((kb / K3_STAGES) - 1) & 1);
        mbar_expect_tx(bar_full + 8 * s, 16384);
        tma_load_2d(sbase + K3_W_BYTES + s * 16384, &mo, kb * 64, branch * S_LEN + rt * 128, bar_full + 8 * s);
      }
    }
  } else {
    const int wg = warp >> 2;
    float acc[64];
    for (int kb = 0; kb < 8; kb++) {
      const int s = kb % K3_STAGES;
      mbar_wait(bar_w + 8 * kb, 0);
      mbar_wait(bar_full + 8 * s, (kb / K3_STAGES) & 1);
      if (threadIdx.x == 0) PROF_T(2, 2 + kb);
      const uint64_t dA = mkdesc(sbase + K3_W_BYTES + s * 16384 + wg * 8192, 16, 1024, 1);
      const uint64_t dB = mkdesc(sbase + kb * 16384, 8192, 1024, 1);
      wg_fence();
#pragma unroll
      for (int k = 0; k < 4; k++) wgmma_ss_n128_tb(acc, dA + k * 2, dB + k * 128, (kb | k) != 0);
      wg_commit();
      if (kb > 0) {
        wg_wait<1>();
        if ((threadIdx.x & 127) == 0) mbar_arrive(bar_empty + 8 * ((kb - 1) % K3_STAGES));
      }
    }
    wg_wait<0>();
    fence_regs(acc);
    if (threadIdx.x == 0) PROF_T(2, 10);
    const uint32_t stg = sbase + K3_W_BYTES + wg * 8192;
    asm volatile("bar.sync 1, 256;" ::: "memory");
    const int lane = threadIdx.x & 31;
    const int rloc = (warp & 3) * 16 + (lane & 15);
#pragma unroll
    for (int c16 = 0; c16 < 8; c16++) {
      const float* a = &acc[c16 * 8];
      const uint32_t r0 = pack_bf16(a[0], a[1]), r1 = pack_bf16(a[2], a[3]), r2 = pack_bf16(a[4], a[5]), r3 = pack_bf16(a[6], a[7]);
      const int chunk = (c16 & 3) * 2 + (lane >> 4);
      const uint32_t addr = stg + (c16 >> 2) * 16384 + rloc * 128 + ((chunk ^ (rloc & 7)) << 4);
      asm volatile("stmatrix.sync.aligned.m8n8.x4.shared.b16 [%0], {%1,%2,%3,%4};" ::"r"(addr), "r"(r0), "r"(r1), "r"(r2), "r"(r3)
                   : "memory");
    }
    fence_proxy_async();
    asm volatile("bar.sync %0, 128;" ::"r"(2 + wg) : "memory");
    if ((threadIdx.x & 127) == 0) {
      tma_store_2d(&mout, stg, branch * DM + ct * 128, rt * 128 + wg * 64);
      tma_store_2d(&mout, stg + 16384, branch * DM + ct * 128 + 64, rt * 128 + wg * 64);
      asm volatile("cp.async.bulk.commit_group;" ::: "memory");
      asm volatile("cp.async.bulk.wait_group.read 0;" ::: "memory");
      if (threadIdx.x == 0) { PROF_T(2, 12); PROF_G(2, 31); }
    }
  }
}

typedef CUresult (*EncodeFn)(CUtensorMap*, CUtensorMapDataType, cuuint32_t, void*, const cuuint64_t*, const cuuint64_t*,
                             const cuuint32_t*, const cuuint32_t*, CUtensorMapInterleave, CUtensorMapSwizzle,
                             CUtensorMapL2promotion, CUtensorMapFloatOOBfill);

void make_map(EncodeFn enc, CUtensorMap* m, const void* ptr, uint64_t inner, uint64_t outer, uint32_t box_inner, uint32_t box_outer) {
  cuuint64_t dims[2] = {inner, outer};
  cuuint64_t strides[1] = {inner * 2};
  cuuint32_t box[2] = {box_inner, box_outer};
  cuuint32_t es[2] = {1, 1};
  enc(m, CU_TENSOR_MAP_DATA_TYPE_BFLOAT16, 2, const_cast<void*>(ptr), dims, strides, box, es, CU_TENSOR_MAP_INTERLEAVE_NONE,
      CU_TENSOR_MAP_SWIZZLE_128B, CU_TENSOR_MAP_L2_PROMOTION_L2_256B, CU_TENSOR_MAP_FLOAT_OOB_FILL_NONE);
}

struct HostState {
  bool init;
  const void* key[7];
  CUtensorMap mxA, mxB, mwA, mwB, mo, mo16, mwoA, mwoB, mout;
};
HostState g_hs;

}

extern "C" void kernel_launch(void* const* d_in, const int* in_sizes, int n_in, void* d_out, int out_size) {
  (void)in_sizes; (void)n_in; (void)out_size;
  HostState& hs = g_hs;
  bool same = hs.init && hs.key[6] == d_out;
  for (int i = 0; i < 6 && same; i++) same = hs.key[i] == d_in[i];
  if (!same) {
    void* fn = nullptr;
    cudaDriverEntryPointQueryResult qr;
    cudaGetDriverEntryPoint("cuTensorMapEncodeTiled", &fn, cudaEnableDefault, &qr);
    EncodeFn enc = (EncodeFn)fn;
    void* go = nullptr;
    cudaGetSymbolAddress(&go, g_o);
    make_map(enc, &hs.mxA, d_in[0], 512, 2048, 64, 128);
    make_map(enc, &hs.mwA, d_in[1], 1536, 512, 64, 32);
    make_map(enc, &hs.mwoA, d_in[2], 512, 512, 64, 64);
    make_map(enc, &hs.mxB, d_in[3], 512, 2048, 64, 128);
    make_map(enc, &hs.mwB, d_in[4], 1536, 512, 64, 32);
    make_map(enc, &hs.mwoB, d_in[5], 512, 512, 64, 64);
    make_map(enc, &hs.mo, go, 512, 4096, 64, 128);
    make_map(enc, &hs.mo16, go, 512, 4096, 64, 16);
    make_map(enc, &hs.mout, d_out, 1024, 2048, 64, 64);
    cudaFuncSetAttribute(qkv_gemm_kernel, cudaFuncAttributeMaxDynamicSharedMemorySize, K1_SMEM);
    cudaFuncSetAttribute(attn_kernel, cudaFuncAttributeMaxDynamicSharedMemorySize, K2_SMEM);
    cudaFuncSetAttribute(out_gemm_kernel, cudaFuncAttributeMaxDynamicSharedMemorySize, K3_SMEM);
    for (int i = 0; i < 6; i++) hs.key[i] = d_in[i];
    hs.key[6] = d_out;
    hs.init = true;
  }
  cudaStream_t st = cudaStreamPerThread;
  {
    cudaLaunchConfig_t cfg = {};
    cfg.gridDim = dim3(128);
    cfg.blockDim = dim3(384);
    cfg.dynamicSmemBytes = K1_SMEM;
    cfg.stream = st;
    cudaLaunchAttribute at[1];
    at[0].id = cudaLaunchAttributeClusterDimension;
    at[0].val.clusterDim.x = 2;
    at[0].val.clusterDim.y = 1;
    at[0].val.clusterDim.z = 1;
    cfg.attrs = at;
    cfg.numAttrs = 1;
    cudaLaunchKernelEx(&cfg, qkv_gemm_kernel, hs.mxA, hs.mxB, hs.mwA, hs.mwB);
  }
  {
    cudaLaunchConfig_t cfg = {};
    cfg.gridDim = dim3(132);
    cfg.blockDim = dim3(512);
    cfg.dynamicSmemBytes = K2_SMEM;
    cfg.stream = st;
    cudaLaunchAttribute at[1];
    at[0].id = cudaLaunchAttributeProgrammaticStreamSerialization;
    at[0].val.programmaticStreamSerializationAllowed = 1;
    cfg.attrs = at;
    cfg.numAttrs = 1;
    cudaLaunchKernelEx(&cfg, attn_kernel, hs.mo16);
    cfg.gridDim = dim3(128);
    cfg.blockDim = dim3(288);
    cfg.dynamicSmemBytes = K3_SMEM;
    cudaLaunchKernelEx(&cfg, out_gemm_kernel, hs.mo, hs.mwoA, hs.mwoB, hs.mout);
  }
}
```

```cpp
#include <cuda_runtime.h>
#include <cuda_bf16.h>
#include <cuda.h>
#include <stdint.h>

namespace {

constexpr int S_LEN = 2048;
constexpr int DM = 512;
constexpr int NH = 32;

constexpr int KV_K_BYTES = 65536;
constexpr int KV_HEAD_BYTES = KV_K_BYTES + 98304;
__device__ uint4 g_qfrag[2 * NH * 32 * 128];
__device__ uint4 g_kv[NH * KV_HEAD_BYTES / 16];
__device__ float g_kvpart[16 * NH * 384];
__device__ float g_nrm[NH * 16 * 4];
__device__ __nv_bfloat16 g_o[2 * S_LEN * DM];

#define PROF_T(k, i) do {} while (0)
#define PROF_G(k, i) do {} while (0)
__device__ __forceinline__ uint32_t smem_u32(const void* p) { return (uint32_t)__cvta_generic_to_shared(p); }
__device__ __forceinline__ void mbar_init(uint32_t bar, int cnt) {
  asm volatile("mbarrier.init.shared::cta.b64 [%0], %1;" ::"r"(bar), "r"(cnt) : "memory");
}
__device__ __forceinline__ void mbar_expect_tx(uint32_t bar, uint32_t bytes) {
  asm volatile("mbarrier.arrive.expect_tx.shared::cta.b64 _, [%0], %1;" ::"r"(bar), "r"(bytes) : "memory");
}
__device__ __forceinline__ void mbar_arrive(uint32_t bar) {
  asm volatile("mbarrier.arrive.shared::cta.b64 _, [%0];" ::"r"(bar) : "memory");
}
__device__ __forceinline__ void mbar_arrive_cluster(uint32_t bar, uint32_t cta) {
  asm volatile(
      "{\n.reg .b32 ra;\nmapa.shared::cluster.u32 ra, %0, %1;\n"
      "mbarrier.arrive.shared::cluster.b64 _, [ra];\n}" ::"r"(bar), "r"(cta) : "memory");
}
__device__ __forceinline__ void mbar_wait(uint32_t bar, uint32_t parity) {
  asm volatile(
      "{\n.reg .pred p;\n"
      "WAIT_LOOP:\n"
      "mbarrier.try_wait.parity.shared::cta.b64 p, [%0], %1, 0x989680;\n"
      "@p bra WAIT_DONE;\n"
      "bra WAIT_LOOP;\n"
      "WAIT_DONE:\n}" ::"r"(bar), "r"(parity) : "memory");
}
__device__ __forceinline__ void mbar_wait_cluster(uint32_t bar, uint32_t parity) {
  asm volatile(
      "{\n.reg .pred p;\n"
      "WAIT_LOOP:\n"
      "mbarrier.try_wait.parity.acquire.cluster.shared::cta.b64 p, [%0], %1, 0x989680;\n"
      "@p bra WAIT_DONE;\n"
      "bra WAIT_LOOP;\n"
      "WAIT_DONE:\n}" ::"r"(bar), "r"(parity) : "memory");
}
__device__ __forceinline__ void fence_barrier_init() {
  asm volatile("fence.mbarrier_init.release.cluster;" ::: "memory");
}
__device__ __forceinline__ void fence_proxy_async() { asm volatile("fence.proxy.async.shared::cta;" ::: "memory"); }
__device__ __forceinline__ void cluster_sync_relaxed() {
  asm volatile("barrier.cluster.arrive.relaxed.aligned;\nbarrier.cluster.wait.aligned;" ::: "memory");
}
__device__ __forceinline__ void tma_load_2d(uint32_t dst, const CUtensorMap* m, int x, int y, uint32_t bar) {
  asm volatile(
      "cp.async.bulk.tensor.2d.shared::cluster.global.mbarrier::complete_tx::bytes [%0], [%1, {%3, %4}], [%2];" ::"r"(dst),
      "l"(m), "r"(bar), "r"(x), "r"(y)
      : "memory");
}
__device__ __forceinline__ void tma_load_2d_mc(uint32_t dst, const CUtensorMap* m, int x, int y, uint32_t bar, uint16_t mask) {
  asm volatile(
      "cp.async.bulk.tensor.2d.shared::cluster.global.mbarrier::complete_tx::bytes.multicast::cluster [%0], [%1, {%3, %4}], "
      "[%2], %5;" ::"r"(dst),
      "l"(m), "r"(bar), "r"(x), "r"(y), "h"(mask)
      : "memory");
}
__device__ __forceinline__ void tma_store_2d(const CUtensorMap* m, uint32_t src, int x, int y) {
  asm volatile("cp.async.bulk.tensor.2d.global.shared::cta.bulk_group [%0, {%2, %3}], [%1];" ::"l"(m), "r"(src), "r"(x),
               "r"(y)
               : "memory");
}
__device__ __forceinline__ void bulk_load(uint32_t dst, const void* src, uint32_t bytes, uint32_t bar) {
  asm volatile("cp.async.bulk.shared::cluster.global.mbarrier::complete_tx::bytes [%0], [%1], %2, [%3];" ::"r"(dst),
               "l"(src), "r"(bytes), "r"(bar)
               : "memory");
}
__device__ __forceinline__ void pdl_launch_dependents() { asm volatile("griddepcontrol.launch_dependents;" ::: "memory"); }
__device__ __forceinline__ void pdl_wait() { asm volatile("griddepcontrol.wait;" ::: "memory"); }
__device__ __forceinline__ void wg_fence() { asm volatile("wgmma.fence.sync.aligned;" ::: "memory"); }
__device__ __forceinline__ void wg_commit() { asm volatile("wgmma.commit_group.sync.aligned;" ::: "memory"); }
template <int N>
__device__ __forceinline__ void wg_wait() {
  asm volatile("wgmma.wait_group.sync.aligned %0;" ::"n"(N) : "memory");
}
template <int M>
__device__ __forceinline__ void fence_regs(float (&r)[M]) {
#pragma unroll
  for (int i = 0; i < M; i++) asm volatile("" : "+f"(r[i])::"memory");
}
__device__ __forceinline__ uint64_t mkdesc(uint32_t addr, uint32_t lbo, uint32_t sbo, uint32_t layout) {
  return (uint64_t)((addr & 0x3FFFF) >> 4) | ((uint64_t)(lbo >> 4) << 16) | ((uint64_t)(sbo >> 4) << 32) |
         ((uint64_t)layout << 62);
}
__device__ __forceinline__ uint32_t pack_bf16(float lo, float hi) {
  uint32_t r;
  asm("cvt.rn.bf16x2.f32 %0, %1, %2;" : "=r"(r) : "f"(hi), "f"(lo));
  return r;
}
__device__ __forceinline__ float bf_lo(uint32_t v) { return __uint_as_float(v << 16); }
__device__ __forceinline__ float bf_hi(uint32_t v) { return __uint_as_float(v & 0xFFFF0000u); }
__device__ __forceinline__ float round_bf16(float x) { return bf_lo(pack_bf16(x, 0.f)); }
__device__ __forceinline__ float ex2f(float x) {
  float y;
  asm("ex2.approx.ftz.f32 %0, %1;" : "=f"(y) : "f"(x));
  return y;
}

__device__ __forceinline__ void wgmma_rs_n24_tb(float (&d)[12], uint32_t a0, uint32_t a1, uint32_t a2, uint32_t a3, uint64_t descB, int scaleD) {
  asm volatile("{\n.reg .pred p;\nsetp.ne.b32 p, %17, 0;\n"
    "wgmma.mma_async.sync.aligned.m64n24k16.f32.bf16.bf16 "
    "{%0, %1, %2, %3, %4, %5, %6, %7, %8, %9, %10, %11}, {%12, %13, %14, %15}, %16, p, 1, 1, 1;\n}\n"
    : "+f"(d[0]), "+f"(d[1]), "+f"(d[2]), "+f"(d[3]), "+f"(d[4]), "+f"(d[5]), "+f"(d[6]), "+f"(d[7]),
      "+f"(d[8]), "+f"(d[9]), "+f"(d[10]), "+f"(d[11])
    : "r"(a0), "r"(a1), "r"(a2), "r"(a3), "l"(descB), "r"(scaleD));
}
__device__ __forceinline__ void wgmma_rs_n64_z(float (&d)[32], uint32_t a0, uint32_t a1, uint32_t a2, uint32_t a3, uint64_t descB) {
  asm volatile("{\n.reg .pred p;\nsetp.ne.b32 p, %37, 0;\n"
    "wgmma.mma_async.sync.aligned.m64n64k16.f32.bf16.bf16 "
    "{%0, %1, %2, %3, %4, %5, %6, %7, %8, %9, %10, %11, %12, %13, %14, %15, %16, %17, %18, %19, %20, %21, %22, %23, %24, %25, %26, %27, %28, %29, %30, %31}, {%32, %33, %34, %35}, %36, p, 1, 1, 0;\n}\n"
    : "=f"(d[0]), "=f"(d[1]), "=f"(d[2]), "=f"(d[3]), "=f"(d[4]), "=f"(d[5]), "=f"(d[6]), "=f"(d[7]),
      "=f"(d[8]), "=f"(d[9]), "=f"(d[10]), "=f"(d[11]), "=f"(d[12]), "=f"(d[13]), "=f"(d[14]), "=f"(d[15]),
      "=f"(d[16]), "=f"(d[17]), "=f"(d[18]), "=f"(d[19]), "=f"(d[20]), "=f"(d[21]), "=f"(d[22]), "=f"(d[23]),
      "=f"(d[24]), "=f"(d[25]), "=f"(d[26]), "=f"(d[27]), "=f"(d[28]), "=f"(d[29]), "=f"(d[30]), "=f"(d[31])
    : "r"(a0), "r"(a1), "r"(a2), "r"(a3), "l"(descB), "n"(0));
}
__device__ __forceinline__ void wgmma_ss_n128_tb(float (&d)[64], uint64_t descA, uint64_t descB, int scaleD) {
  asm volatile("{\n.reg .pred p;\nsetp.ne.b32 p, %66, 0;\n"
    "wgmma.mma_async.sync.aligned.m64n128k16.f32.bf16.bf16 "
    "{%0, %1, %2, %3, %4, %5, %6, %7, %8, %9, %10, %11, %12, %13, %14, %15, %16, %17, %18, %19, %20, %21, %22, %23, %24, %25, %26, %27, %28, %29, %30, %31, %32, %33, %34, %35, %36, %37, %38, %39, %40, %41, %42, %43, %44, %45, %46, %47, %48, %49, %50, %51, %52, %53, %54, %55, %56, %57, %58, %59, %60, %61, %62, %63}, %64, %65, p, 1, 1, 0, 1;\n}\n"
    : "+f"(d[0]), "+f"(d[1]), "+f"(d[2]), "+f"(d[3]), "+f"(d[4]), "+f"(d[5]), "+f"(d[6]), "+f"(d[7]),
      "+f"(d[8]), "+f"(d[9]), "+f"(d[10]), "+f"(d[11]), "+f"(d[12]), "+f"(d[13]), "+f"(d[14]), "+f"(d[15]),
      "+f"(d[16]), "+f"(d[17]), "+f"(d[18]), "+f"(d[19]), "+f"(d[20]), "+f"(d[21]), "+f"(d[22]), "+f"(d[23]),
      "+f"(d[24]), "+f"(d[25]), "+f"(d[26]), "+f"(d[27]), "+f"(d[28]), "+f"(d[29]), "+f"(d[30]), "+f"(d[31]),
      "+f"(d[32]), "+f"(d[33]), "+f"(d[34]), "+f"(d[35]), "+f"(d[36]), "+f"(d[37]), "+f"(d[38]), "+f"(d[39]),
      "+f"(d[40]), "+f"(d[41]), "+f"(d[42]), "+f"(d[43]), "+f"(d[44]), "+f"(d[45]), "+f"(d[46]), "+f"(d[47]),
      "+f"(d[48]), "+f"(d[49]), "+f"(d[50]), "+f"(d[51]), "+f"(d[52]), "+f"(d[53]), "+f"(d[54]), "+f"(d[55]),
      "+f"(d[56]), "+f"(d[57]), "+f"(d[58]), "+f"(d[59]), "+f"(d[60]), "+f"(d[61]), "+f"(d[62]), "+f"(d[63])
    : "l"(descA), "l"(descB), "r"(scaleD));
}
__device__ __forceinline__ void wgmma_ss_n192_tb(float (&d)[96], uint64_t descA, uint64_t descB, int scaleD) {
  asm volatile("{\n.reg .pred p;\nsetp.ne.b32 p, %98, 0;\n"
    "wgmma.mma_async.sync.aligned.m64n192k16.f32.bf16.bf16 "
    "{%0, %1, %2, %3, %4, %5, %6, %7, %8, %9, %10, %11, %12, %13, %14, %15, %16, %17, %18, %19, %20, %21, %22, %23, %24, %25, %26, %27, %28, %29, %30, %31, %32, %33, %34, %35, %36, %37, %38, %39, %40, %41, %42, %43, %44, %45, %46, %47, %48, %49, %50, %51, %52, %53, %54, %55, %56, %57, %58, %59, %60, %61, %62, %63, %64, %65, %66, %67, %68, %69, %70, %71, %72, %73, %74, %75, %76, %77, %78, %79, %80, %81, %82, %83, %84, %85, %86, %87, %88, %89, %90, %91, %92, %93, %94, %95}, %96, %97, p, 1, 1, 0, 1;\n}\n"
    : "+f"(d[0]), "+f"(d[1]), "+f"(d[2]), "+f"(d[3]), "+f"(d[4]), "+f"(d[5]), "+f"(d[6]), "+f"(d[7]),
      "+f"(d[8]), "+f"(d[9]), "+f"(d[10]), "+f"(d[11]), "+f"(d[12]), "+f"(d[13]), "+f"(d[14]), "+f"(d[15]),
      "+f"(d[16]), "+f"(d[17]), "+f"(d[18]), "+f"(d[19]), "+f"(d[20]), "+f"(d[21]), "+f"(d[22]), "+f"(d[23]),
      "+f"(d[24]), "+f"(d[25]), "+f"(d[26]), "+f"(d[27]), "+f"(d[28]), "+f"(d[29]), "+f"(d[30]), "+f"(d[31]),
      "+f"(d[32]), "+f"(d[33]), "+f"(d[34]), "+f"(d[35]), "+f"(d[36]), "+f"(d[37]), "+f"(d[38]), "+f"(d[39]),
      "+f"(d[40]), "+f"(d[41]), "+f"(d[42]), "+f"(d[43]), "+f"(d[44]), "+f"(d[45]), "+f"(d[46]), "+f"(d[47]),
      "+f"(d[48]), "+f"(d[49]), "+f"(d[50]), "+f"(d[51]), "+f"(d[52]), "+f"(d[53]), "+f"(d[54]), "+f"(d[55]),
      "+f"(d[56]), "+f"(d[57]), "+f"(d[58]), "+f"(d[59]), "+f"(d[60]), "+f"(d[61]), "+f"(d[62]), "+f"(d[63]),
      "+f"(d[64]), "+f"(d[65]), "+f"(d[66]), "+f"(d[67]), "+f"(d[68]), "+f"(d[69]), "+f"(d[70]), "+f"(d[71]),
      "+f"(d[72]), "+f"(d[73]), "+f"(d[74]), "+f"(d[75]), "+f"(d[76]), "+f"(d[77]), "+f"(d[78]), "+f"(d[79]),
      "+f"(d[80]), "+f"(d[81]), "+f"(d[82]), "+f"(d[83]), "+f"(d[84]), "+f"(d[85]), "+f"(d[86]), "+f"(d[87]),
      "+f"(d[88]), "+f"(d[89]), "+f"(d[90]), "+f"(d[91]), "+f"(d[92]), "+f"(d[93]), "+f"(d[94]), "+f"(d[95])
    : "l"(descA), "l"(descB), "r"(scaleD));
}

__device__ __forceinline__ void ldsm4t(uint32_t (&b)[4], uint32_t addr) {
  asm volatile("ldmatrix.sync.aligned.m8n8.x4.trans.shared.b16 {%0,%1,%2,%3}, [%4];"
               : "=r"(b[0]), "=r"(b[1]), "=r"(b[2]), "=r"(b[3])
               : "r"(addr));
}
__device__ __forceinline__ void hmma(float (&c)[4], uint32_t a0, uint32_t a1, uint32_t a2, uint32_t a3, uint32_t b0, uint32_t b1) {
  asm("mma.sync.aligned.m16n8k16.row.col.f32.bf16.bf16.f32 {%0,%1,%2,%3}, {%4,%5,%6,%7}, {%8,%9}, {%0,%1,%2,%3};"
      : "+f"(c[0]), "+f"(c[1]), "+f"(c[2]), "+f"(c[3])
      : "r"(a0), "r"(a1), "r"(a2), "r"(a3), "r"(b0), "r"(b1));
}

__device__ __forceinline__ uint32_t movm(uint32_t a) {
  uint32_t d;
  asm volatile("movmatrix.sync.aligned.m8n8.trans.b16 %0, %1;" : "=r"(d) : "r"(a));
  return d;
}

constexpr int K1_STAGES = 4;
constexpr int K1_W_BYTES = 3 * 8192;
constexpr int K1_X_BYTES = 8 * 16384;
constexpr int K1_BAR_OFF = K1_X_BYTES + K1_STAGES * K1_W_BYTES;
constexpr int K1_SMEM = K1_BAR_OFF + 192 + 1024;
constexpr float QSCALE = 0.25f * 1.4426950408889634f;

__device__ __forceinline__ uint32_t phi2(uint32_t t2) {
  uint32_t a2, mask, r2, o2;
  asm("add.rn.bf16x2 %0, %1, %2;" : "=r"(a2) : "r"(t2), "r"(0x3F803F80u));
  const uint32_t e2 = pack_bf16(ex2f(bf_lo(t2) * 1.4426950408889634f), ex2f(bf_hi(t2) * 1.4426950408889634f));
  asm("set.gt.u32.bf16x2 %0, %1, %2;" : "=r"(mask) : "r"(t2), "r"(0u));
  r2 = (a2 & mask) | (e2 & ~mask);
  asm("add.rn.bf16x2 %0, %1, %2;" : "=r"(o2) : "r"(r2), "r"(0x35863586u));
  return o2;
}

#define K1_SLOT_KB(h) ((h) < 4 ? 2 * (h) : 2 * ((h) - 4) + 1)
struct EpiCtx {
  uint4* qf;
  uint32_t* kp;
  uint32_t* vp;
  uint32_t* s_red;
  float* red;
  int lane;
};

template <bool LINEAR, int J, int HH, int PART>
__device__ __forceinline__ void epi_slice(const float (&acc)[96], const EpiCtx& c, uint32_t (&pk)[4], float& vmax) {
  constexpr int h = J * 4 + HH;
  const float* a = &acc[HH * 8];
  const float* k = &acc[32 + HH * 8];
  const float* v = &acc[64 + HH * 8];
  if (!LINEAR) {
    if (PART == 0) {
      c.qf[h * 32 * 128] = make_uint4(pack_bf16(a[0] * QSCALE, a[1] * QSCALE), pack_bf16(a[2] * QSCALE, a[3] * QSCALE),
                                      pack_bf16(a[4] * QSCALE, a[5] * QSCALE), pack_bf16(a[6] * QSCALE, a[7] * QSCALE));
      uint32_t* kh = c.kp + h * (KV_HEAD_BYTES / 4);
      kh[0] = pack_bf16(k[0], k[1]);
      kh[64] = pack_bf16(k[2], k[3]);
      kh[32] = pack_bf16(k[4], k[5]);
      kh[96] = pack_bf16(k[6], k[7]);
      float q0 = a[0] * a[0] + a[1] * a[1] + a[4] * a[4] + a[5] * a[5];
      float q1 = a[2] * a[2] + a[3] * a[3] + a[6] * a[6] + a[7] * a[7];
      float k0 = k[0] * k[0] + k[1] * k[1] + k[4] * k[4] + k[5] * k[5];
      float k1 = k[2] * k[2] + k[3] * k[3] + k[6] * k[6] + k[7] * k[7];
#pragma unroll
      for (int o = 1; o <= 2; o <<= 1) {
        q0 += __shfl_xor_sync(0xffffffffu, q0, o);
        q1 += __shfl_xor_sync(0xffffffffu, q1, o);
        k0 += __shfl_xor_sync(0xffffffffu, k0, o);
        k1 += __shfl_xor_sync(0xffffffffu, k1, o);
      }
      const uint32_t qm = __reduce_max_sync(0xffffffffu, max(__float_as_uint(q0) & 0x7FFFFFFFu, __float_as_uint(q1) & 0x7FFFFFFFu));
      const uint32_t km = __reduce_max_sync(0xffffffffu, max(__float_as_uint(k0) & 0x7FFFFFFFu, __float_as_uint(k1) & 0x7FFFFFFFu));
      if (c.lane == 0) {
        atomicMax(&c.s_red[h * 2 + 0], qm);
        atomicMax(&c.s_red[h * 2 + 1], km);
      }
    } else {
      uint32_t* vh = c.vp + h * (KV_HEAD_BYTES / 4);
      vh[0] = pack_bf16(v[0], v[1]);
      vh[96] = pack_bf16(v[2], v[3]);
      vh[32] = pack_bf16(v[4], v[5]);
      vh[128] = pack_bf16(v[6], v[7]);
      vh[64] = 0x3F803F80u;
      vh[160] = 0x3F803F80u;
#pragma unroll
      for (int i = 0; i < 8; i++) asm("max.NaN.f32 %0, %0, %1;" : "+f"(vmax) : "f"(fabsf(v[i])));
    }
  } else {
    if (PART == 0) {
      c.qf[h * 32 * 128] = make_uint4(phi2(pack_bf16(a[0], a[1])), phi2(pack_bf16(a[2], a[3])), phi2(pack_bf16(a[4], a[5])),
                                      phi2(pack_bf16(a[6], a[7])));
      pk[0] = movm(phi2(pack_bf16(k[0], k[1])));
      pk[2] = movm(phi2(pack_bf16(k[2], k[3])));
      pk[1] = movm(phi2(pack_bf16(k[4], k[5])));
      pk[3] = movm(phi2(pack_bf16(k[6], k[7])));
    } else {
      const uint32_t b0 = movm(pack_bf16(v[0], v[1]));
      const uint32_t b1 = movm(pack_bf16(v[2], v[3]));
      const uint32_t b2 = movm(pack_bf16(v[4], v[5]));
      const uint32_t b3 = movm(pack_bf16(v[6], v[7]));
      float c0[4] = {0, 0, 0, 0}, c1[4] = {0, 0, 0, 0}, c2[4] = {0, 0, 0, 0};
      hmma(c0, pk[0], pk[1], pk[2], pk[3], b0, b1);
      hmma(c1, pk[0], pk[1], pk[2], pk[3], b2, b3);
      hmma(c2, pk[0], pk[1], pk[2], pk[3], 0x3F803F80u, 0x3F803F80u);
      float* slot = c.red + K1_SLOT_KB(h) * 4096;
#pragma unroll
      for (int i = 0; i < 4; i++) {
        slot[i * 32] = c0[i];
        slot[(4 + i) * 32] = c1[i];
        slot[(8 + i) * 32] = c2[i];
      }
    }
  }
}

template <bool LINEAR>
__device__ __forceinline__ void qkv_consumer(uint32_t sbase, uint8_t* smem_gen, uint32_t* s_red, int cp, int rt) {
  const uint32_t bar_full = sbase + K1_BAR_OFF;
  const uint32_t bar_empty = bar_full + 8 * K1_STAGES;
  const int warp = threadIdx.x >> 5;
  const int wg = warp >> 2;
  const int lane = threadIdx.x & 31;
  float acc0[96], acc1[96];
#pragma unroll 1
  for (int kb = 0; kb < 8; kb++) {
    const int s = kb % K1_STAGES;
    mbar_wait(bar_full + 8 * s, (kb / K1_STAGES) & 1);
    if (threadIdx.x == 0) PROF_T(0, 2 + (kb >> 1));
    const uint64_t dA = mkdesc(sbase + kb * 16384 + wg * 8192, 16, 1024, 1);
    const uint64_t dB = mkdesc(sbase + K1_X_BYTES + s * K1_W_BYTES, 8192, 1024, 1);
    wg_fence();
#pragma unroll
    for (int k = 0; k < 4; k++) wgmma_ss_n192_tb(acc0, dA + k * 2, dB + k * 128, (kb | k) != 0);
    wg_commit();
    if (kb > 0) {
      wg_wait<1>();
      if ((threadIdx.x & 127) == 0) {
        const int sp = (kb - 1) % K1_STAGES;
        mbar_arrive_cluster(bar_empty + 8 * sp, 0);
        mbar_arrive_cluster(bar_empty + 8 * sp, 1);
      }
    }
  }
  wg_wait<0>();
  fence_regs(acc0);
  if ((threadIdx.x & 127) == 0) {
    mbar_arrive_cluster(bar_empty + 8 * (7 % K1_STAGES), 0);
    mbar_arrive_cluster(bar_empty + 8 * (7 % K1_STAGES), 1);
  }
  if (threadIdx.x == 0) PROF_T(0, 6);

  EpiCtx c;
  {
    const int row0 = rt * 128 + wg * 64 + (warp & 3) * 16;
    c.qf = g_qfrag + ((size_t)((LINEAR ? NH : 0) + cp * 8) * 32 + (rt * 2 + wg)) * 128 + (threadIdx.x & 127);
    uint32_t* img = reinterpret_cast<uint32_t*>(reinterpret_cast<uint8_t*>(g_kv) + (size_t)(cp * 8) * KV_HEAD_BYTES);
    c.kp = img + (row0 >> 3) * 64 + lane;
    c.vp = img + KV_K_BYTES / 4 + (row0 >> 3) * 96 + lane;
    c.s_red = s_red;
    c.red = reinterpret_cast<float*>(smem_gen + wg * 8192) + (warp & 3) * 384 + lane;
    c.lane = lane;
  }
  uint32_t pk[4];
  float vmax = 0.f;
#define K1_T1_STEP(KB)                                                                           \
  {                                                                                              \
    constexpr int g = 8 + KB;                                                                    \
    constexpr int s = g % K1_STAGES;                                                             \
    mbar_wait(bar_full + 8 * s, (g / K1_STAGES) & 1);                                            \
    const uint64_t dA = mkdesc(sbase + KB * 16384 + wg * 8192, 16, 1024, 1);                     \
    const uint64_t dB = mkdesc(sbase + K1_X_BYTES + s * K1_W_BYTES, 8192, 1024, 1);              \
    wg_fence();                                                                                  \
    _Pragma("unroll") for (int k = 0; k < 4; k++) wgmma_ss_n192_tb(acc1, dA + k * 2, dB + k * 128, (KB | k) != 0); \
    wg_commit();                                                                                 \
    epi_slice<LINEAR, 0, KB / 2, KB & 1>(acc0, c, pk, vmax);                                     \
    wg_wait<0>();                                                                                \
    if (KB + K1_STAGES < 8 && (threadIdx.x & 127) == 0) {                                        \
      mbar_arrive_cluster(bar_empty + 8 * s, 0);                                                 \
      mbar_arrive_cluster(bar_empty + 8 * s, 1);                                                 \
    }                                                                                            \
  }
  K1_T1_STEP(0) K1_T1_STEP(1) K1_T1_STEP(2) K1_T1_STEP(3) K1_T1_STEP(4) K1_T1_STEP(5) K1_T1_STEP(6) K1_T1_STEP(7)
#undef K1_T1_STEP
  fence_regs(acc1);
  if (threadIdx.x == 0) PROF_T(0, 10);
  epi_slice<LINEAR, 1, 0, 0>(acc1, c, pk, vmax);
  epi_slice<LINEAR, 1, 0, 1>(acc1, c, pk, vmax);
  epi_slice<LINEAR, 1, 1, 0>(acc1, c, pk, vmax);
  epi_slice<LINEAR, 1, 1, 1>(acc1, c, pk, vmax);
  epi_slice<LINEAR, 1, 2, 0>(acc1, c, pk, vmax);
  epi_slice<LINEAR, 1, 2, 1>(acc1, c, pk, vmax);
  epi_slice<LINEAR, 1, 3, 0>(acc1, c, pk, vmax);
  epi_slice<LINEAR, 1, 3, 1>(acc1, c, pk, vmax);
  if (!LINEAR) {
    const uint32_t vm = __reduce_max_sync(0xffffffffu, __float_as_uint(vmax) & 0x7FFFFFFFu);
    if (lane == 0) atomicMax(&s_red[16], vm);
    asm volatile("bar.sync 1, 256;" ::: "memory");
    if (threadIdx.x < 8) {
      *reinterpret_cast<float4*>(&g_nrm[((cp * 8 + threadIdx.x) * 16 + rt) * 4]) =
          make_float4(__uint_as_float(s_red[threadIdx.x * 2]), __uint_as_float(s_red[threadIdx.x * 2 + 1]), __uint_as_float(s_red[16]), 0.f);
    }
  } else {
    asm volatile("bar.sync 1, 256;" ::: "memory");
    float* dst = g_kvpart + ((size_t)rt * NH + cp * 8) * 384;
#pragma unroll
    for (int i = 0; i < 12; i++) {
      const int o = threadIdx.x + i * 256;
      const int h = o / 384, e = o - h * 384;
      const float* src = reinterpret_cast<const float*>(smem_gen) + K1_SLOT_KB(h) * 4096 + e;
      float sum = 0.f;
#pragma unroll
      for (int w = 0; w < 8; w++) sum += src[(w >> 2) * 2048 + (w & 3) * 384];
      dst[o] = sum;
    }
  }
}

__global__ void __launch_bounds__(384, 1)
qkv_gemm_kernel(const __grid_constant__ CUtensorMap mxA, const __grid_constant__ CUtensorMap mxB,
                const __grid_constant__ CUtensorMap mwA, const __grid_constant__ CUtensorMap mwB) {
  extern __shared__ uint8_t smem_raw[];
  const uint32_t sbase = (smem_u32(smem_raw) + 1023) & ~1023u;
  uint8_t* smem_gen = smem_raw + (sbase - smem_u32(smem_raw));
  const uint32_t bar_full = sbase + K1_BAR_OFF;
  const uint32_t bar_empty = bar_full + 8 * K1_STAGES;
  uint32_t* s_red = reinterpret_cast<uint32_t*>(smem_gen + K1_BAR_OFF + 64);

  const int rank = blockIdx.x & 1;
  const int pair = blockIdx.x >> 1;
  const int branch = pair >> 5;
  const int rp = (pair & 31) >> 2;
  const int cp = pair & 3;
  const int rt = rp * 2 + rank;
  const int warp = threadIdx.x >> 5;
  if (threadIdx.x == 0) { PROF_G(0, 30); PROF_T(0, 0); }
  const CUtensorMap* mx = branch ? &mxA : &mxB;
  const CUtensorMap* mw = branch ? &mwA : &mwB;

  if (threadIdx.x == 256) {
    asm volatile("prefetch.tensormap [%0];" ::"l"(mx) : "memory");
    asm volatile("prefetch.tensormap [%0];" ::"l"(mw) : "memory");
    for (int i = 0; i < K1_STAGES; i++) {
      mbar_init(bar_full + 8 * i, 1);
      mbar_init(bar_empty + 8 * i, 4);
    }
    fence_barrier_init();
    fence_proxy_async();
    for (int kb = 0; kb < K1_STAGES; kb++) mbar_expect_tx(bar_full + 8 * kb, 16384 + K1_W_BYTES);
    tma_load_2d(sbase, mx, 0, rt * 128, bar_full);
  }
  pdl_launch_dependents();
  if (threadIdx.x < 32) s_red[threadIdx.x] = 0;
  __syncthreads();
  cluster_sync_relaxed();
  if (threadIdx.x == 0) PROF_T(0, 1);

  if (warp >= 8) {
    asm volatile("setmaxnreg.dec.sync.aligned.u32 40;");
    if (threadIdx.x == 256) {
      for (int g = 0; g < 16; g++) {
        const int s = g % K1_STAGES;
        const int kb = g & 7;
        if (g >= K1_STAGES) {
          mbar_wait(bar_empty + 8 * s, ((g / K1_STAGES) - 1) & 1);
          mbar_expect_tx(bar_full + 8 * s, (g < 8 ? 16384 : 0) + K1_W_BYTES);
        }
        if (g > 0 && g < 8) tma_load_2d(sbase + kb * 16384, mx, kb * 64, rt * 128, bar_full + 8 * s);
        const int h0 = cp * 8 + (g >> 3) * 4;
        const uint32_t st = sbase + K1_X_BYTES + s * K1_W_BYTES + rank * 4096;
#pragma unroll
        for (int p = 0; p < 3; p++)
          tma_load_2d_mc(st + p * 8192, mw, p * 512 + h0 * 16, kb * 64 + rank * 32, bar_full + 8 * s, (uint16_t)3);
      }
    }
    __syncwarp();
    cluster_sync_relaxed();
  } else {
    asm volatile("setmaxnreg.inc.sync.aligned.u32 232;");
    if (branch == 0) qkv_consumer<false>(sbase, smem_gen, s_red, cp, rt);
    else qkv_consumer<true>(sbase, smem_gen, s_red, cp, rt);
    if (threadIdx.x == 0) PROF_T(0, 11);
    __syncwarp();
    cluster_sync_relaxed();
    if (threadIdx.x == 0) { PROF_T(0, 12); PROF_G(0, 31); }
  }
}

constexpr int K2_SMEM = KV_HEAD_BYTES + 1024 + 256;

#define ATT_NPOLY 18
#define ATT_CH 4
#define ATT_D 2
#define ATT_GM 1
#define ATT_DEG 2
struct ExpC {
  uint32_t k3c00, kmask, seven, c3;
};
__device__ __forceinline__ uint32_t hfma2(uint32_t a, uint32_t b, uint32_t c) {
  uint32_t r;
  asm("fma.rn.f16x2 %0, %1, %2, %3;" : "=r"(r) : "r"(a), "r"(b), "r"(c));
  return r;
}
__device__ __forceinline__ uint32_t exp2_poly_pair(float t0, float t1, const ExpC& c) {
  uint32_t u;
  asm("prmt.b32 %0, %1, %2, 0x5410;" : "=r"(u) : "r"(__float_as_uint(t0)), "r"(__float_as_uint(t1)));
  uint32_t m;
  asm("lop3.b32 %0, %1, 0x03FF03FF, %2, 0xEA;" : "=r"(m) : "r"(u), "r"(c.k3c00));
  uint32_t p = hfma2(m, c.c3, 0xa385a385u);
  p = hfma2(p, m, 0x4ad64ad7u);
  uint32_t mu;
  asm("lop3.b32 %0, %1, 0xFC00FC00, %2, 0xEA;" : "=r"(mu) : "r"(u), "r"(c.kmask));
  uint32_t r;
  asm("{.reg .b32 t; shf.r.wrap.b32 t, %1, %2, 3; add.u32 %0, t, %3;}" : "=r"(r) : "r"(mu), "r"(c.seven), "r"(p));
  return r;
}
__device__ __forceinline__ float gadd(float x, float M, uint32_t g) {
  float r = x;
  asm("{.reg .pred p; setp.ne.b32 p, %2, -1; @p add.f32 %0, %0, %1;}" : "+f"(r) : "f"(M), "r"(g));
  return r;
}
__device__ __forceinline__ float gex2(float x, uint32_t g) {
  float r = x;
  asm("{.reg .pred p; setp.ne.b32 p, %1, -1; @p ex2.approx.ftz.f32 %0, %0;}" : "+f"(r) : "r"(g));
  return r;
}
template <int NPOLY, int NPAIR, int CH, int D>
__device__ __forceinline__ void exp_tile(const float (&s)[2 * NPAIR], uint32_t (&p)[NPAIR], const ExpC& c) {
#pragma unroll
  for (int i = 0; i < NPAIR; i++) {
    const bool isPoly = ((i + 1) * NPOLY / 32) != (i * NPOLY / 32);
    const int ch = i / CH;
    const bool gated = ch >= D;
    int gi = (ch - D) * CH + CH - 1;
    if (gated) {
      while (gi > (ch - D) * CH && !(((gi + 1) * NPOLY / 32) != (gi * NPOLY / 32))) gi--;
    }
    const uint32_t g = gated ? p[gi] : 0;
    if (!isPoly) {
      if (gated && ATT_GM) p[i] = pack_bf16(gex2(s[2 * i], g), gex2(s[2 * i + 1], g));
      else p[i] = pack_bf16(ex2f(s[2 * i]), ex2f(s[2 * i + 1]));
    } else {
      if (gated) p[i] = exp2_poly_pair(gadd(s[2 * i], 12329.f, g), gadd(s[2 * i + 1], 12329.f, g), c);
      else p[i] = exp2_poly_pair(s[2 * i] + 12329.f, s[2 * i + 1] + 12329.f, c);
    }
  }
}

__device__ __forceinline__ void store_o(__nv_bfloat16* o, int row0, int head, int lane, const uint32_t (&r)[4]) {
  const int g = lane >> 2, t = lane & 3;
  uint32_t* p0 = reinterpret_cast<uint32_t*>(o + (size_t)(row0 + g) * DM + head * 16) + t;
  uint32_t* p1 = reinterpret_cast<uint32_t*>(o + (size_t)(row0 + g + 8) * DM + head * 16) + t;
  p0[0] = r[0];
  p1[0] = r[1];
  p0[4] = r[2];
  p1[4] = r[3];
}

__device__ __forceinline__ void safe_exp(const float (&s)[32], uint32_t (&p)[16], float (&o)[12], float& m0, float& m1) {
  float x0 = s[0], x1 = s[2];
#pragma unroll
  for (int i = 0; i < 8; i++) {
    x0 = fmaxf(x0, fmaxf(s[4 * i], s[4 * i + 1]));
    x1 = fmaxf(x1, fmaxf(s[4 * i + 2], s[4 * i + 3]));
  }
  x0 = fmaxf(x0, __shfl_xor_sync(0xffffffffu, x0, 1));
  x1 = fmaxf(x1, __shfl_xor_sync(0xffffffffu, x1, 1));
  x0 = fmaxf(x0, __shfl_xor_sync(0xffffffffu, x0, 2));
  x1 = fmaxf(x1, __shfl_xor_sync(0xffffffffu, x1, 2));
  const float n0 = fmaxf(m0, x0), n1 = fmaxf(m1, x1);
  const float c0 = ex2f(m0 - n0), c1 = ex2f(m1 - n1);
  m0 = n0;
  m1 = n1;
#pragma unroll
  for (int i = 0; i < 3; i++) {
    o[4 * i] *= c0;
    o[4 * i + 1] *= c0;
    o[4 * i + 2] *= c1;
    o[4 * i + 3] *= c1;
  }
#pragma unroll
  for (int i = 0; i < 8; i++) {
    p[2 * i] = pack_bf16(ex2f(s[4 * i] - n0), ex2f(s[4 * i + 1] - n0));
    p[2 * i + 1] = pack_bf16(ex2f(s[4 * i + 2] - n1), ex2f(s[4 * i + 3] - n1));
  }
}

__device__ __forceinline__ void attn_step(float (&sx)[32], float (&sy)[32], float (&o)[12], const uint4& qf, uint64_t dK, uint64_t dV,
                                          const ExpC& ec) {
  uint32_t pa[16], pb[16];
  wg_fence();
  wgmma_rs_n64_z(sy, qf.x, qf.y, qf.z, qf.w, dK + 128);
  wg_commit();
  exp_tile<ATT_NPOLY, 16, ATT_CH, ATT_D>(sx, pa, ec);
  wg_fence();
  wgmma_rs_n24_tb(o, pa[12], pa[13], pa[14], pa[15], dV + 3 * 48, 1);
  wg_commit();
  wg_wait<1>();
  fence_regs(sy);
  exp_tile<ATT_NPOLY, 16, ATT_CH, ATT_D>(sy, pb, ec);
  wg_fence();
#pragma unroll
  for (int k = 0; k < 3; k++) wgmma_rs_n24_tb(o, pa[4 * k], pa[4 * k + 1], pa[4 * k + 2], pa[4 * k + 3], dV + k * 48, 1);
#pragma unroll
  for (int k = 0; k < 4; k++) wgmma_rs_n24_tb(o, pb[4 * k], pb[4 * k + 1], pb[4 * k + 2], pb[4 * k + 3], dV + (4 + k) * 48, 1);
  wgmma_rs_n64_z(sy, qf.x, qf.y, qf.z, qf.w, dK + 256);
  wg_commit();
  wg_wait<0>();
  fence_regs(sy);
}

template <bool SAFE>
__device__ __forceinline__ void attn_tile(uint64_t dK, uint64_t dV, uint32_t bar, const uint4 qf, const ExpC& ec, uint32_t (&outp)[4]) {
  float o[12];
#pragma unroll
  for (int i = 0; i < 12; i++) asm volatile("mov.f32 %0, 0f00000000;" : "=f"(o[i]));
  mbar_wait(bar, 0);
  if (!SAFE) {
    float s0[32], s1[32];
    wg_fence();
    wgmma_rs_n64_z(s0, qf.x, qf.y, qf.z, qf.w, dK);
    wg_commit();
    wg_wait<0>();
    fence_regs(s0);
#pragma unroll 1
    for (int c = 0; c < 4; c++) {
      if (c > 0) mbar_wait(bar + 8 * c, 0);
#pragma unroll 1
      for (int j = 0; j < 2; j++) {
        attn_step(s0, s1, o, qf, dK, dV, ec);
        attn_step(s1, s0, o, qf, dK + 256, dV + 384, ec);
        dK += 512;
        dV += 768;
      }
    }
  } else {
    float m0 = -INFINITY, m1 = -INFINITY;
#pragma unroll 1
    for (int j = 0; j < 32; j++) {
      if ((j & 7) == 0) mbar_wait(bar + 8 * (j >> 3), 0);
      float s[32];
      uint32_t p[16];
      wg_fence();
      wgmma_rs_n64_z(s, qf.x, qf.y, qf.z, qf.w, dK);
      wg_commit();
      wg_wait<0>();
      fence_regs(s);
      safe_exp(s, p, o, m0, m1);
      wg_fence();
#pragma unroll
      for (int k = 0; k < 4; k++) wgmma_rs_n24_tb(o, p[4 * k], p[4 * k + 1], p[4 * k + 2], p[4 * k + 3], dV + k * 48, 1);
      wg_commit();
      wg_wait<0>();
      fence_regs(o);
      dK += 128;
      dV += 192;
    }
  }
  fence_regs(o);
  const float r0 = 1.0f / o[8], r1 = 1.0f / o[10];
  outp[0] = pack_bf16(o[0] * r0, o[1] * r0);
  outp[1] = pack_bf16(o[2] * r1, o[3] * r1);
  outp[2] = pack_bf16(o[4] * r0, o[5] * r0);
  outp[3] = pack_bf16(o[6] * r1, o[7] * r1);
}

__device__ __forceinline__ void linear_attn_cta(uint8_t* smem_raw, uint32_t sbase, const CUtensorMap* mo16, int cta) {
  const int warp = threadIdx.x >> 5, lane = threadIdx.x & 31;
  float* red = reinterpret_cast<float*>(smem_raw + (sbase - smem_u32(smem_raw)) + 131072);
  {
    const float* src = g_kvpart + (size_t)cta * 8 * 384;
    float sum[6];
#pragma unroll
    for (int i = 0; i < 6; i++) sum[i] = 0.f;
#pragma unroll
    for (int r = 0; r < 16; r++) {
#pragma unroll
      for (int i = 0; i < 6; i++) sum[i] += src[(size_t)r * NH * 384 + threadIdx.x + i * 512];
    }
#pragma unroll
    for (int i = 0; i < 6; i++) red[threadIdx.x + i * 512] = round_bf16(sum[i]);
  }
  __syncthreads();
  uint32_t bf[8][6];
  {
    const int g = lane >> 2, t = lane & 3;
#pragma unroll
    for (int h = 0; h < 8; h++) {
#pragma unroll
      for (int f = 0; f < 6; f++) {
        const int blk = f >> 1, half = f & 1;
        const int e = (blk == 2) ? 0 : g;
        const int d = 2 * t + 8 * half;
        const int base = h * 384 + (blk * 4 + half * 2 + (e & 1)) * 32 + (e >> 1);
        bf[h][f] = pack_bf16(red[base + (d & 7) * 4], red[base + ((d + 1) & 7) * 4]);
      }
    }
  }
  const uint32_t stg = sbase + warp * 8192;
#pragma unroll 1
  for (int rb = 0; rb < 8; rb++) {
    const int blk16 = rb * 16 + warp;
    const uint4* qp = g_qfrag + ((size_t)(NH + cta * 8) * 32 + (blk16 >> 2)) * 128 + (blk16 & 3) * 32 + lane;
    uint4 q[8];
#pragma unroll
    for (int h = 0; h < 8; h++) q[h] = qp[h * 32 * 128];
    const uint32_t buf = stg + (rb & 1) * 4096;
    if (rb >= 2) {
      if (lane == 0) asm volatile("cp.async.bulk.wait_group.read 1;" ::: "memory");
      __syncwarp();
    }
#pragma unroll
    for (int h = 0; h < 8; h++) {
      float n0[4] = {0, 0, 0, 0}, n1[4] = {0, 0, 0, 0}, dn[4] = {0, 0, 0, 0};
      hmma(n0, q[h].x, q[h].y, q[h].z, q[h].w, bf[h][0], bf[h][1]);
      hmma(n1, q[h].x, q[h].y, q[h].z, q[h].w, bf[h][2], bf[h][3]);
      hmma(dn, q[h].x, q[h].y, q[h].z, q[h].w, bf[h][4], bf[h][5]);
      const float d0 = round_bf16(round_bf16(dn[0]) + 1e-6f), d1 = round_bf16(round_bf16(dn[2]) + 1e-6f);
      const uint32_t r0 = pack_bf16(__fdividef(round_bf16(n0[0]), d0), __fdividef(round_bf16(n0[1]), d0));
      const uint32_t r1 = pack_bf16(__fdividef(round_bf16(n0[2]), d1), __fdividef(round_bf16(n0[3]), d1));
      const uint32_t r2 = pack_bf16(__fdividef(round_bf16(n1[0]), d0), __fdividef(round_bf16(n1[1]), d0));
      const uint32_t r3 = pack_bf16(__fdividef(round_bf16(n1[2]), d1), __fdividef(round_bf16(n1[3]), d1));
      const int row = lane & 15;
      const int chunk = (h & 3) * 2 + (lane >> 4);
      const uint32_t addr = buf + (h >> 2) * 2048 + row * 128 + ((chunk ^ (row & 7)) << 4);
      asm volatile("stmatrix.sync.aligned.m8n8.x4.shared.b16 [%0], {%1,%2,%3,%4};" ::"r"(addr), "r"(r0), "r"(r1), "r"(r2), "r"(r3)
                   : "memory");
    }
    fence_proxy_async();
    __syncwarp();
    if (lane == 0) {
      tma_store_2d(mo16, buf, cta * 128, blk16 * 16);
      tma_store_2d(mo16, buf + 2048, cta * 128 + 64, blk16 * 16);
      asm volatile("cp.async.bulk.commit_group;" ::: "memory");
    }
  }
  if (lane == 0) asm volatile("cp.async.bulk.wait_group 0;" ::: "memory");
}

__global__ void __launch_bounds__(512, 1) attn_kernel(const __grid_constant__ CUtensorMap mo16) {
  extern __shared__ uint8_t smem_raw[];
  const uint32_t sbase = (smem_u32(smem_raw) + 1023) & ~1023u;
  const uint32_t bar = sbase + KV_HEAD_BYTES;
  if (threadIdx.x == 0) { PROF_G(1, 30); PROF_T(1, 0); }
  if (threadIdx.x == 0) {
    for (int i = 0; i < 4; i++) mbar_init(bar + 8 * i, 1);
    fence_barrier_init();
    fence_proxy_async();
  }
  __syncthreads();
  pdl_launch_dependents();
  pdl_wait();
  if (blockIdx.x >= 128) {
    linear_attn_cta(smem_raw, sbase, &mo16, blockIdx.x - 128);
    if (threadIdx.x == 0) { PROF_T(1, 5); PROF_G(1, 31); }
    return;
  }
  const int head = blockIdx.x >> 2, qb = blockIdx.x & 3;
  if (threadIdx.x == 0) {
    const uint8_t* img = reinterpret_cast<const uint8_t*>(g_kv) + (size_t)head * KV_HEAD_BYTES;
    mbar_expect_tx(bar, 32768 + 24576);
    bulk_load(sbase, img, 32768, bar);
    bulk_load(sbase + KV_K_BYTES, img + KV_K_BYTES, 24576, bar);
    for (int i = 1; i < 4; i++) {
      mbar_expect_tx(bar + 8 * i, (i < 3 ? 16384 : 0) + 24576);
      if (i < 3) bulk_load(sbase + (i + 1) * 16384, img + (i + 1) * 16384, 16384, bar + 8 * i);
      bulk_load(sbase + KV_K_BYTES + i * 24576, img + KV_K_BYTES + i * 24576, 24576, bar + 8 * i);
    }
  }
  const int lane = threadIdx.x & 31;
  bool safe_path;
  {
    float4 n = make_float4(0.f, 0.f, 0.f, 0.f);
    if (lane < 16) n = *reinterpret_cast<const float4*>(&g_nrm[(head * 16 + lane) * 4]);
    uint32_t qm = ((lane >> 2) == qb) ? __float_as_uint(n.x) : 0u;
    qm = __reduce_max_sync(0xffffffffu, qm);
    const uint32_t km = __reduce_max_sync(0xffffffffu, __float_as_uint(n.y));
    const uint32_t vm = __reduce_max_sync(0xffffffffu, __float_as_uint(n.z));
    const float b2 = __uint_as_float(qm) * (QSCALE * QSCALE) * __uint_as_float(km) * 1.02f;
    const float vmax = __uint_as_float(vm);
    const bool ok = (b2 <= 21.5f * 21.5f) && (vmax <= 1.0e24f) && (vmax >= 1.0e-18f || vmax == 0.f);
    safe_path = !ok;
  }
  const int wg = threadIdx.x >> 7, warp = (threadIdx.x >> 5) & 3;
  uint32_t zero;
  asm volatile("mov.u32 %0, %%smid;" : "=r"(zero));
  zero >>= 16;
  const ExpC ec{0x3C003C00u + zero, 0x00070000u + zero, 7u + zero, (ATT_DEG == 3 ? 0x2cfd2cfdu : 0x35623562u) + zero};
  const uint64_t dK = mkdesc(sbase, 128, 256, 0);
  const uint64_t dV = mkdesc(sbase + KV_K_BYTES, 384, 128, 0);
#pragma unroll 1
  for (int t = 0; t < 2; t++) {
    const int tile64 = qb * 8 + wg * 2 + t;
    const uint4 qf = g_qfrag[(head * 32 + tile64) * 128 + (threadIdx.x & 127)];
    uint32_t r[4];
    if (threadIdx.x == 0) PROF_T(1, 1 + t);
    if (!safe_path) attn_tile<false>(dK, dV, bar, qf, ec, r);
    else attn_tile<true>(dK, dV, bar, qf, ec, r);
    store_o(g_o + (size_t)S_LEN * DM, tile64 * 64 + warp * 16, head, lane, r);
  }
  if (threadIdx.x == 0) { PROF_T(1, 5); PROF_G(1, 31); }
}

constexpr int K3_STAGES = 5;
constexpr int K3_W_BYTES = 8 * 16384;
constexpr int K3_BAR_OFF = K3_W_BYTES + K3_STAGES * 16384;
constexpr int K3_SMEM = K3_BAR_OFF + 256 + 1024;

__global__ void __launch_bounds__(288, 1)
out_gemm_kernel(const __grid_constant__ CUtensorMap mo, const __grid_constant__ CUtensorMap mwA,
                const __grid_constant__ CUtensorMap mwB, const __grid_constant__ CUtensorMap mout) {
  extern __shared__ uint8_t smem_raw[];
  const uint32_t sbase = (smem_u32(smem_raw) + 1023) & ~1023u;
  const uint32_t bar_full = sbase + K3_BAR_OFF;
  const uint32_t bar_empty = bar_full + 8 * K3_STAGES;
  const uint32_t bar_w = bar_empty + 8 * K3_STAGES;
  const int branch = blockIdx.x >> 6;
  const int rt = (blockIdx.x & 63) >> 2;
  const int ct = blockIdx.x & 3;
  const int warp = threadIdx.x >> 5;
  if (threadIdx.x == 0) { PROF_G(2, 30); PROF_T(2, 0); }
  if (threadIdx.x == 256) {
    const CUtensorMap* mw = branch ? &mwB : &mwA;
    asm volatile("prefetch.tensormap [%0];" ::"l"(mw) : "memory");
    asm volatile("prefetch.tensormap [%0];" ::"l"(&mo) : "memory");
    asm volatile("prefetch.tensormap [%0];" ::"l"(&mout) : "memory");
    for (int i = 0; i < K3_STAGES; i++) {
      mbar_init(bar_full + 8 * i, 1);
      mbar_init(bar_empty + 8 * i, 2);
    }
    for (int i = 0; i < 8; i++) mbar_init(bar_w + 8 * i, 1);
    fence_barrier_init();
    fence_proxy_async();
    for (int kb = 0; kb < 8; kb++) {
      mbar_expect_tx(bar_w + 8 * kb, 16384);
      tma_load_2d(sbase + kb * 16384, mw, ct * 128, kb * 64, bar_w + 8 * kb);
      tma_load_2d(sbase + kb * 16384 + 8192, mw, ct * 128 + 64, kb * 64, bar_w + 8 * kb);
    }
  }
  __syncthreads();
  if (warp == 8) {
    if ((threadIdx.x & 31) == 0) {
      pdl_wait();
      PROF_T(2, 1);
      for (int kb = 0; kb < 8; kb++) {
        const int s = kb % K3_STAGES;
        if (kb >= K3_STAGES) mbar_wait(bar_empty + 8 * s, ((kb / K3_STAGES) - 1) & 1);
        mbar_expect_tx(bar_full + 8 * s, 16384);
        tma_load_2d(sbase + K3_W_BYTES + s * 16384, &mo, kb * 64, branch * S_LEN + rt * 128, bar_full + 8 * s);
      }
    }
  } else {
    const int wg = warp >> 2;
    float acc[64];
    for (int kb = 0; kb < 8; kb++) {
      const int s = kb % K3_STAGES;
      mbar_wait(bar_w + 8 * kb, 0);
      mbar_wait(bar_full + 8 * s, (kb / K3_STAGES) & 1);
      if (threadIdx.x == 0) PROF_T(2, 2 + kb);
      const uint64_t dA = mkdesc(sbase + K3_W_BYTES + s * 16384 + wg * 8192, 16, 1024, 1);
      const uint64_t dB = mkdesc(sbase + kb * 16384, 8192, 1024, 1);
      wg_fence();
#pragma unroll
      for (int k = 0; k < 4; k++) wgmma_ss_n128_tb(acc, dA + k * 2, dB + k * 128, (kb | k) != 0);
      wg_commit();
      if (kb > 0) {
        wg_wait<1>();
        if ((threadIdx.x & 127) == 0) mbar_arrive(bar_empty + 8 * ((kb - 1) % K3_STAGES));
      }
    }
    wg_wait<0>();
    fence_regs(acc);
    if (threadIdx.x == 0) PROF_T(2, 10);
    const uint32_t stg = sbase + K3_W_BYTES + wg * 8192;
    asm volatile("bar.sync 1, 256;" ::: "memory");
    const int lane = threadIdx.x & 31;
    const int rloc = (warp & 3) * 16 + (lane & 15);
#pragma unroll
    for (int c16 = 0; c16 < 8; c16++) {
      const float* a = &acc[c16 * 8];
      const uint32_t r0 = pack_bf16(a[0], a[1]), r1 = pack_bf16(a[2], a[3]), r2 = pack_bf16(a[4], a[5]), r3 = pack_bf16(a[6], a[7]);
      const int chunk = (c16 & 3) * 2 + (lane >> 4);
      const uint32_t addr = stg + (c16 >> 2) * 16384 + rloc * 128 + ((chunk ^ (rloc & 7)) << 4);
      asm volatile("stmatrix.sync.aligned.m8n8.x4.shared.b16 [%0], {%1,%2,%3,%4};" ::"r"(addr), "r"(r0), "r"(r1), "r"(r2), "r"(r3)
                   : "memory");
    }
    fence_proxy_async();
    asm volatile("bar.sync %0, 128;" ::"r"(2 + wg) : "memory");
    if ((threadIdx.x & 127) == 0) {
      tma_store_2d(&mout, stg, branch * DM + ct * 128, rt * 128 + wg * 64);
      tma_store_2d(&mout, stg + 16384, branch * DM + ct * 128 + 64, rt * 128 + wg * 64);
      asm volatile("cp.async.bulk.commit_group;" ::: "memory");
      asm volatile("cp.async.bulk.wait_group.read 0;" ::: "memory");
      if (threadIdx.x == 0) { PROF_T(2, 12); PROF_G(2, 31); }
    }
  }
}

typedef CUresult (*EncodeFn)(CUtensorMap*, CUtensorMapDataType, cuuint32_t, void*, const cuuint64_t*, const cuuint64_t*,
                             const cuuint32_t*, const cuuint32_t*, CUtensorMapInterleave, CUtensorMapSwizzle,
                             CUtensorMapL2promotion, CUtensorMapFloatOOBfill);

void make_map(EncodeFn enc, CUtensorMap* m, const void* ptr, uint64_t inner, uint64_t outer, uint32_t box_inner, uint32_t box_outer) {
  cuuint64_t dims[2] = {inner, outer};
  cuuint64_t strides[1] = {inner * 2};
  cuuint32_t box[2] = {box_inner, box_outer};
  cuuint32_t es[2] = {1, 1};
  enc(m, CU_TENSOR_MAP_DATA_TYPE_BFLOAT16, 2, const_cast<void*>(ptr), dims, strides, box, es, CU_TENSOR_MAP_INTERLEAVE_NONE,
      CU_TENSOR_MAP_SWIZZLE_128B, CU_TENSOR_MAP_L2_PROMOTION_L2_256B, CU_TENSOR_MAP_FLOAT_OOB_FILL_NONE);
}

struct HostState {
  bool init;
  const void* key[7];
  CUtensorMap mxA, mxB, mwA, mwB, mo, mo16, mwoA, mwoB, mout;
};
HostState g_hs;

}

extern "C" void kernel_launch(void* const* d_in, const int* in_sizes, int n_in, void* d_out, int out_size) {
  (void)in_sizes; (void)n_in; (void)out_size;
  HostState& hs = g_hs;
  bool same = hs.init && hs.key[6] == d_out;
  for (int i = 0; i < 6 && same; i++) same = hs.key[i] == d_in[i];
  if (!same) {
    void* fn = nullptr;
    cudaDriverEntryPointQueryResult qr;
    cudaGetDriverEntryPoint("cuTensorMapEncodeTiled", &fn, cudaEnableDefault, &qr);
    EncodeFn enc = (EncodeFn)fn;
    void* go = nullptr;
    cudaGetSymbolAddress(&go, g_o);
    make_map(enc, &hs.mxA, d_in[0], 512, 2048, 64, 128);
    make_map(enc, &hs.mwA, d_in[1], 1536, 512, 64, 32);
    make_map(enc, &hs.mwoA, d_in[2], 512, 512, 64, 64);
    make_map(enc, &hs.mxB, d_in[3], 512, 2048, 64, 128);
    make_map(enc, &hs.mwB, d_in[4], 1536, 512, 64, 32);
    make_map(enc, &hs.mwoB, d_in[5], 512, 512, 64, 64);
    make_map(enc, &hs.mo, go, 512, 4096, 64, 128);
    make_map(enc, &hs.mo16, go, 512, 4096, 64, 16);
    make_map(enc, &hs.mout, d_out, 1024, 2048, 64, 64);
    cudaFuncSetAttribute(qkv_gemm_kernel, cudaFuncAttributeMaxDynamicSharedMemorySize, K1_SMEM);
    cudaFuncSetAttribute(attn_kernel, cudaFuncAttributeMaxDynamicSharedMemorySize, K2_SMEM);
    cudaFuncSetAttribute(out_gemm_kernel, cudaFuncAttributeMaxDynamicSharedMemorySize, K3_SMEM);
    for (int i = 0; i < 6; i++) hs.key[i] = d_in[i];
    hs.key[6] = d_out;
    hs.init = true;
  }
  cudaStream_t st = cudaStreamPerThread;
  {
    cudaLaunchConfig_t cfg = {};
    cfg.gridDim = dim3(128);
    cfg.blockDim = dim3(384);
    cfg.dynamicSmemBytes = K1_SMEM;
    cfg.stream = st;
    cudaLaunchAttribute at[1];
    at[0].id = cudaLaunchAttributeClusterDimension;
    at[0].val.clusterDim.x = 2;
    at[0].val.clusterDim.y = 1;
    at[0].val.clusterDim.z = 1;
    cfg.attrs = at;
    cfg.numAttrs = 1;
    cudaLaunchKernelEx(&cfg, qkv_gemm_kernel, hs.mxA, hs.mxB, hs.mwA, hs.mwB);
  }
  {
    cudaLaunchConfig_t cfg = {};
    cfg.gridDim = dim3(132);
    cfg.blockDim = dim3(512);
    cfg.dynamicSmemBytes = K2_SMEM;
    cfg.stream = st;
    cudaLaunchAttribute at[1];
    at[0].id = cudaLaunchAttributeProgrammaticStreamSerialization;
    at[0].val.programmaticStreamSerializationAllowed = 1;
    cfg.attrs = at;
    cfg.numAttrs = 1;
    cudaLaunchKernelEx(&cfg, attn_kernel, hs.mo16);
    cfg.gridDim = dim3(128);
    cfg.blockDim = dim3(288);
    cfg.dynamicSmemBytes = K3_SMEM;
    cudaLaunchKernelEx(&cfg, out_gemm_kernel, hs.mo, hs.mwoA, hs.mwoB, hs.mout);
  }
}
```

```cpp
#include <cuda_runtime.h>
#include <cuda_bf16.h>
#include <cuda.h>
#include <stdint.h>

namespace {

constexpr int S_LEN = 2048;
constexpr int DM = 512;
constexpr int NH = 32;

constexpr int KV_K_BYTES = 65536;
constexpr int KV_HEAD_BYTES = KV_K_BYTES + 98304;
__device__ uint4 g_qfrag[2 * NH * 32 * 128];
__device__ uint4 g_kv[NH * KV_HEAD_BYTES / 16];
__device__ float g_kvpart[16 * NH * 384];
__device__ float g_nrm[NH * 16 * 4];
__device__ __nv_bfloat16 g_o[2 * S_LEN * DM];

#define PROF_T(k, i) do {} while (0)
#define PROF_G(k, i) do {} while (0)
__device__ __forceinline__ uint32_t smem_u32(const void* p) { return (uint32_t)__cvta_generic_to_shared(p); }
__device__ __forceinline__ void mbar_init(uint32_t bar, int cnt) {
  asm volatile("mbarrier.init.shared::cta.b64 [%0], %1;" ::"r"(bar), "r"(cnt) : "memory");
}
__device__ __forceinline__ void mbar_expect_tx(uint32_t bar, uint32_t bytes) {
  asm volatile("mbarrier.arrive.expect_tx.shared::cta.b64 _, [%0], %1;" ::"r"(bar), "r"(bytes) : "memory");
}
__device__ __forceinline__ void mbar_arrive(uint32_t bar) {
  asm volatile("mbarrier.arrive.shared::cta.b64 _, [%0];" ::"r"(bar) : "memory");
}
__device__ __forceinline__ void mbar_arrive_cluster(uint32_t bar, uint32_t cta) {
  asm volatile(
      "{\n.reg .b32 ra;\nmapa.shared::cluster.u32 ra, %0, %1;\n"
      "mbarrier.arrive.shared::cluster.b64 _, [ra];\n}" ::"r"(bar), "r"(cta) : "memory");
}
__device__ __forceinline__ void mbar_wait(uint32_t bar, uint32_t parity) {
  asm volatile(
      "{\n.reg .pred p;\n"
      "WAIT_LOOP:\n"
      "mbarrier.try_wait.parity.shared::cta.b64 p, [%0], %1, 0x989680;\n"
      "@p bra WAIT_DONE;\n"
      "bra WAIT_LOOP;\n"
      "WAIT_DONE:\n}" ::"r"(bar), "r"(parity) : "memory");
}
__device__ __forceinline__ void mbar_wait_cluster(uint32_t bar, uint32_t parity) {
  asm volatile(
      "{\n.reg .pred p;\n"
      "WAIT_LOOP:\n"
      "mbarrier.try_wait.parity.acquire.cluster.shared::cta.b64 p, [%0], %1, 0x989680;\n"
      "@p bra WAIT_DONE;\n"
      "bra WAIT_LOOP;\n"
      "WAIT_DONE:\n}" ::"r"(bar), "r"(parity) : "memory");
}
__device__ __forceinline__ void fence_barrier_init() {
  asm volatile("fence.mbarrier_init.release.cluster;" ::: "memory");
}
__device__ __forceinline__ void fence_proxy_async() { asm volatile("fence.proxy.async.shared::cta;" ::: "memory"); }
__device__ __forceinline__ void cluster_sync_relaxed() {
  asm volatile("barrier.cluster.arrive.relaxed.aligned;\nbarrier.cluster.wait.aligned;" ::: "memory");
}
__device__ __forceinline__ void tma_load_2d(uint32_t dst, const CUtensorMap* m, int x, int y, uint32_t bar) {
  asm volatile(
      "cp.async.bulk.tensor.2d.shared::cluster.global.mbarrier::complete_tx::bytes [%0], [%1, {%3, %4}], [%2];" ::"r"(dst),
      "l"(m), "r"(bar), "r"(x), "r"(y)
      : "memory");
}
__device__ __forceinline__ void tma_load_2d_mc(uint32_t dst, const CUtensorMap* m, int x, int y, uint32_t bar, uint16_t mask) {
  asm volatile(
      "cp.async.bulk.tensor.2d.shared::cluster.global.mbarrier::complete_tx::bytes.multicast::cluster [%0], [%1, {%3, %4}], "
      "[%2], %5;" ::"r"(dst),
      "l"(m), "r"(bar), "r"(x), "r"(y), "h"(mask)
      : "memory");
}
__device__ __forceinline__ void tma_store_2d(const CUtensorMap* m, uint32_t src, int x, int y) {
  asm volatile("cp.async.bulk.tensor.2d.global.shared::cta.bulk_group [%0, {%2, %3}], [%1];" ::"l"(m), "r"(src), "r"(x),
               "r"(y)
               : "memory");
}
__device__ __forceinline__ void bulk_load(uint32_t dst, const void* src, uint32_t bytes, uint32_t bar) {
  asm volatile("cp.async.bulk.shared::cluster.global.mbarrier::complete_tx::bytes [%0], [%1], %2, [%3];" ::"r"(dst),
               "l"(src), "r"(bytes), "r"(bar)
               : "memory");
}
__device__ __forceinline__ void bulk_load_mc(uint32_t dst, const void* src, uint32_t bytes, uint32_t bar, uint16_t mask) {
  asm volatile("cp.async.bulk.shared::cluster.global.mbarrier::complete_tx::bytes.multicast::cluster [%0], [%1], %2, [%3], %4;" ::"r"(dst),
               "l"(src), "r"(bytes), "r"(bar), "h"(mask)
               : "memory");
}
__device__ __forceinline__ void pdl_launch_dependents() { asm volatile("griddepcontrol.launch_dependents;" ::: "memory"); }
__device__ __forceinline__ void pdl_wait() { asm volatile("griddepcontrol.wait;" ::: "memory"); }
__device__ __forceinline__ void wg_fence() { asm volatile("wgmma.fence.sync.aligned;" ::: "memory"); }
__device__ __forceinline__ void wg_commit() { asm volatile("wgmma.commit_group.sync.aligned;" ::: "memory"); }
template <int N>
__device__ __forceinline__ void wg_wait() {
  asm volatile("wgmma.wait_group.sync.aligned %0;" ::"n"(N) : "memory");
}
template <int M>
__device__ __forceinline__ void fence_regs(float (&r)[M]) {
#pragma unroll
  for (int i = 0; i < M; i++) asm volatile("" : "+f"(r[i])::"memory");
}
__device__ __forceinline__ uint64_t mkdesc(uint32_t addr, uint32_t lbo, uint32_t sbo, uint32_t layout) {
  return (uint64_t)((addr & 0x3FFFF) >> 4) | ((uint64_t)(lbo >> 4) << 16) | ((uint64_t)(sbo >> 4) << 32) |
         ((uint64_t)layout << 62);
}
__device__ __forceinline__ uint32_t pack_bf16(float lo, float hi) {
  uint32_t r;
  asm("cvt.rn.bf16x2.f32 %0, %1, %2;" : "=r"(r) : "f"(hi), "f"(lo));
  return r;
}
__device__ __forceinline__ float bf_lo(uint32_t v) { return __uint_as_float(v << 16); }
__device__ __forceinline__ float bf_hi(uint32_t v) { return __uint_as_float(v & 0xFFFF0000u); }
__device__ __forceinline__ float round_bf16(float x) { return bf_lo(pack_bf16(x, 0.f)); }
__device__ __forceinline__ float ex2f(float x) {
  float y;
  asm("ex2.approx.ftz.f32 %0, %1;" : "=f"(y) : "f"(x));
  return y;
}

__device__ __forceinline__ void wgmma_rs_n24_tb(float (&d)[12], uint32_t a0, uint32_t a1, uint32_t a2, uint32_t a3, uint64_t descB, int scaleD) {
  asm volatile("{\n.reg .pred p;\nsetp.ne.b32 p, %17, 0;\n"
    "wgmma.mma_async.sync.aligned.m64n24k16.f32.bf16.bf16 "
    "{%0, %1, %2, %3, %4, %5, %6, %7, %8, %9, %10, %11}, {%12, %13, %14, %15}, %16, p, 1, 1, 1;\n}\n"
    : "+f"(d[0]), "+f"(d[1]), "+f"(d[2]), "+f"(d[3]), "+f"(d[4]), "+f"(d[5]), "+f"(d[6]), "+f"(d[7]),
      "+f"(d[8]), "+f"(d[9]), "+f"(d[10]), "+f"(d[11])
    : "r"(a0), "r"(a1), "r"(a2), "r"(a3), "l"(descB), "r"(scaleD));
}
__device__ __forceinline__ void wgmma_rs_n64_z(float (&d)[32], uint32_t a0, uint32_t a1, uint32_t a2, uint32_t a3, uint64_t descB) {
  asm volatile("{\n.reg .pred p;\nsetp.ne.b32 p, %37, 0;\n"
    "wgmma.mma_async.sync.aligned.m64n64k16.f32.bf16.bf16 "
    "{%0, %1, %2, %3, %4, %5, %6, %7, %8, %9, %10, %11, %12, %13, %14, %15, %16, %17, %18, %19, %20, %21, %22, %23, %24, %25, %26, %27, %28, %29, %30, %31}, {%32, %33, %34, %35}, %36, p, 1, 1, 0;\n}\n"
    : "=f"(d[0]), "=f"(d[1]), "=f"(d[2]), "=f"(d[3]), "=f"(d[4]), "=f"(d[5]), "=f"(d[6]), "=f"(d[7]),
      "=f"(d[8]), "=f"(d[9]), "=f"(d[10]), "=f"(d[11]), "=f"(d[12]), "=f"(d[13]), "=f"(d[14]), "=f"(d[15]),
      "=f"(d[16]), "=f"(d[17]), "=f"(d[18]), "=f"(d[19]), "=f"(d[20]), "=f"(d[21]), "=f"(d[22]), "=f"(d[23]),
      "=f"(d[24]), "=f"(d[25]), "=f"(d[26]), "=f"(d[27]), "=f"(d[28]), "=f"(d[29]), "=f"(d[30]), "=f"(d[31])
    : "r"(a0), "r"(a1), "r"(a2), "r"(a3), "l"(descB), "n"(0));
}
__device__ __forceinline__ void wgmma_ss_n128_tb(float (&d)[64], uint64_t descA, uint64_t descB, int scaleD) {
  asm volatile("{\n.reg .pred p;\nsetp.ne.b32 p, %66, 0;\n"
    "wgmma.mma_async.sync.aligned.m64n128k16.f32.bf16.bf16 "
    "{%0, %1, %2, %3, %4, %5, %6, %7, %8, %9, %10, %11, %12, %13, %14, %15, %16, %17, %18, %19, %20, %21, %22, %23, %24, %25, %26, %27, %28, %29, %30, %31, %32, %33, %34, %35, %36, %37, %38, %39, %40, %41, %42, %43, %44, %45, %46, %47, %48, %49, %50, %51, %52, %53, %54, %55, %56, %57, %58, %59, %60, %61, %62, %63}, %64, %65, p, 1, 1, 0, 1;\n}\n"
    : "+f"(d[0]), "+f"(d[1]), "+f"(d[2]), "+f"(d[3]), "+f"(d[4]), "+f"(d[5]), "+f"(d[6]), "+f"(d[7]),
      "+f"(d[8]), "+f"(d[9]), "+f"(d[10]), "+f"(d[11]), "+f"(d[12]), "+f"(d[13]), "+f"(d[14]), "+f"(d[15]),
      "+f"(d[16]), "+f"(d[17]), "+f"(d[18]), "+f"(d[19]), "+f"(d[20]), "+f"(d[21]), "+f"(d[22]), "+f"(d[23]),
      "+f"(d[24]), "+f"(d[25]), "+f"(d[26]), "+f"(d[27]), "+f"(d[28]), "+f"(d[29]), "+f"(d[30]), "+f"(d[31]),
      "+f"(d[32]), "+f"(d[33]), "+f"(d[34]), "+f"(d[35]), "+f"(d[36]), "+f"(d[37]), "+f"(d[38]), "+f"(d[39]),
      "+f"(d[40]), "+f"(d[41]), "+f"(d[42]), "+f"(d[43]), "+f"(d[44]), "+f"(d[45]), "+f"(d[46]), "+f"(d[47]),
      "+f"(d[48]), "+f"(d[49]), "+f"(d[50]), "+f"(d[51]), "+f"(d[52]), "+f"(d[53]), "+f"(d[54]), "+f"(d[55]),
      "+f"(d[56]), "+f"(d[57]), "+f"(d[58]), "+f"(d[59]), "+f"(d[60]), "+f"(d[61]), "+f"(d[62]), "+f"(d[63])
    : "l"(descA), "l"(descB), "r"(scaleD));
}
__device__ __forceinline__ void wgmma_ss_n192_tb(float (&d)[96], uint64_t descA, uint64_t descB, int scaleD) {
  asm volatile("{\n.reg .pred p;\nsetp.ne.b32 p, %98, 0;\n"
    "wgmma.mma_async.sync.aligned.m64n192k16.f32.bf16.bf16 "
    "{%0, %1, %2, %3, %4, %5, %6, %7, %8, %9, %10, %11, %12, %13, %14, %15, %16, %17, %18, %19, %20, %21, %22, %23, %24, %25, %26, %27, %28, %29, %30, %31, %32, %33, %34, %35, %36, %37, %38, %39, %40, %41, %42, %43, %44, %45, %46, %47, %48, %49, %50, %51, %52, %53, %54, %55, %56, %57, %58, %59, %60, %61, %62, %63, %64, %65, %66, %67, %68, %69, %70, %71, %72, %73, %74, %75, %76, %77, %78, %79, %80, %81, %82, %83, %84, %85, %86, %87, %88, %89, %90, %91, %92, %93, %94, %95}, %96, %97, p, 1, 1, 0, 1;\n}\n"
    : "+f"(d[0]), "+f"(d[1]), "+f"(d[2]), "+f"(d[3]), "+f"(d[4]), "+f"(d[5]), "+f"(d[6]), "+f"(d[7]),
      "+f"(d[8]), "+f"(d[9]), "+f"(d[10]), "+f"(d[11]), "+f"(d[12]), "+f"(d[13]), "+f"(d[14]), "+f"(d[15]),
      "+f"(d[16]), "+f"(d[17]), "+f"(d[18]), "+f"(d[19]), "+f"(d[20]), "+f"(d[21]), "+f"(d[22]), "+f"(d[23]),
      "+f"(d[24]), "+f"(d[25]), "+f"(d[26]), "+f"(d[27]), "+f"(d[28]), "+f"(d[29]), "+f"(d[30]), "+f"(d[31]),
      "+f"(d[32]), "+f"(d[33]), "+f"(d[34]), "+f"(d[35]), "+f"(d[36]), "+f"(d[37]), "+f"(d[38]), "+f"(d[39]),
      "+f"(d[40]), "+f"(d[41]), "+f"(d[42]), "+f"(d[43]), "+f"(d[44]), "+f"(d[45]), "+f"(d[46]), "+f"(d[47]),
      "+f"(d[48]), "+f"(d[49]), "+f"(d[50]), "+f"(d[51]), "+f"(d[52]), "+f"(d[53]), "+f"(d[54]), "+f"(d[55]),
      "+f"(d[56]), "+f"(d[57]), "+f"(d[58]), "+f"(d[59]), "+f"(d[60]), "+f"(d[61]), "+f"(d[62]), "+f"(d[63]),
      "+f"(d[64]), "+f"(d[65]), "+f"(d[66]), "+f"(d[67]), "+f"(d[68]), "+f"(d[69]), "+f"(d[70]), "+f"(d[71]),
      "+f"(d[72]), "+f"(d[73]), "+f"(d[74]), "+f"(d[75]), "+f"(d[76]), "+f"(d[77]), "+f"(d[78]), "+f"(d[79]),
      "+f"(d[80]), "+f"(d[81]), "+f"(d[82]), "+f"(d[83]), "+f"(d[84]), "+f"(d[85]), "+f"(d[86]), "+f"(d[87]),
      "+f"(d[88]), "+f"(d[89]), "+f"(d[90]), "+f"(d[91]), "+f"(d[92]), "+f"(d[93]), "+f"(d[94]), "+f"(d[95])
    : "l"(descA), "l"(descB), "r"(scaleD));
}

__device__ __forceinline__ void ldsm4t(uint32_t (&b)[4], uint32_t addr) {
  asm volatile("ldmatrix.sync.aligned.m8n8.x4.trans.shared.b16 {%0,%1,%2,%3}, [%4];"
               : "=r"(b[0]), "=r"(b[1]), "=r"(b[2]), "=r"(b[3])
               : "r"(addr));
}
__device__ __forceinline__ void hmma(float (&c)[4], uint32_t a0, uint32_t a1, uint32_t a2, uint32_t a3, uint32_t b0, uint32_t b1) {
  asm("mma.sync.aligned.m16n8k16.row.col.f32.bf16.bf16.f32 {%0,%1,%2,%3}, {%4,%5,%6,%7}, {%8,%9}, {%0,%1,%2,%3};"
      : "+f"(c[0]), "+f"(c[1]), "+f"(c[2]), "+f"(c[3])
      : "r"(a0), "r"(a1), "r"(a2), "r"(a3), "r"(b0), "r"(b1));
}

__device__ __forceinline__ uint32_t movm(uint32_t a) {
  uint32_t d;
  asm volatile("movmatrix.sync.aligned.m8n8.trans.b16 %0, %1;" : "=r"(d) : "r"(a));
  return d;
}

constexpr int K1_STAGES = 4;
constexpr int K1_W_BYTES = 3 * 8192;
constexpr int K1_X_BYTES = 8 * 16384;
constexpr int K1_BAR_OFF = K1_X_BYTES + K1_STAGES * K1_W_BYTES;
constexpr int K1_SMEM = K1_BAR_OFF + 192 + 1024;
constexpr float QSCALE = 0.25f * 1.4426950408889634f;

__device__ __forceinline__ uint32_t phi2(uint32_t t2) {
  uint32_t a2, mask, r2, o2;
  asm("add.rn.bf16x2 %0, %1, %2;" : "=r"(a2) : "r"(t2), "r"(0x3F803F80u));
  const uint32_t e2 = pack_bf16(ex2f(bf_lo(t2) * 1.4426950408889634f), ex2f(bf_hi(t2) * 1.4426950408889634f));
  asm("set.gt.u32.bf16x2 %0, %1, %2;" : "=r"(mask) : "r"(t2), "r"(0u));
  r2 = (a2 & mask) | (e2 & ~mask);
  asm("add.rn.bf16x2 %0, %1, %2;" : "=r"(o2) : "r"(r2), "r"(0x35863586u));
  return o2;
}

#define K1_SLOT_KB(h) ((h) < 4 ? 2 * (h) : 2 * ((h) - 4) + 1)
struct EpiCtx {
  uint4* qf;
  uint32_t* kp;
  uint32_t* vp;
  uint32_t* s_red;
  float* red;
  int lane;
};

template <bool LINEAR, int J, int HH, int PART>
__device__ __forceinline__ void epi_slice(const float (&acc)[96], const EpiCtx& c, uint32_t (&pk)[4], float& vmax) {
  constexpr int h = J * 4 + HH;
  const float* a = &acc[HH * 8];
  const float* k = &acc[32 + HH * 8];
  const float* v = &acc[64 + HH * 8];
  if (!LINEAR) {
    if (PART == 0) {
      c.qf[h * 32 * 128] = make_uint4(pack_bf16(a[0] * QSCALE, a[1] * QSCALE), pack_bf16(a[2] * QSCALE, a[3] * QSCALE),
                                      pack_bf16(a[4] * QSCALE, a[5] * QSCALE), pack_bf16(a[6] * QSCALE, a[7] * QSCALE));
      uint32_t* kh = c.kp + h * (KV_HEAD_BYTES / 4);
      kh[0] = pack_bf16(k[0], k[1]);
      kh[64] = pack_bf16(k[2], k[3]);
      kh[32] = pack_bf16(k[4], k[5]);
      kh[96] = pack_bf16(k[6], k[7]);
      float q0 = a[0] * a[0] + a[1] * a[1] + a[4] * a[4] + a[5] * a[5];
      float q1 = a[2] * a[2] + a[3] * a[3] + a[6] * a[6] + a[7] * a[7];
      float k0 = k[0] * k[0] + k[1] * k[1] + k[4] * k[4] + k[5] * k[5];
      float k1 = k[2] * k[2] + k[3] * k[3] + k[6] * k[6] + k[7] * k[7];
#pragma unroll
      for (int o = 1; o <= 2; o <<= 1) {
        q0 += __shfl_xor_sync(0xffffffffu, q0, o);
        q1 += __shfl_xor_sync(0xffffffffu, q1, o);
        k0 += __shfl_xor_sync(0xffffffffu, k0, o);
        k1 += __shfl_xor_sync(0xffffffffu, k1, o);
      }
      const uint32_t qm = __reduce_max_sync(0xffffffffu, max(__float_as_uint(q0) & 0x7FFFFFFFu, __float_as_uint(q1) & 0x7FFFFFFFu));
      const uint32_t km = __reduce_max_sync(0xffffffffu, max(__float_as_uint(k0) & 0x7FFFFFFFu, __float_as_uint(k1) & 0x7FFFFFFFu));
      if (c.lane == 0) {
        atomicMax(&c.s_red[h * 2 + 0], qm);
        atomicMax(&c.s_red[h * 2 + 1], km);
      }
    } else {
      uint32_t* vh = c.vp + h * (KV_HEAD_BYTES / 4);
      vh[0] = pack_bf16(v[0], v[1]);
      vh[96] = pack_bf16(v[2], v[3]);
      vh[32] = pack_bf16(v[4], v[5]);
      vh[128] = pack_bf16(v[6], v[7]);
      vh[64] = 0x3F803F80u;
      vh[160] = 0x3F803F80u;
#pragma unroll
      for (int i = 0; i < 8; i++) asm("max.NaN.f32 %0, %0, %1;" : "+f"(vmax) : "f"(fabsf(v[i])));
    }
  } else {
    if (PART == 0) {
      c.qf[h * 32 * 128] = make_uint4(phi2(pack_bf16(a[0], a[1])), phi2(pack_bf16(a[2], a[3])), phi2(pack_bf16(a[4], a[5])),
                                      phi2(pack_bf16(a[6], a[7])));
      pk[0] = movm(phi2(pack_bf16(k[0], k[1])));
      pk[2] = movm(phi2(pack_bf16(k[2], k[3])));
      pk[1] = movm(phi2(pack_bf16(k[4], k[5])));
      pk[3] = movm(phi2(pack_bf16(k[6], k[7])));
    } else {
      const uint32_t b0 = movm(pack_bf16(v[0], v[1]));
      const uint32_t b1 = movm(pack_bf16(v[2], v[3]));
      const uint32_t b2 = movm(pack_bf16(v[4], v[5]));
      const uint32_t b3 = movm(pack_bf16(v[6], v[7]));
      float c0[4] = {0, 0, 0, 0}, c1[4] = {0, 0, 0, 0}, c2[4] = {0, 0, 0, 0};
      hmma(c0, pk[0], pk[1], pk[2], pk[3], b0, b1);
      hmma(c1, pk[0], pk[1], pk[2], pk[3], b2, b3);
      hmma(c2, pk[0], pk[1], pk[2], pk[3], 0x3F803F80u, 0x3F803F80u);
      float* slot = c.red + K1_SLOT_KB(h) * 4096;
#pragma unroll
      for (int i = 0; i < 4; i++) {
        slot[i * 32] = c0[i];
        slot[(4 + i) * 32] = c1[i];
        slot[(8 + i) * 32] = c2[i];
      }
    }
  }
}

template <bool LINEAR>
__device__ __forceinline__ void qkv_consumer(uint32_t sbase, uint8_t* smem_gen, uint32_t* s_red, int cp, int rt) {
  const uint32_t bar_full = sbase + K1_BAR_OFF;
  const uint32_t bar_empty = bar_full + 8 * K1_STAGES;
  const int warp = threadIdx.x >> 5;
  const int wg = warp >> 2;
  const int lane = threadIdx.x & 31;
  float acc0[96], acc1[96];
#pragma unroll 1
  for (int kb = 0; kb < 8; kb++) {
    const int s = kb % K1_STAGES;
    mbar_wait(bar_full + 8 * s, (kb / K1_STAGES) & 1);
    if (threadIdx.x == 0) PROF_T(0, 2 + (kb >> 1));
    const uint64_t dA = mkdesc(sbase + kb * 16384 + wg * 8192, 16, 1024, 1);
    const uint64_t dB = mkdesc(sbase + K1_X_BYTES + s * K1_W_BYTES, 8192, 1024, 1);
    wg_fence();
#pragma unroll
    for (int k = 0; k < 4; k++) wgmma_ss_n192_tb(acc0, dA + k * 2, dB + k * 128, (kb | k) != 0);
    wg_commit();
    if (kb > 0) {
      wg_wait<1>();
      if ((threadIdx.x & 127) == 0) {
        const int sp = (kb - 1) % K1_STAGES;
        mbar_arrive_cluster(bar_empty + 8 * sp, 0);
        mbar_arrive_cluster(bar_empty + 8 * sp, 1);
      }
    }
  }
  wg_wait<0>();
  fence_regs(acc0);
  if ((threadIdx.x & 127) == 0) {
    mbar_arrive_cluster(bar_empty + 8 * (7 % K1_STAGES), 0);
    mbar_arrive_cluster(bar_empty + 8 * (7 % K1_STAGES), 1);
  }
  if (threadIdx.x == 0) PROF_T(0, 6);

  EpiCtx c;
  {
    const int row0 = rt * 128 + wg * 64 + (warp & 3) * 16;
    c.qf = g_qfrag + ((size_t)((LINEAR ? NH : 0) + cp * 8) * 32 + (rt * 2 + wg)) * 128 + (threadIdx.x & 127);
    uint32_t* img = reinterpret_cast<uint32_t*>(reinterpret_cast<uint8_t*>(g_kv) + (size_t)(cp * 8) * KV_HEAD_BYTES);
    c.kp = img + (row0 >> 3) * 64 + lane;
    c.vp = img + KV_K_BYTES / 4 + (row0 >> 3) * 96 + lane;
    c.s_red = s_red;
    c.red = reinterpret_cast<float*>(smem_gen + wg * 8192) + (warp & 3) * 384 + lane;
    c.lane = lane;
  }
  uint32_t pk[4];
  float vmax = 0.f;
#define K1_T1_STEP(KB)                                                                           \
  {                                                                                              \
    constexpr int g = 8 + KB;                                                                    \
    constexpr int s = g % K1_STAGES;                                                             \
    mbar_wait(bar_full + 8 * s, (g / K1_STAGES) & 1);                                            \
    const uint64_t dA = mkdesc(sbase + KB * 16384 + wg * 8192, 16, 1024, 1);                     \
    const uint64_t dB = mkdesc(sbase + K1_X_BYTES + s * K1_W_BYTES, 8192, 1024, 1);              \
    wg_fence();                                                                                  \
    _Pragma("unroll") for (int k = 0; k < 4; k++) wgmma_ss_n192_tb(acc1, dA + k * 2, dB + k * 128, (KB | k) != 0); \
    wg_commit();                                                                                 \
    epi_slice<LINEAR, 0, KB / 2, KB & 1>(acc0, c, pk, vmax);                                     \
    wg_wait<0>();                                                                                \
    if (KB + K1_STAGES < 8 && (threadIdx.x & 127) == 0) {                                        \
      mbar_arrive_cluster(bar_empty + 8 * s, 0);                                                 \
      mbar_arrive_cluster(bar_empty + 8 * s, 1);                                                 \
    }                                                                                            \
  }
  K1_T1_STEP(0) K1_T1_STEP(1) K1_T1_STEP(2) K1_T1_STEP(3) K1_T1_STEP(4) K1_T1_STEP(5) K1_T1_STEP(6) K1_T1_STEP(7)
#undef K1_T1_STEP
  fence_regs(acc1);
  if (threadIdx.x == 0) PROF_T(0, 10);
  epi_slice<LINEAR, 1, 0, 0>(acc1, c, pk, vmax);
  epi_slice<LINEAR, 1, 0, 1>(acc1, c, pk, vmax);
  epi_slice<LINEAR, 1, 1, 0>(acc1, c, pk, vmax);
  epi_slice<LINEAR, 1, 1, 1>(acc1, c, pk, vmax);
  epi_slice<LINEAR, 1, 2, 0>(acc1, c, pk, vmax);
  epi_slice<LINEAR, 1, 2, 1>(acc1, c, pk, vmax);
  epi_slice<LINEAR, 1, 3, 0>(acc1, c, pk, vmax);
  epi_slice<LINEAR, 1, 3, 1>(acc1, c, pk, vmax);
  if (!LINEAR) {
    const uint32_t vm = __reduce_max_sync(0xffffffffu, __float_as_uint(vmax) & 0x7FFFFFFFu);
    if (lane == 0) atomicMax(&s_red[16], vm);
    asm volatile("bar.sync 1, 256;" ::: "memory");
    if (threadIdx.x < 8) {
      *reinterpret_cast<float4*>(&g_nrm[((cp * 8 + threadIdx.x) * 16 + rt) * 4]) =
          make_float4(__uint_as_float(s_red[threadIdx.x * 2]), __uint_as_float(s_red[threadIdx.x * 2 + 1]), __uint_as_float(s_red[16]), 0.f);
    }
  } else {
    asm volatile("bar.sync 1, 256;" ::: "memory");
    float* dst = g_kvpart + ((size_t)rt * NH + cp * 8) * 384;
#pragma unroll
    for (int i = 0; i < 12; i++) {
      const int o = threadIdx.x + i * 256;
      const int h = o / 384, e = o - h * 384;
      const float* src = reinterpret_cast<const float*>(smem_gen) + K1_SLOT_KB(h) * 4096 + e;
      float sum = 0.f;
#pragma unroll
      for (int w = 0; w < 8; w++) sum += src[(w >> 2) * 2048 + (w & 3) * 384];
      dst[o] = sum;
    }
  }
}

__global__ void __launch_bounds__(384, 1)
qkv_gemm_kernel(const __grid_constant__ CUtensorMap mxA, const __grid_constant__ CUtensorMap mxB,
                const __grid_constant__ CUtensorMap mwA, const __grid_constant__ CUtensorMap mwB) {
  extern __shared__ uint8_t smem_raw[];
  const uint32_t sbase = (smem_u32(smem_raw) + 1023) & ~1023u;
  uint8_t* smem_gen = smem_raw + (sbase - smem_u32(smem_raw));
  const uint32_t bar_full = sbase + K1_BAR_OFF;
  const uint32_t bar_empty = bar_full + 8 * K1_STAGES;
  uint32_t* s_red = reinterpret_cast<uint32_t*>(smem_gen + K1_BAR_OFF + 64);

  const int rank = blockIdx.x & 1;
  const int pair = blockIdx.x >> 1;
  const int branch = pair >> 5;
  const int rp = (pair & 31) >> 2;
  const int cp = pair & 3;
  const int rt = rp * 2 + rank;
  const int warp = threadIdx.x >> 5;
  if (threadIdx.x == 0) { PROF_G(0, 30); PROF_T(0, 0); }
  const CUtensorMap* mx = branch ? &mxA : &mxB;
  const CUtensorMap* mw = branch ? &mwA : &mwB;

  if (threadIdx.x == 256) {
    asm volatile("prefetch.tensormap [%0];" ::"l"(mx) : "memory");
    asm volatile("prefetch.tensormap [%0];" ::"l"(mw) : "memory");
    for (int i = 0; i < K1_STAGES; i++) {
      mbar_init(bar_full + 8 * i, 1);
      mbar_init(bar_empty + 8 * i, 4);
    }
    fence_barrier_init();
    fence_proxy_async();
    for (int kb = 0; kb < K1_STAGES; kb++) mbar_expect_tx(bar_full + 8 * kb, 16384 + K1_W_BYTES);
    tma_load_2d(sbase, mx, 0, rt * 128, bar_full);
  }
  pdl_launch_dependents();
  if (threadIdx.x < 32) s_red[threadIdx.x] = 0;
  __syncthreads();
  cluster_sync_relaxed();
  if (threadIdx.x == 0) PROF_T(0, 1);

  if (warp >= 8) {
    asm volatile("setmaxnreg.dec.sync.aligned.u32 40;");
    if (threadIdx.x == 256) {
      for (int g = 0; g < 16; g++) {
        const int s = g % K1_STAGES;
        const int kb = g & 7;
        if (g >= K1_STAGES) {
          mbar_wait(bar_empty + 8 * s, ((g / K1_STAGES) - 1) & 1);
          mbar_expect_tx(bar_full + 8 * s, (g < 8 ? 16384 : 0) + K1_W_BYTES);
        }
        if (g > 0 && g < 8) tma_load_2d(sbase + kb * 16384, mx, kb * 64, rt * 128, bar_full + 8 * s);
        const int h0 = cp * 8 + (g >> 3) * 4;
        const uint32_t st = sbase + K1_X_BYTES + s * K1_W_BYTES + rank * 4096;
#pragma unroll
        for (int p = 0; p < 3; p++)
          tma_load_2d_mc(st + p * 8192, mw, p * 512 + h0 * 16, kb * 64 + rank * 32, bar_full + 8 * s, (uint16_t)3);
      }
    }
    __syncwarp();
    cluster_sync_relaxed();
  } else {
    asm volatile("setmaxnreg.inc.sync.aligned.u32 232;");
    if (branch == 0) qkv_consumer<false>(sbase, smem_gen, s_red, cp, rt);
    else qkv_consumer<true>(sbase, smem_gen, s_red, cp, rt);
    if (threadIdx.x == 0) PROF_T(0, 11);
    __syncwarp();
    cluster_sync_relaxed();
    if (threadIdx.x == 0) { PROF_T(0, 12); PROF_G(0, 31); }
  }
}

constexpr int K2_SMEM = KV_HEAD_BYTES + 1024 + 256;

#define ATT_NPOLY 18
#define ATT_CH 8
#define ATT_D 1
#define ATT_GM 1
#define ATT_DEG 2
struct ExpC {
  uint32_t k3c00, kmask, seven, c3;
};
__device__ __forceinline__ uint32_t hfma2(uint32_t a, uint32_t b, uint32_t c) {
  uint32_t r;
  asm("fma.rn.f16x2 %0, %1, %2, %3;" : "=r"(r) : "r"(a), "r"(b), "r"(c));
  return r;
}
__device__ __forceinline__ uint32_t exp2_poly_pair(float t0, float t1, const ExpC& c) {
  uint32_t u;
  asm("prmt.b32 %0, %1, %2, 0x5410;" : "=r"(u) : "r"(__float_as_uint(t0)), "r"(__float_as_uint(t1)));
  uint32_t m;
  asm("lop3.b32 %0, %1, 0x03FF03FF, %2, 0xEA;" : "=r"(m) : "r"(u), "r"(c.k3c00));
  uint32_t p = hfma2(m, c.c3, 0xa385a385u);
  p = hfma2(p, m, 0x4ad64ad7u);
  uint32_t mu;
  asm("lop3.b32 %0, %1, 0xFC00FC00, %2, 0xEA;" : "=r"(mu) : "r"(u), "r"(c.kmask));
  uint32_t r;
  asm("{.reg .b32 t; shf.r.wrap.b32 t, %1, %2, 3; add.u32 %0, t, %3;}" : "=r"(r) : "r"(mu), "r"(c.seven), "r"(p));
  return r;
}
__device__ __forceinline__ float gadd(float x, float M, uint32_t g) {
  float r = x;
  asm("{.reg .pred p; setp.ne.b32 p, %2, -1; @p add.f32 %0, %0, %1;}" : "+f"(r) : "f"(M), "r"(g));
  return r;
}
__device__ __forceinline__ float gex2(float x, uint32_t g) {
  float r = x;
  asm("{.reg .pred p; setp.ne.b32 p, %1, -1; @p ex2.approx.ftz.f32 %0, %0;}" : "+f"(r) : "r"(g));
  return r;
}
template <int NPOLY, int NPAIR, int CH, int D>
__device__ __forceinline__ void exp_tile(const float (&s)[2 * NPAIR], uint32_t (&p)[NPAIR], const ExpC& c) {
#pragma unroll
  for (int i = 0; i < NPAIR; i++) {
    const bool isPoly = ((i + 1) * NPOLY / 32) != (i * NPOLY / 32);
    const int ch = i / CH;
    const bool gated = ch >= D;
    int gi = (ch - D) * CH + CH - 1;
    if (gated) {
      while (gi > (ch - D) * CH && !(((gi + 1) * NPOLY / 32) != (gi * NPOLY / 32))) gi--;
    }
    const uint32_t g = gated ? p[gi] : 0;
    if (!isPoly) {
      if (gated && ATT_GM) p[i] = pack_bf16(gex2(s[2 * i], g), gex2(s[2 * i + 1], g));
      else p[i] = pack_bf16(ex2f(s[2 * i]), ex2f(s[2 * i + 1]));
    } else {
      if (gated) p[i] = exp2_poly_pair(gadd(s[2 * i], 12329.f, g), gadd(s[2 * i + 1], 12329.f, g), c);
      else p[i] = exp2_poly_pair(s[2 * i] + 12329.f, s[2 * i + 1] + 12329.f, c);
    }
  }
}

__device__ __forceinline__ void store_o(__nv_bfloat16* o, int row0, int head, int lane, const uint32_t (&r)[4]) {
  const int g = lane >> 2, t = lane & 3;
  uint32_t* p0 = reinterpret_cast<uint32_t*>(o + (size_t)(row0 + g) * DM + head * 16) + t;
  uint32_t* p1 = reinterpret_cast<uint32_t*>(o + (size_t)(row0 + g + 8) * DM + head * 16) + t;
  p0[0] = r[0];
  p1[0] = r[1];
  p0[4] = r[2];
  p1[4] = r[3];
}

__device__ __forceinline__ void safe_exp(const float (&s)[32], uint32_t (&p)[16], float (&o)[12], float& m0, float& m1) {
  float x0 = s[0], x1 = s[2];
#pragma unroll
  for (int i = 0; i < 8; i++) {
    x0 = fmaxf(x0, fmaxf(s[4 * i], s[4 * i + 1]));
    x1 = fmaxf(x1, fmaxf(s[4 * i + 2], s[4 * i + 3]));
  }
  x0 = fmaxf(x0, __shfl_xor_sync(0xffffffffu, x0, 1));
  x1 = fmaxf(x1, __shfl_xor_sync(0xffffffffu, x1, 1));
  x0 = fmaxf(x0, __shfl_xor_sync(0xffffffffu, x0, 2));
  x1 = fmaxf(x1, __shfl_xor_sync(0xffffffffu, x1, 2));
  const float n0 = fmaxf(m0, x0), n1 = fmaxf(m1, x1);
  const float c0 = ex2f(m0 - n0), c1 = ex2f(m1 - n1);
  m0 = n0;
  m1 = n1;
#pragma unroll
  for (int i = 0; i < 3; i++) {
    o[4 * i] *= c0;
    o[4 * i + 1] *= c0;
    o[4 * i + 2] *= c1;
    o[4 * i + 3] *= c1;
  }
#pragma unroll
  for (int i = 0; i < 8; i++) {
    p[2 * i] = pack_bf16(ex2f(s[4 * i] - n0), ex2f(s[4 * i + 1] - n0));
    p[2 * i + 1] = pack_bf16(ex2f(s[4 * i + 2] - n1), ex2f(s[4 * i + 3] - n1));
  }
}

__device__ __forceinline__ void attn_step(float (&sx)[32], float (&sy)[32], float (&o)[12], const uint4& qf, uint64_t dK, uint64_t dV,
                                          const ExpC& ec) {
  uint32_t pa[16], pb[16];
  wg_fence();
  wgmma_rs_n64_z(sy, qf.x, qf.y, qf.z, qf.w, dK + 128);
  wg_commit();
  exp_tile<ATT_NPOLY, 16, ATT_CH, ATT_D>(sx, pa, ec);
  wg_fence();
  wgmma_rs_n24_tb(o, pa[12], pa[13], pa[14], pa[15], dV + 3 * 48, 1);
  wg_commit();
  wg_wait<1>();
  fence_regs(sy);
  exp_tile<ATT_NPOLY, 16, ATT_CH, ATT_D>(sy, pb, ec);
  wg_fence();
#pragma unroll
  for (int k = 0; k < 3; k++) wgmma_rs_n24_tb(o, pa[4 * k], pa[4 * k + 1], pa[4 * k + 2], pa[4 * k + 3], dV + k * 48, 1);
#pragma unroll
  for (int k = 0; k < 4; k++) wgmma_rs_n24_tb(o, pb[4 * k], pb[4 * k + 1], pb[4 * k + 2], pb[4 * k + 3], dV + (4 + k) * 48, 1);
  wgmma_rs_n64_z(sy, qf.x, qf.y, qf.z, qf.w, dK + 256);
  wg_commit();
  wg_wait<0>();
  fence_regs(sy);
}

template <bool SAFE>
__device__ __forceinline__ void attn_tile(uint64_t dK, uint64_t dV, uint32_t bar, const uint4 qf, const ExpC& ec, uint32_t (&outp)[4]) {
  float o[12];
#pragma unroll
  for (int i = 0; i < 12; i++) asm volatile("mov.f32 %0, 0f00000000;" : "=f"(o[i]));
  mbar_wait(bar, 0);
  if (!SAFE) {
    float s0[32], s1[32];
    wg_fence();
    wgmma_rs_n64_z(s0, qf.x, qf.y, qf.z, qf.w, dK);
    wg_commit();
    wg_wait<0>();
    fence_regs(s0);
#pragma unroll 1
    for (int p = 0; p < 8; p++) {
      if (p & 1) mbar_wait(bar + 8 * min((p + 1) >> 1, 3), 0);
      attn_step(s0, s1, o, qf, dK, dV, ec);
      attn_step(s1, s0, o, qf, dK + 256, dV + 384, ec);
      dK += 512;
      dV += 768;
    }
  } else {
    float m0 = -INFINITY, m1 = -INFINITY;
#pragma unroll 1
    for (int j = 0; j < 32; j++) {
      if (j == 4) { mbar_wait(bar + 8, 0); mbar_wait(bar + 16, 0); mbar_wait(bar + 24, 0); }
      float s[32];
      uint32_t p[16];
      wg_fence();
      wgmma_rs_n64_z(s, qf.x, qf.y, qf.z, qf.w, dK);
      wg_commit();
      wg_wait<0>();
      fence_regs(s);
      safe_exp(s, p, o, m0, m1);
      wg_fence();
#pragma unroll
      for (int k = 0; k < 4; k++) wgmma_rs_n24_tb(o, p[4 * k], p[4 * k + 1], p[4 * k + 2], p[4 * k + 3], dV + k * 48, 1);
      wg_commit();
      wg_wait<0>();
      fence_regs(o);
      dK += 128;
      dV += 192;
    }
  }
  fence_regs(o);
  const float r0 = 1.0f / o[8], r1 = 1.0f / o[10];
  outp[0] = pack_bf16(o[0] * r0, o[1] * r0);
  outp[1] = pack_bf16(o[2] * r1, o[3] * r1);
  outp[2] = pack_bf16(o[4] * r0, o[5] * r0);
  outp[3] = pack_bf16(o[6] * r1, o[7] * r1);
}

__device__ __forceinline__ void linear_attn_cta(uint8_t* smem_raw, uint32_t sbase, const CUtensorMap* mo16, int cta) {
  const int warp = threadIdx.x >> 5, lane = threadIdx.x & 31;
  float* red = reinterpret_cast<float*>(smem_raw + (sbase - smem_u32(smem_raw)) + 131072);
  {
    const float* src = g_kvpart + (size_t)cta * 8 * 384;
    float sum[6];
#pragma unroll
    for (int i = 0; i < 6; i++) sum[i] = 0.f;
#pragma unroll
    for (int r = 0; r < 16; r++) {
#pragma unroll
      for (int i = 0; i < 6; i++) sum[i] += src[(size_t)r * NH * 384 + threadIdx.x + i * 512];
    }
#pragma unroll
    for (int i = 0; i < 6; i++) red[threadIdx.x + i * 512] = round_bf16(sum[i]);
  }
  __syncthreads();
  uint32_t bf[8][6];
  {
    const int g = lane >> 2, t = lane & 3;
#pragma unroll
    for (int h = 0; h < 8; h++) {
#pragma unroll
      for (int f = 0; f < 6; f++) {
        const int blk = f >> 1, half = f & 1;
        const int e = (blk == 2) ? 0 : g;
        const int d = 2 * t + 8 * half;
        const int base = h * 384 + (blk * 4 + half * 2 + (e & 1)) * 32 + (e >> 1);
        bf[h][f] = pack_bf16(red[base + (d & 7) * 4], red[base + ((d + 1) & 7) * 4]);
      }
    }
  }
  const uint32_t stg = sbase + warp * 8192;
#pragma unroll 1
  for (int rb = 0; rb < 8; rb++) {
    const int blk16 = rb * 16 + warp;
    const uint4* qp = g_qfrag + ((size_t)(NH + cta * 8) * 32 + (blk16 >> 2)) * 128 + (blk16 & 3) * 32 + lane;
    uint4 q[8];
#pragma unroll
    for (int h = 0; h < 8; h++) q[h] = qp[h * 32 * 128];
    const uint32_t buf = stg + (rb & 1) * 4096;
    if (rb >= 2) {
      if (lane == 0) asm volatile("cp.async.bulk.wait_group.read 1;" ::: "memory");
      __syncwarp();
    }
#pragma unroll
    for (int h = 0; h < 8; h++) {
      float n0[4] = {0, 0, 0, 0}, n1[4] = {0, 0, 0, 0}, dn[4] = {0, 0, 0, 0};
      hmma(n0, q[h].x, q[h].y, q[h].z, q[h].w, bf[h][0], bf[h][1]);
      hmma(n1, q[h].x, q[h].y, q[h].z, q[h].w, bf[h][2], bf[h][3]);
      hmma(dn, q[h].x, q[h].y, q[h].z, q[h].w, bf[h][4], bf[h][5]);
      const float d0 = round_bf16(round_bf16(dn[0]) + 1e-6f), d1 = round_bf16(round_bf16(dn[2]) + 1e-6f);
      const uint32_t r0 = pack_bf16(__fdividef(round_bf16(n0[0]), d0), __fdividef(round_bf16(n0[1]), d0));
      const uint32_t r1 = pack_bf16(__fdividef(round_bf16(n0[2]), d1), __fdividef(round_bf16(n0[3]), d1));
      const uint32_t r2 = pack_bf16(__fdividef(round_bf16(n1[0]), d0), __fdividef(round_bf16(n1[1]), d0));
      const uint32_t r3 = pack_bf16(__fdividef(round_bf16(n1[2]), d1), __fdividef(round_bf16(n1[3]), d1));
      const int row = lane & 15;
      const int chunk = (h & 3) * 2 + (lane >> 4);
      const uint32_t addr = buf + (h >> 2) * 2048 + row * 128 + ((chunk ^ (row & 7)) << 4);
      asm volatile("stmatrix.sync.aligned.m8n8.x4.shared.b16 [%0], {%1,%2,%3,%4};" ::"r"(addr), "r"(r0), "r"(r1), "r"(r2), "r"(r3)
                   : "memory");
    }
    fence_proxy_async();
    __syncwarp();
    if (lane == 0) {
      tma_store_2d(mo16, buf, cta * 128, blk16 * 16);
      tma_store_2d(mo16, buf + 2048, cta * 128 + 64, blk16 * 16);
      asm volatile("cp.async.bulk.commit_group;" ::: "memory");
    }
  }
  if (lane == 0) asm volatile("cp.async.bulk.wait_group 0;" ::: "memory");
}

__global__ void __launch_bounds__(512, 1) attn_kernel(const __grid_constant__ CUtensorMap mo16) {
  extern __shared__ uint8_t smem_raw[];
  const uint32_t sbase = (smem_u32(smem_raw) + 1023) & ~1023u;
  const uint32_t bar = sbase + KV_HEAD_BYTES;
  if (threadIdx.x == 0) { PROF_G(1, 30); PROF_T(1, 0); }
  if (threadIdx.x == 0) {
    for (int i = 0; i < 4; i++) mbar_init(bar + 8 * i, 1);
    fence_barrier_init();
    fence_proxy_async();
  }
  __syncthreads();
  cluster_sync_relaxed();
  pdl_launch_dependents();
  pdl_wait();
  if (blockIdx.x >= 128) {
    linear_attn_cta(smem_raw, sbase, &mo16, blockIdx.x - 128);
    if (threadIdx.x == 0) { PROF_T(1, 5); PROF_G(1, 31); }
    return;
  }
  const int head = blockIdx.x >> 2, qb = blockIdx.x & 3;
  if (threadIdx.x == 0) {
    const uint8_t* img = reinterpret_cast<const uint8_t*>(g_kv) + (size_t)head * KV_HEAD_BYTES;
    const int half = blockIdx.x & 1;
    const int ke[5] = {0, 320, 832, 1344, 2048};
    const int ve[5] = {0, 256, 768, 1280, 2048};
#pragma unroll
    for (int g = 0; g < 4; g++) {
      const int kb = (ke[g + 1] - ke[g]) * 32, vb = (ve[g + 1] - ve[g]) * 48;
      mbar_expect_tx(bar + 8 * g, kb + vb);
      const int ko = ke[g] * 32 + half * (kb / 2), vo = KV_K_BYTES + ve[g] * 48 + half * (vb / 2);
      bulk_load_mc(sbase + ko, img + ko, kb / 2, bar + 8 * g, (uint16_t)3);
      bulk_load_mc(sbase + vo, img + vo, vb / 2, bar + 8 * g, (uint16_t)3);
    }
  }
  const int lane = threadIdx.x & 31;
  bool safe_path;
  {
    float4 n = make_float4(0.f, 0.f, 0.f, 0.f);
    if (lane < 16) n = *reinterpret_cast<const float4*>(&g_nrm[(head * 16 + lane) * 4]);
    uint32_t qm = ((lane >> 2) == qb) ? __float_as_uint(n.x) : 0u;
    qm = __reduce_max_sync(0xffffffffu, qm);
    const uint32_t km = __reduce_max_sync(0xffffffffu, __float_as_uint(n.y));
    const uint32_t vm = __reduce_max_sync(0xffffffffu, __float_as_uint(n.z));
    const float b2 = __uint_as_float(qm) * (QSCALE * QSCALE) * __uint_as_float(km) * 1.02f;
    const float vmax = __uint_as_float(vm);
    const bool ok = (b2 <= 21.5f * 21.5f) && (vmax <= 1.0e24f) && (vmax >= 1.0e-18f || vmax == 0.f);
    safe_path = !ok;
  }
  const int wg = threadIdx.x >> 7, warp = (threadIdx.x >> 5) & 3;
  uint32_t zero;
  asm volatile("mov.u32 %0, %%smid;" : "=r"(zero));
  zero >>= 16;
  const ExpC ec{0x3C003C00u + zero, 0x00070000u + zero, 7u + zero, (ATT_DEG == 3 ? 0x2cfd2cfdu : 0x35623562u) + zero};
  const uint64_t dK = mkdesc(sbase, 128, 256, 0);
  const uint64_t dV = mkdesc(sbase + KV_K_BYTES, 384, 128, 0);
  uint4 qnext = g_qfrag[(head * 32 + qb * 8 + wg * 2) * 128 + (threadIdx.x & 127)];
#pragma unroll 1
  for (int t = 0; t < 2; t++) {
    const int tile64 = qb * 8 + wg * 2 + t;
    const uint4 qf = qnext;
    if (t == 0) qnext = g_qfrag[(head * 32 + tile64 + 1) * 128 + (threadIdx.x & 127)];
    uint32_t r[4];
    if (threadIdx.x == 0) PROF_T(1, 1 + t);
    if (!safe_path) attn_tile<false>(dK, dV, bar, qf, ec, r);
    else attn_tile<true>(dK, dV, bar, qf, ec, r);
    store_o(g_o + (size_t)S_LEN * DM, tile64 * 64 + warp * 16, head, lane, r);
  }
  if (threadIdx.x == 0) { PROF_T(1, 5); PROF_G(1, 31); }
}

constexpr int K3_STAGES = 5;
constexpr int K3_W_BYTES = 8 * 16384;
constexpr int K3_BAR_OFF = K3_W_BYTES + K3_STAGES * 16384;
constexpr int K3_SMEM = K3_BAR_OFF + 256 + 1024;

__global__ void __launch_bounds__(288, 1)
out_gemm_kernel(const __grid_constant__ CUtensorMap mo, const __grid_constant__ CUtensorMap mwA,
                const __grid_constant__ CUtensorMap mwB, const __grid_constant__ CUtensorMap mout) {
  extern __shared__ uint8_t smem_raw[];
  const uint32_t sbase = (smem_u32(smem_raw) + 1023) & ~1023u;
  const uint32_t bar_full = sbase + K3_BAR_OFF;
  const uint32_t bar_empty = bar_full + 8 * K3_STAGES;
  const uint32_t bar_w = bar_empty + 8 * K3_STAGES;
  const int branch = blockIdx.x >> 6;
  const int rt = (blockIdx.x & 63) >> 2;
  const int ct = blockIdx.x & 3;
  const int warp = threadIdx.x >> 5;
  if (threadIdx.x == 0) { PROF_G(2, 30); PROF_T(2, 0); }
  if (threadIdx.x == 256) {
    const CUtensorMap* mw = branch ? &mwB : &mwA;
    asm volatile("prefetch.tensormap [%0];" ::"l"(mw) : "memory");
    asm volatile("prefetch.tensormap [%0];" ::"l"(&mo) : "memory");
    asm volatile("prefetch.tensormap [%0];" ::"l"(&mout) : "memory");
    for (int i = 0; i < K3_STAGES; i++) {
      mbar_init(bar_full + 8 * i, 1);
      mbar_init(bar_empty + 8 * i, 2);
    }
    for (int i = 0; i < 8; i++) mbar_init(bar_w + 8 * i, 1);
    fence_barrier_init();
    fence_proxy_async();
    for (int kb = 0; kb < 8; kb++) {
      mbar_expect_tx(bar_w + 8 * kb, 16384);
      tma_load_2d(sbase + kb * 16384, mw, ct * 128, kb * 64, bar_w + 8 * kb);
      tma_load_2d(sbase + kb * 16384 + 8192, mw, ct * 128 + 64, kb * 64, bar_w + 8 * kb);
    }
  }
  __syncthreads();
  if (warp == 8) {
    if ((threadIdx.x & 31) == 0) {
      pdl_wait();
      PROF_T(2, 1);
      for (int kb = 0; kb < 8; kb++) {
        const int s = kb % K3_STAGES;
        if (kb >= K3_STAGES) mbar_wait(bar_empty + 8 * s, ((kb / K3_STAGES) - 1) & 1);
        mbar_expect_tx(bar_full + 8 * s, 16384);
        tma_load_2d(sbase + K3_W_BYTES + s * 16384, &mo, kb * 64, branch * S_LEN + rt * 128, bar_full + 8 * s);
      }
    }
  } else {
    const int wg = warp >> 2;
    float acc[64];
    for (int kb = 0; kb < 8; kb++) {
      const int s = kb % K3_STAGES;
      mbar_wait(bar_w + 8 * kb, 0);
      mbar_wait(bar_full + 8 * s, (kb / K3_STAGES) & 1);
      if (threadIdx.x == 0) PROF_T(2, 2 + kb);
      const uint64_t dA = mkdesc(sbase + K3_W_BYTES + s * 16384 + wg * 8192, 16, 1024, 1);
      const uint64_t dB = mkdesc(sbase + kb * 16384, 8192, 1024, 1);
      wg_fence();
#pragma unroll
      for (int k = 0; k < 4; k++) wgmma_ss_n128_tb(acc, dA + k * 2, dB + k * 128, (kb | k) != 0);
      wg_commit();
      if (kb > 0) {
        wg_wait<1>();
        if ((threadIdx.x & 127) == 0) mbar_arrive(bar_empty + 8 * ((kb - 1) % K3_STAGES));
      }
    }
    wg_wait<0>();
    fence_regs(acc);
    if (threadIdx.x == 0) PROF_T(2, 10);
    const uint32_t stg = sbase + K3_W_BYTES + wg * 8192;
    asm volatile("bar.sync 1, 256;" ::: "memory");
    const int lane = threadIdx.x & 31;
    const int rloc = (warp & 3) * 16 + (lane & 15);
#pragma unroll
    for (int c16 = 0; c16 < 8; c16++) {
      const float* a = &acc[c16 * 8];
      const uint32_t r0 = pack_bf16(a[0], a[1]), r1 = pack_bf16(a[2], a[3]), r2 = pack_bf16(a[4], a[5]), r3 = pack_bf16(a[6], a[7]);
      const int chunk = (c16 & 3) * 2 + (lane >> 4);
      const uint32_t addr = stg + (c16 >> 2) * 16384 + rloc * 128 + ((chunk ^ (rloc & 7)) << 4);
      asm volatile("stmatrix.sync.aligned.m8n8.x4.shared.b16 [%0], {%1,%2,%3,%4};" ::"r"(addr), "r"(r0), "r"(r1), "r"(r2), "r"(r3)
                   : "memory");
    }
    fence_proxy_async();
    asm volatile("bar.sync %0, 128;" ::"r"(2 + wg) : "memory");
    if ((threadIdx.x & 127) == 0) {
      tma_store_2d(&mout, stg, branch * DM + ct * 128, rt * 128 + wg * 64);
      tma_store_2d(&mout, stg + 16384, branch * DM + ct * 128 + 64, rt * 128 + wg * 64);
      asm volatile("cp.async.bulk.commit_group;" ::: "memory");
      asm volatile("cp.async.bulk.wait_group.read 0;" ::: "memory");
      if (threadIdx.x == 0) { PROF_T(2, 12); PROF_G(2, 31); }
    }
  }
}

typedef CUresult (*EncodeFn)(CUtensorMap*, CUtensorMapDataType, cuuint32_t, void*, const cuuint64_t*, const cuuint64_t*,
                             const cuuint32_t*, const cuuint32_t*, CUtensorMapInterleave, CUtensorMapSwizzle,
                             CUtensorMapL2promotion, CUtensorMapFloatOOBfill);

void make_map(EncodeFn enc, CUtensorMap* m, const void* ptr, uint64_t inner, uint64_t outer, uint32_t box_inner, uint32_t box_outer) {
  cuuint64_t dims[2] = {inner, outer};
  cuuint64_t strides[1] = {inner * 2};
  cuuint32_t box[2] = {box_inner, box_outer};
  cuuint32_t es[2] = {1, 1};
  enc(m, CU_TENSOR_MAP_DATA_TYPE_BFLOAT16, 2, const_cast<void*>(ptr), dims, strides, box, es, CU_TENSOR_MAP_INTERLEAVE_NONE,
      CU_TENSOR_MAP_SWIZZLE_128B, CU_TENSOR_MAP_L2_PROMOTION_L2_256B, CU_TENSOR_MAP_FLOAT_OOB_FILL_NONE);
}

struct HostState {
  bool init;
  const void* key[7];
  CUtensorMap mxA, mxB, mwA, mwB, mo, mo16, mwoA, mwoB, mout;
};
HostState g_hs;

}

extern "C" void kernel_launch(void* const* d_in, const int* in_sizes, int n_in, void* d_out, int out_size) {
  (void)in_sizes; (void)n_in; (void)out_size;
  HostState& hs = g_hs;
  bool same = hs.init && hs.key[6] == d_out;
  for (int i = 0; i < 6 && same; i++) same = hs.key[i] == d_in[i];
  if (!same) {
    void* fn = nullptr;
    cudaDriverEntryPointQueryResult qr;
    cudaGetDriverEntryPoint("cuTensorMapEncodeTiled", &fn, cudaEnableDefault, &qr);
    EncodeFn enc = (EncodeFn)fn;
    void* go = nullptr;
    cudaGetSymbolAddress(&go, g_o);
    make_map(enc, &hs.mxA, d_in[0], 512, 2048, 64, 128);
    make_map(enc, &hs.mwA, d_in[1], 1536, 512, 64, 32);
    make_map(enc, &hs.mwoA, d_in[2], 512, 512, 64, 64);
    make_map(enc, &hs.mxB, d_in[3], 512, 2048, 64, 128);
    make_map(enc, &hs.mwB, d_in[4], 1536, 512, 64, 32);
    make_map(enc, &hs.mwoB, d_in[5], 512, 512, 64, 64);
    make_map(enc, &hs.mo, go, 512, 4096, 64, 128);
    make_map(enc, &hs.mo16, go, 512, 4096, 64, 16);
    make_map(enc, &hs.mout, d_out, 1024, 2048, 64, 64);
    cudaFuncSetAttribute(qkv_gemm_kernel, cudaFuncAttributeMaxDynamicSharedMemorySize, K1_SMEM);
    cudaFuncSetAttribute(attn_kernel, cudaFuncAttributeMaxDynamicSharedMemorySize, K2_SMEM);
    cudaFuncSetAttribute(out_gemm_kernel, cudaFuncAttributeMaxDynamicSharedMemorySize, K3_SMEM);
    for (int i = 0; i < 6; i++) hs.key[i] = d_in[i];
    hs.key[6] = d_out;
    hs.init = true;
  }
  cudaStream_t st = cudaStreamPerThread;
  {
    cudaLaunchConfig_t cfg = {};
    cfg.gridDim = dim3(128);
    cfg.blockDim = dim3(384);
    cfg.dynamicSmemBytes = K1_SMEM;
    cfg.stream = st;
    cudaLaunchAttribute at[1];
    at[0].id = cudaLaunchAttributeClusterDimension;
    at[0].val.clusterDim.x = 2;
    at[0].val.clusterDim.y = 1;
    at[0].val.clusterDim.z = 1;
    cfg.attrs = at;
    cfg.numAttrs = 1;
    cudaLaunchKernelEx(&cfg, qkv_gemm_kernel, hs.mxA, hs.mxB, hs.mwA, hs.mwB);
  }
  {
    cudaLaunchConfig_t cfg = {};
    cfg.gridDim = dim3(132);
    cfg.blockDim = dim3(512);
    cfg.dynamicSmemBytes = K2_SMEM;
    cfg.stream = st;
    cudaLaunchAttribute at[1];
    at[0].id = cudaLaunchAttributeProgrammaticStreamSerialization;
    at[0].val.programmaticStreamSerializationAllowed = 1;
    cudaLaunchAttribute at2[2];
    at2[0] = at[0];
    at2[1].id = cudaLaunchAttributeClusterDimension;
    at2[1].val.clusterDim.x = 2;
    at2[1].val.clusterDim.y = 1;
    at2[1].val.clusterDim.z = 1;
    cfg.attrs = at2;
    cfg.numAttrs = 2;
    cudaLaunchKernelEx(&cfg, attn_kernel, hs.mo16);
    cfg.attrs = at;
    cfg.numAttrs = 1;
    cfg.gridDim = dim3(128);
    cfg.blockDim = dim3(288);
    cfg.dynamicSmemBytes = K3_SMEM;
    cudaLaunchKernelEx(&cfg, out_gemm_kernel, hs.mo, hs.mwoA, hs.mwoB, hs.mout);
  }
}
```

```cpp
#include <cuda_runtime.h>
#include <cuda_bf16.h>
#include <cuda.h>
#include <stdint.h>

namespace {

constexpr int S_LEN = 2048;
constexpr int DM = 512;
constexpr int NH = 32;

constexpr int KV_K_BYTES = 65536;
constexpr int KV_HEAD_BYTES = KV_K_BYTES + 98304;
__device__ uint4 g_qfrag[2 * NH * 32 * 128];
__device__ uint4 g_kv[NH * KV_HEAD_BYTES / 16];
__device__ float g_kvpart[16 * NH * 384];
__device__ float g_nrm[NH * 16 * 4];
__device__ __nv_bfloat16 g_o[2 * S_LEN * DM];

#define g_prof_dummy(i) true
#define PROF_T(k, i) do {} while (0)
#define PROF_G(k, i) do {} while (0)
__device__ __forceinline__ uint32_t smem_u32(const void* p) { return (uint32_t)__cvta_generic_to_shared(p); }
__device__ __forceinline__ void mbar_init(uint32_t bar, int cnt) {
  asm volatile("mbarrier.init.shared::cta.b64 [%0], %1;" ::"r"(bar), "r"(cnt) : "memory");
}
__device__ __forceinline__ void mbar_expect_tx(uint32_t bar, uint32_t bytes) {
  asm volatile("mbarrier.arrive.expect_tx.shared::cta.b64 _, [%0], %1;" ::"r"(bar), "r"(bytes) : "memory");
}
__device__ __forceinline__ void mbar_arrive(uint32_t bar) {
  asm volatile("mbarrier.arrive.shared::cta.b64 _, [%0];" ::"r"(bar) : "memory");
}
__device__ __forceinline__ void mbar_arrive_cluster(uint32_t bar, uint32_t cta) {
  asm volatile(
      "{\n.reg .b32 ra;\nmapa.shared::cluster.u32 ra, %0, %1;\n"
      "mbarrier.arrive.shared::cluster.b64 _, [ra];\n}" ::"r"(bar), "r"(cta) : "memory");
}
__device__ __forceinline__ void mbar_wait(uint32_t bar, uint32_t parity) {
  asm volatile(
      "{\n.reg .pred p;\n"
      "WAIT_LOOP:\n"
      "mbarrier.try_wait.parity.shared::cta.b64 p, [%0], %1, 0x989680;\n"
      "@p bra WAIT_DONE;\n"
      "bra WAIT_LOOP;\n"
      "WAIT_DONE:\n}" ::"r"(bar), "r"(parity) : "memory");
}
__device__ __forceinline__ void mbar_wait_cluster(uint32_t bar, uint32_t parity) {
  asm volatile(
      "{\n.reg .pred p;\n"
      "WAIT_LOOP:\n"
      "mbarrier.try_wait.parity.acquire.cluster.shared::cta.b64 p, [%0], %1, 0x989680;\n"
      "@p bra WAIT_DONE;\n"
      "bra WAIT_LOOP;\n"
      "WAIT_DONE:\n}" ::"r"(bar), "r"(parity) : "memory");
}
__device__ __forceinline__ void fence_barrier_init() {
  asm volatile("fence.mbarrier_init.release.cluster;" ::: "memory");
}
__device__ __forceinline__ void fence_proxy_async() { asm volatile("fence.proxy.async.shared::cta;" ::: "memory"); }
__device__ __forceinline__ void cluster_sync_relaxed() {
  asm volatile("barrier.cluster.arrive.relaxed.aligned;\nbarrier.cluster.wait.aligned;" ::: "memory");
}
__device__ __forceinline__ void tma_load_2d(uint32_t dst, const CUtensorMap* m, int x, int y, uint32_t bar) {
  asm volatile(
      "cp.async.bulk.tensor.2d.shared::cluster.global.mbarrier::complete_tx::bytes [%0], [%1, {%3, %4}], [%2];" ::"r"(dst),
      "l"(m), "r"(bar), "r"(x), "r"(y)
      : "memory");
}
__device__ __forceinline__ void tma_load_2d_mc(uint32_t dst, const CUtensorMap* m, int x, int y, uint32_t bar, uint16_t mask) {
  asm volatile(
      "cp.async.bulk.tensor.2d.shared::cluster.global.mbarrier::complete_tx::bytes.multicast::cluster [%0], [%1, {%3, %4}], "
      "[%2], %5;" ::"r"(dst),
      "l"(m), "r"(bar), "r"(x), "r"(y), "h"(mask)
      : "memory");
}
__device__ __forceinline__ void tma_store_2d(const CUtensorMap* m, uint32_t src, int x, int y) {
  asm volatile("cp.async.bulk.tensor.2d.global.shared::cta.bulk_group [%0, {%2, %3}], [%1];" ::"l"(m), "r"(src), "r"(x),
               "r"(y)
               : "memory");
}
__device__ __forceinline__ void bulk_load(uint32_t dst, const void* src, uint32_t bytes, uint32_t bar) {
  asm volatile("cp.async.bulk.shared::cluster.global.mbarrier::complete_tx::bytes [%0], [%1], %2, [%3];" ::"r"(dst),
               "l"(src), "r"(bytes), "r"(bar)
               : "memory");
}
__device__ __forceinline__ void bulk_load_mc(uint32_t dst, const void* src, uint32_t bytes, uint32_t bar, uint16_t mask) {
  asm volatile("cp.async.bulk.shared::cluster.global.mbarrier::complete_tx::bytes.multicast::cluster [%0], [%1], %2, [%3], %4;" ::"r"(dst),
               "l"(src), "r"(bytes), "r"(bar), "h"(mask)
               : "memory");
}
__device__ __forceinline__ void pdl_launch_dependents() { asm volatile("griddepcontrol.launch_dependents;" ::: "memory"); }
__device__ __forceinline__ void pdl_wait() { asm volatile("griddepcontrol.wait;" ::: "memory"); }
__device__ __forceinline__ void wg_fence() { asm volatile("wgmma.fence.sync.aligned;" ::: "memory"); }
__device__ __forceinline__ void wg_commit() { asm volatile("wgmma.commit_group.sync.aligned;" ::: "memory"); }
template <int N>
__device__ __forceinline__ void wg_wait() {
  asm volatile("wgmma.wait_group.sync.aligned %0;" ::"n"(N) : "memory");
}
template <int M>
__device__ __forceinline__ void fence_regs(float (&r)[M]) {
#pragma unroll
  for (int i = 0; i < M; i++) asm volatile("" : "+f"(r[i])::"memory");
}
__device__ __forceinline__ uint64_t mkdesc(uint32_t addr, uint32_t lbo, uint32_t sbo, uint32_t layout) {
  return (uint64_t)((addr & 0x3FFFF) >> 4) | ((uint64_t)(lbo >> 4) << 16) | ((uint64_t)(sbo >> 4) << 32) |
         ((uint64_t)layout << 62);
}
__device__ __forceinline__ uint32_t pack_bf16(float lo, float hi) {
  uint32_t r;
  asm("cvt.rn.bf16x2.f32 %0, %1, %2;" : "=r"(r) : "f"(hi), "f"(lo));
  return r;
}
__device__ __forceinline__ float bf_lo(uint32_t v) { return __uint_as_float(v << 16); }
__device__ __forceinline__ float bf_hi(uint32_t v) { return __uint_as_float(v & 0xFFFF0000u); }
__device__ __forceinline__ float round_bf16(float x) { return bf_lo(pack_bf16(x, 0.f)); }
__device__ __forceinline__ float ex2f(float x) {
  float y;
  asm("ex2.approx.ftz.f32 %0, %1;" : "=f"(y) : "f"(x));
  return y;
}

__device__ __forceinline__ void wgmma_rs_n24_tb(float (&d)[12], uint32_t a0, uint32_t a1, uint32_t a2, uint32_t a3, uint64_t descB, int scaleD) {
  asm volatile("{\n.reg .pred p;\nsetp.ne.b32 p, %17, 0;\n"
    "wgmma.mma_async.sync.aligned.m64n24k16.f32.bf16.bf16 "
    "{%0, %1, %2, %3, %4, %5, %6, %7, %8, %9, %10, %11}, {%12, %13, %14, %15}, %16, p, 1, 1, 1;\n}\n"
    : "+f"(d[0]), "+f"(d[1]), "+f"(d[2]), "+f"(d[3]), "+f"(d[4]), "+f"(d[5]), "+f"(d[6]), "+f"(d[7]),
      "+f"(d[8]), "+f"(d[9]), "+f"(d[10]), "+f"(d[11])
    : "r"(a0), "r"(a1), "r"(a2), "r"(a3), "l"(descB), "r"(scaleD));
}
__device__ __forceinline__ void wgmma_rs_n64_z(float (&d)[32], uint32_t a0, uint32_t a1, uint32_t a2, uint32_t a3, uint64_t descB) {
  asm volatile("{\n.reg .pred p;\nsetp.ne.b32 p, %37, 0;\n"
    "wgmma.mma_async.sync.aligned.m64n64k16.f32.bf16.bf16 "
    "{%0, %1, %2, %3, %4, %5, %6, %7, %8, %9, %10, %11, %12, %13, %14, %15, %16, %17, %18, %19, %20, %21, %22, %23, %24, %25, %26, %27, %28, %29, %30, %31}, {%32, %33, %34, %35}, %36, p, 1, 1, 0;\n}\n"
    : "=f"(d[0]), "=f"(d[1]), "=f"(d[2]), "=f"(d[3]), "=f"(d[4]), "=f"(d[5]), "=f"(d[6]), "=f"(d[7]),
      "=f"(d[8]), "=f"(d[9]), "=f"(d[10]), "=f"(d[11]), "=f"(d[12]), "=f"(d[13]), "=f"(d[14]), "=f"(d[15]),
      "=f"(d[16]), "=f"(d[17]), "=f"(d[18]), "=f"(d[19]), "=f"(d[20]), "=f"(d[21]), "=f"(d[22]), "=f"(d[23]),
      "=f"(d[24]), "=f"(d[25]), "=f"(d[26]), "=f"(d[27]), "=f"(d[28]), "=f"(d[29]), "=f"(d[30]), "=f"(d[31])
    : "r"(a0), "r"(a1), "r"(a2), "r"(a3), "l"(descB), "n"(0));
}
__device__ __forceinline__ void wgmma_ss_n128_tb(float (&d)[64], uint64_t descA, uint64_t descB, int scaleD) {
  asm volatile("{\n.reg .pred p;\nsetp.ne.b32 p, %66, 0;\n"
    "wgmma.mma_async.sync.aligned.m64n128k16.f32.bf16.bf16 "
    "{%0, %1, %2, %3, %4, %5, %6, %7, %8, %9, %10, %11, %12, %13, %14, %15, %16, %17, %18, %19, %20, %21, %22, %23, %24, %25, %26, %27, %28, %29, %30, %31, %32, %33, %34, %35, %36, %37, %38, %39, %40, %41, %42, %43, %44, %45, %46, %47, %48, %49, %50, %51, %52, %53, %54, %55, %56, %57, %58, %59, %60, %61, %62, %63}, %64, %65, p, 1, 1, 0, 1;\n}\n"
    : "+f"(d[0]), "+f"(d[1]), "+f"(d[2]), "+f"(d[3]), "+f"(d[4]), "+f"(d[5]), "+f"(d[6]), "+f"(d[7]),
      "+f"(d[8]), "+f"(d[9]), "+f"(d[10]), "+f"(d[11]), "+f"(d[12]), "+f"(d[13]), "+f"(d[14]), "+f"(d[15]),
      "+f"(d[16]), "+f"(d[17]), "+f"(d[18]), "+f"(d[19]), "+f"(d[20]), "+f"(d[21]), "+f"(d[22]), "+f"(d[23]),
      "+f"(d[24]), "+f"(d[25]), "+f"(d[26]), "+f"(d[27]), "+f"(d[28]), "+f"(d[29]), "+f"(d[30]), "+f"(d[31]),
      "+f"(d[32]), "+f"(d[33]), "+f"(d[34]), "+f"(d[35]), "+f"(d[36]), "+f"(d[37]), "+f"(d[38]), "+f"(d[39]),
      "+f"(d[40]), "+f"(d[41]), "+f"(d[42]), "+f"(d[43]), "+f"(d[44]), "+f"(d[45]), "+f"(d[46]), "+f"(d[47]),
      "+f"(d[48]), "+f"(d[49]), "+f"(d[50]), "+f"(d[51]), "+f"(d[52]), "+f"(d[53]), "+f"(d[54]), "+f"(d[55]),
      "+f"(d[56]), "+f"(d[57]), "+f"(d[58]), "+f"(d[59]), "+f"(d[60]), "+f"(d[61]), "+f"(d[62]), "+f"(d[63])
    : "l"(descA), "l"(descB), "r"(scaleD));
}
__device__ __forceinline__ void wgmma_ss_n192_tb(float (&d)[96], uint64_t descA, uint64_t descB, int scaleD) {
  asm volatile("{\n.reg .pred p;\nsetp.ne.b32 p, %98, 0;\n"
    "wgmma.mma_async.sync.aligned.m64n192k16.f32.bf16.bf16 "
    "{%0, %1, %2, %3, %4, %5, %6, %7, %8, %9, %10, %11, %12, %13, %14, %15, %16, %17, %18, %19, %20, %21, %22, %23, %24, %25, %26, %27, %28, %29, %30, %31, %32, %33, %34, %35, %36, %37, %38, %39, %40, %41, %42, %43, %44, %45, %46, %47, %48, %49, %50, %51, %52, %53, %54, %55, %56, %57, %58, %59, %60, %61, %62, %63, %64, %65, %66, %67, %68, %69, %70, %71, %72, %73, %74, %75, %76, %77, %78, %79, %80, %81, %82, %83, %84, %85, %86, %87, %88, %89, %90, %91, %92, %93, %94, %95}, %96, %97, p, 1, 1, 0, 1;\n}\n"
    : "+f"(d[0]), "+f"(d[1]), "+f"(d[2]), "+f"(d[3]), "+f"(d[4]), "+f"(d[5]), "+f"(d[6]), "+f"(d[7]),
      "+f"(d[8]), "+f"(d[9]), "+f"(d[10]), "+f"(d[11]), "+f"(d[12]), "+f"(d[13]), "+f"(d[14]), "+f"(d[15]),
      "+f"(d[16]), "+f"(d[17]), "+f"(d[18]), "+f"(d[19]), "+f"(d[20]), "+f"(d[21]), "+f"(d[22]), "+f"(d[23]),
      "+f"(d[24]), "+f"(d[25]), "+f"(d[26]), "+f"(d[27]), "+f"(d[28]), "+f"(d[29]), "+f"(d[30]), "+f"(d[31]),
      "+f"(d[32]), "+f"(d[33]), "+f"(d[34]), "+f"(d[35]), "+f"(d[36]), "+f"(d[37]), "+f"(d[38]), "+f"(d[39]),
      "+f"(d[40]), "+f"(d[41]), "+f"(d[42]), "+f"(d[43]), "+f"(d[44]), "+f"(d[45]), "+f"(d[46]), "+f"(d[47]),
      "+f"(d[48]), "+f"(d[49]), "+f"(d[50]), "+f"(d[51]), "+f"(d[52]), "+f"(d[53]), "+f"(d[54]), "+f"(d[55]),
      "+f"(d[56]), "+f"(d[57]), "+f"(d[58]), "+f"(d[59]), "+f"(d[60]), "+f"(d[61]), "+f"(d[62]), "+f"(d[63]),
      "+f"(d[64]), "+f"(d[65]), "+f"(d[66]), "+f"(d[67]), "+f"(d[68]), "+f"(d[69]), "+f"(d[70]), "+f"(d[71]),
      "+f"(d[72]), "+f"(d[73]), "+f"(d[74]), "+f"(d[75]), "+f"(d[76]), "+f"(d[77]), "+f"(d[78]), "+f"(d[79]),
      "+f"(d[80]), "+f"(d[81]), "+f"(d[82]), "+f"(d[83]), "+f"(d[84]), "+f"(d[85]), "+f"(d[86]), "+f"(d[87]),
      "+f"(d[88]), "+f"(d[89]), "+f"(d[90]), "+f"(d[91]), "+f"(d[92]), "+f"(d[93]), "+f"(d[94]), "+f"(d[95])
    : "l"(descA), "l"(descB), "r"(scaleD));
}

__device__ __forceinline__ void ldsm4t(uint32_t (&b)[4], uint32_t addr) {
  asm volatile("ldmatrix.sync.aligned.m8n8.x4.trans.shared.b16 {%0,%1,%2,%3}, [%4];"
               : "=r"(b[0]), "=r"(b[1]), "=r"(b[2]), "=r"(b[3])
               : "r"(addr));
}
__device__ __forceinline__ void hmma(float (&c)[4], uint32_t a0, uint32_t a1, uint32_t a2, uint32_t a3, uint32_t b0, uint32_t b1) {
  asm("mma.sync.aligned.m16n8k16.row.col.f32.bf16.bf16.f32 {%0,%1,%2,%3}, {%4,%5,%6,%7}, {%8,%9}, {%0,%1,%2,%3};"
      : "+f"(c[0]), "+f"(c[1]), "+f"(c[2]), "+f"(c[3])
      : "r"(a0), "r"(a1), "r"(a2), "r"(a3), "r"(b0), "r"(b1));
}

__device__ __forceinline__ uint32_t movm(uint32_t a) {
  uint32_t d;
  asm volatile("movmatrix.sync.aligned.m8n8.trans.b16 %0, %1;" : "=r"(d) : "r"(a));
  return d;
}

constexpr int K1_STAGES = 4;
constexpr int K1_W_BYTES = 3 * 8192;
constexpr int K1_X_BYTES = 8 * 16384;
constexpr int K1_BAR_OFF = K1_X_BYTES + K1_STAGES * K1_W_BYTES;
constexpr int K1_SMEM = K1_BAR_OFF + 192 + 1024;
constexpr float QSCALE = 0.25f * 1.4426950408889634f;

__device__ __forceinline__ uint32_t phi2(uint32_t t2) {
  uint32_t a2, mask, r2, o2;
  asm("add.rn.bf16x2 %0, %1, %2;" : "=r"(a2) : "r"(t2), "r"(0x3F803F80u));
  const uint32_t e2 = pack_bf16(ex2f(bf_lo(t2) * 1.4426950408889634f), ex2f(bf_hi(t2) * 1.4426950408889634f));
  asm("set.gt.u32.bf16x2 %0, %1, %2;" : "=r"(mask) : "r"(t2), "r"(0u));
  r2 = (a2 & mask) | (e2 & ~mask);
  asm("add.rn.bf16x2 %0, %1, %2;" : "=r"(o2) : "r"(r2), "r"(0x35863586u));
  return o2;
}

#define K1_SLOT_KB(h) ((h) < 4 ? 2 * (h) : 2 * ((h) - 4) + 1)
struct EpiCtx {
  uint4* qf;
  uint32_t* kp;
  uint32_t* vp;
  uint32_t* s_red;
  float* red;
  int lane;
};

template <bool LINEAR, int J, int HH, int PART>
__device__ __forceinline__ void epi_slice(const float (&acc)[96], const EpiCtx& c, uint32_t (&pk)[4], float& vmax) {
  constexpr int h = J * 4 + HH;
  const float* a = &acc[HH * 8];
  const float* k = &acc[32 + HH * 8];
  const float* v = &acc[64 + HH * 8];
  if (!LINEAR) {
    if (PART == 0) {
      c.qf[h * 32 * 128] = make_uint4(pack_bf16(a[0] * QSCALE, a[1] * QSCALE), pack_bf16(a[2] * QSCALE, a[3] * QSCALE),
                                      pack_bf16(a[4] * QSCALE, a[5] * QSCALE), pack_bf16(a[6] * QSCALE, a[7] * QSCALE));
      uint32_t* kh = c.kp + h * (KV_HEAD_BYTES / 4);
      kh[0] = pack_bf16(k[0], k[1]);
      kh[64] = pack_bf16(k[2], k[3]);
      kh[32] = pack_bf16(k[4], k[5]);
      kh[96] = pack_bf16(k[6], k[7]);
      float q0 = a[0] * a[0] + a[1] * a[1] + a[4] * a[4] + a[5] * a[5];
      float q1 = a[2] * a[2] + a[3] * a[3] + a[6] * a[6] + a[7] * a[7];
      float k0 = k[0] * k[0] + k[1] * k[1] + k[4] * k[4] + k[5] * k[5];
      float k1 = k[2] * k[2] + k[3] * k[3] + k[6] * k[6] + k[7] * k[7];
#pragma unroll
      for (int o = 1; o <= 2; o <<= 1) {
        q0 += __shfl_xor_sync(0xffffffffu, q0, o);
        q1 += __shfl_xor_sync(0xffffffffu, q1, o);
        k0 += __shfl_xor_sync(0xffffffffu, k0, o);
        k1 += __shfl_xor_sync(0xffffffffu, k1, o);
      }
      const uint32_t qm = __reduce_max_sync(0xffffffffu, max(__float_as_uint(q0) & 0x7FFFFFFFu, __float_as_uint(q1) & 0x7FFFFFFFu));
      const uint32_t km = __reduce_max_sync(0xffffffffu, max(__float_as_uint(k0) & 0x7FFFFFFFu, __float_as_uint(k1) & 0x7FFFFFFFu));
      if (c.lane == 0) {
        atomicMax(&c.s_red[h * 2 + 0], qm);
        atomicMax(&c.s_red[h * 2 + 1], km);
      }
    } else {
      uint32_t* vh = c.vp + h * (KV_HEAD_BYTES / 4);
      vh[0] = pack_bf16(v[0], v[1]);
      vh[96] = pack_bf16(v[2], v[3]);
      vh[32] = pack_bf16(v[4], v[5]);
      vh[128] = pack_bf16(v[6], v[7]);
      vh[64] = 0x3F803F80u;
      vh[160] = 0x3F803F80u;
#pragma unroll
      for (int i = 0; i < 8; i++) asm("max.NaN.f32 %0, %0, %1;" : "+f"(vmax) : "f"(fabsf(v[i])));
    }
  } else {
    if (PART == 0) {
      c.qf[h * 32 * 128] = make_uint4(phi2(pack_bf16(a[0], a[1])), phi2(pack_bf16(a[2], a[3])), phi2(pack_bf16(a[4], a[5])),
                                      phi2(pack_bf16(a[6], a[7])));
      pk[0] = movm(phi2(pack_bf16(k[0], k[1])));
      pk[2] = movm(phi2(pack_bf16(k[2], k[3])));
      pk[1] = movm(phi2(pack_bf16(k[4], k[5])));
      pk[3] = movm(phi2(pack_bf16(k[6], k[7])));
    } else {
      const uint32_t b0 = movm(pack_bf16(v[0], v[1]));
      const uint32_t b1 = movm(pack_bf16(v[2], v[3]));
      const uint32_t b2 = movm(pack_bf16(v[4], v[5]));
      const uint32_t b3 = movm(pack_bf16(v[6], v[7]));
      float c0[4] = {0, 0, 0, 0}, c1[4] = {0, 0, 0, 0}, c2[4] = {0, 0, 0, 0};
      hmma(c0, pk[0], pk[1], pk[2], pk[3], b0, b1);
      hmma(c1, pk[0], pk[1], pk[2], pk[3], b2, b3);
      hmma(c2, pk[0], pk[1], pk[2], pk[3], 0x3F803F80u, 0x3F803F80u);
      float* slot = c.red + K1_SLOT_KB(h) * 4096;
#pragma unroll
      for (int i = 0; i < 4; i++) {
        slot[i * 32] = c0[i];
        slot[(4 + i) * 32] = c1[i];
        slot[(8 + i) * 32] = c2[i];
      }
    }
  }
}

template <bool LINEAR>
__device__ __forceinline__ void qkv_consumer(uint32_t sbase, uint8_t* smem_gen, uint32_t* s_red, int cp, int rt) {
  const uint32_t bar_full = sbase + K1_BAR_OFF;
  const uint32_t bar_empty = bar_full + 8 * K1_STAGES;
  const int warp = threadIdx.x >> 5;
  const int wg = warp >> 2;
  const int lane = threadIdx.x & 31;
  float acc0[96], acc1[96];
#pragma unroll 1
  for (int kb = 0; kb < 8; kb++) {
    const int s = kb % K1_STAGES;
    mbar_wait(bar_full + 8 * s, (kb / K1_STAGES) & 1);
    if (threadIdx.x == 0) PROF_T(0, 2 + (kb >> 1));
    const uint64_t dA = mkdesc(sbase + kb * 16384 + wg * 8192, 16, 1024, 1);
    const uint64_t dB = mkdesc(sbase + K1_X_BYTES + s * K1_W_BYTES, 8192, 1024, 1);
    wg_fence();
#pragma unroll
    for (int k = 0; k < 4; k++) wgmma_ss_n192_tb(acc0, dA + k * 2, dB + k * 128, (kb | k) != 0);
    wg_commit();
    if (kb > 0) {
      wg_wait<1>();
      if ((threadIdx.x & 127) == 0) {
        const int sp = (kb - 1) % K1_STAGES;
        mbar_arrive_cluster(bar_empty + 8 * sp, 0);
        mbar_arrive_cluster(bar_empty + 8 * sp, 1);
      }
    }
  }
  wg_wait<0>();
  fence_regs(acc0);
  if ((threadIdx.x & 127) == 0) {
    mbar_arrive_cluster(bar_empty + 8 * (7 % K1_STAGES), 0);
    mbar_arrive_cluster(bar_empty + 8 * (7 % K1_STAGES), 1);
  }
  if (threadIdx.x == 0) PROF_T(0, 6);

  EpiCtx c;
  {
    const int row0 = rt * 128 + wg * 64 + (warp & 3) * 16;
    c.qf = g_qfrag + ((size_t)((LINEAR ? NH : 0) + cp * 8) * 32 + (rt * 2 + wg)) * 128 + (threadIdx.x & 127);
    uint32_t* img = reinterpret_cast<uint32_t*>(reinterpret_cast<uint8_t*>(g_kv) + (size_t)(cp * 8) * KV_HEAD_BYTES);
    c.kp = img + (row0 >> 3) * 64 + lane;
    c.vp = img + KV_K_BYTES / 4 + (row0 >> 3) * 96 + lane;
    c.s_red = s_red;
    c.red = reinterpret_cast<float*>(smem_gen + wg * 8192) + (warp & 3) * 384 + lane;
    c.lane = lane;
  }
  uint32_t pk[4];
  float vmax = 0.f;
#define K1_T1_STEP(KB)                                                                           \
  {                                                                                              \
    constexpr int g = 8 + KB;                                                                    \
    constexpr int s = g % K1_STAGES;                                                             \
    mbar_wait(bar_full + 8 * s, (g / K1_STAGES) & 1);                                            \
    const uint64_t dA = mkdesc(sbase + KB * 16384 + wg * 8192, 16, 1024, 1);                     \
    const uint64_t dB = mkdesc(sbase + K1_X_BYTES + s * K1_W_BYTES, 8192, 1024, 1);              \
    wg_fence();                                                                                  \
    _Pragma("unroll") for (int k = 0; k < 4; k++) wgmma_ss_n192_tb(acc1, dA + k * 2, dB + k * 128, (KB | k) != 0); \
    wg_commit();                                                                                 \
    epi_slice<LINEAR, 0, KB / 2, KB & 1>(acc0, c, pk, vmax);                                     \
    wg_wait<0>();                                                                                \
    if (KB + K1_STAGES < 8 && (threadIdx.x & 127) == 0) {                                        \
      mbar_arrive_cluster(bar_empty + 8 * s, 0);                                                 \
      mbar_arrive_cluster(bar_empty + 8 * s, 1);                                                 \
    }                                                                                            \
  }
  K1_T1_STEP(0) K1_T1_STEP(1) K1_T1_STEP(2) K1_T1_STEP(3) K1_T1_STEP(4) K1_T1_STEP(5) K1_T1_STEP(6) K1_T1_STEP(7)
#undef K1_T1_STEP
  fence_regs(acc1);
  if (threadIdx.x == 0) PROF_T(0, 10);
  epi_slice<LINEAR, 1, 0, 0>(acc1, c, pk, vmax);
  epi_slice<LINEAR, 1, 0, 1>(acc1, c, pk, vmax);
  epi_slice<LINEAR, 1, 1, 0>(acc1, c, pk, vmax);
  epi_slice<LINEAR, 1, 1, 1>(acc1, c, pk, vmax);
  epi_slice<LINEAR, 1, 2, 0>(acc1, c, pk, vmax);
  epi_slice<LINEAR, 1, 2, 1>(acc1, c, pk, vmax);
  epi_slice<LINEAR, 1, 3, 0>(acc1, c, pk, vmax);
  epi_slice<LINEAR, 1, 3, 1>(acc1, c, pk, vmax);
  if (!LINEAR) {
    const uint32_t vm = __reduce_max_sync(0xffffffffu, __float_as_uint(vmax) & 0x7FFFFFFFu);
    if (lane == 0) atomicMax(&s_red[16], vm);
    asm volatile("bar.sync 1, 256;" ::: "memory");
    if (threadIdx.x < 8) {
      *reinterpret_cast<float4*>(&g_nrm[((cp * 8 + threadIdx.x) * 16 + rt) * 4]) =
          make_float4(__uint_as_float(s_red[threadIdx.x * 2]), __uint_as_float(s_red[threadIdx.x * 2 + 1]), __uint_as_float(s_red[16]), 0.f);
    }
  } else {
    asm volatile("bar.sync 1, 256;" ::: "memory");
    float* dst = g_kvpart + ((size_t)rt * NH + cp * 8) * 384;
#pragma unroll
    for (int i = 0; i < 12; i++) {
      const int o = threadIdx.x + i * 256;
      const int h = o / 384, e = o - h * 384;
      const float* src = reinterpret_cast<const float*>(smem_gen) + K1_SLOT_KB(h) * 4096 + e;
      float sum = 0.f;
#pragma unroll
      for (int w = 0; w < 8; w++) sum += src[(w >> 2) * 2048 + (w & 3) * 384];
      dst[o] = sum;
    }
  }
}

__global__ void __launch_bounds__(384, 1)
qkv_gemm_kernel(const __grid_constant__ CUtensorMap mxA, const __grid_constant__ CUtensorMap mxB,
                const __grid_constant__ CUtensorMap mwA, const __grid_constant__ CUtensorMap mwB) {
  extern __shared__ uint8_t smem_raw[];
  const uint32_t sbase = (smem_u32(smem_raw) + 1023) & ~1023u;
  uint8_t* smem_gen = smem_raw + (sbase - smem_u32(smem_raw));
  const uint32_t bar_full = sbase + K1_BAR_OFF;
  const uint32_t bar_empty = bar_full + 8 * K1_STAGES;
  uint32_t* s_red = reinterpret_cast<uint32_t*>(smem_gen + K1_BAR_OFF + 64);

  const int rank = blockIdx.x & 1;
  const int pair = blockIdx.x >> 1;
  const int branch = pair >> 5;
  const int rp = (pair & 31) >> 2;
  const int cp = pair & 3;
  const int rt = rp * 2 + rank;
  const int warp = threadIdx.x >> 5;
  if (threadIdx.x == 0) { PROF_G(0, 30); PROF_T(0, 0); }
  const CUtensorMap* mx = branch ? &mxA : &mxB;
  const CUtensorMap* mw = branch ? &mwA : &mwB;

  if (threadIdx.x == 256) {
    asm volatile("prefetch.tensormap [%0];" ::"l"(mx) : "memory");
    asm volatile("prefetch.tensormap [%0];" ::"l"(mw) : "memory");
    for (int i = 0; i < K1_STAGES; i++) {
      mbar_init(bar_full + 8 * i, 1);
      mbar_init(bar_empty + 8 * i, 4);
    }
    fence_barrier_init();
    fence_proxy_async();
    for (int kb = 0; kb < K1_STAGES; kb++) mbar_expect_tx(bar_full + 8 * kb, 16384 + K1_W_BYTES);
    tma_load_2d(sbase, mx, 0, rt * 128, bar_full);
  }
  pdl_launch_dependents();
  if (threadIdx.x < 32) s_red[threadIdx.x] = 0;
  __syncthreads();
  cluster_sync_relaxed();
  if (threadIdx.x == 0) PROF_T(0, 1);

  if (warp >= 8) {
    asm volatile("setmaxnreg.dec.sync.aligned.u32 40;");
    if (threadIdx.x == 256) {
      for (int g = 0; g < 16; g++) {
        const int s = g % K1_STAGES;
        const int kb = g & 7;
        if (g >= K1_STAGES) {
          mbar_wait(bar_empty + 8 * s, ((g / K1_STAGES) - 1) & 1);
          mbar_expect_tx(bar_full + 8 * s, (g < 8 ? 16384 : 0) + K1_W_BYTES);
        }
        if (g > 0 && g < 8) tma_load_2d(sbase + kb * 16384, mx, kb * 64, rt * 128, bar_full + 8 * s);
        const int h0 = cp * 8 + (g >> 3) * 4;
        const uint32_t st = sbase + K1_X_BYTES + s * K1_W_BYTES + rank * 4096;
#pragma unroll
        for (int p = 0; p < 3; p++)
          tma_load_2d_mc(st + p * 8192, mw, p * 512 + h0 * 16, kb * 64 + rank * 32, bar_full + 8 * s, (uint16_t)3);
      }
    }
    __syncwarp();
    cluster_sync_relaxed();
  } else {
    asm volatile("setmaxnreg.inc.sync.aligned.u32 232;");
    if (branch == 0) qkv_consumer<false>(sbase, smem_gen, s_red, cp, rt);
    else qkv_consumer<true>(sbase, smem_gen, s_red, cp, rt);
    if (threadIdx.x == 0) PROF_T(0, 11);
    __syncwarp();
    cluster_sync_relaxed();
    if (threadIdx.x == 0) { PROF_T(0, 12); PROF_G(0, 31); }
  }
}

constexpr int K2_SMEM = KV_HEAD_BYTES + 1024 + 256;

#define ATT_NPOLY 18
#define ATT_CH 8
#define ATT_D 1
#define ATT_GM 1
#define ATT_DEG 2
struct ExpC {
  uint32_t k3c00, kmask, seven, c3;
};
__device__ __forceinline__ uint32_t hfma2(uint32_t a, uint32_t b, uint32_t c) {
  uint32_t r;
  asm("fma.rn.f16x2 %0, %1, %2, %3;" : "=r"(r) : "r"(a), "r"(b), "r"(c));
  return r;
}
__device__ __forceinline__ uint32_t exp2_poly_pair(float t0, float t1, const ExpC& c) {
  uint32_t u;
  asm("prmt.b32 %0, %1, %2, 0x5410;" : "=r"(u) : "r"(__float_as_uint(t0)), "r"(__float_as_uint(t1)));
  uint32_t m;
  asm("lop3.b32 %0, %1, 0x03FF03FF, %2, 0xEA;" : "=r"(m) : "r"(u), "r"(c.k3c00));
  uint32_t p = hfma2(m, c.c3, 0xa385a385u);
  p = hfma2(p, m, 0x4ad64ad7u);
  uint32_t mu;
  asm("lop3.b32 %0, %1, 0xFC00FC00, %2, 0xEA;" : "=r"(mu) : "r"(u), "r"(c.kmask));
  uint32_t r;
  asm("{.reg .b32 t; shf.r.wrap.b32 t, %1, %2, 3; add.u32 %0, t, %3;}" : "=r"(r) : "r"(mu), "r"(c.seven), "r"(p));
  return r;
}
__device__ __forceinline__ float gadd(float x, float M, uint32_t g) {
  float r = x;
  asm("{.reg .pred p; setp.ne.b32 p, %2, -1; @p add.f32 %0, %0, %1;}" : "+f"(r) : "f"(M), "r"(g));
  return r;
}
__device__ __forceinline__ float gex2(float x, uint32_t g) {
  float r = x;
  asm("{.reg .pred p; setp.ne.b32 p, %1, -1; @p ex2.approx.ftz.f32 %0, %0;}" : "+f"(r) : "r"(g));
  return r;
}
template <int NPOLY, int NPAIR, int CH, int D>
__device__ __forceinline__ void exp_tile(const float (&s)[2 * NPAIR], uint32_t (&p)[NPAIR], const ExpC& c) {
#pragma unroll
  for (int i = 0; i < NPAIR; i++) {
    const bool isPoly = ((i + 1) * NPOLY / 32) != (i * NPOLY / 32);
    const int ch = i / CH;
    const bool gated = ch >= D;
    int gi = (ch - D) * CH + CH - 1;
    if (gated) {
      while (gi > (ch - D) * CH && !(((gi + 1) * NPOLY / 32) != (gi * NPOLY / 32))) gi--;
    }
    const uint32_t g = gated ? p[gi] : 0;
    if (!isPoly) {
      if (gated && ATT_GM) p[i] = pack_bf16(gex2(s[2 * i], g), gex2(s[2 * i + 1], g));
      else p[i] = pack_bf16(ex2f(s[2 * i]), ex2f(s[2 * i + 1]));
    } else {
      if (gated) p[i] = exp2_poly_pair(gadd(s[2 * i], 12329.f, g), gadd(s[2 * i + 1], 12329.f, g), c);
      else p[i] = exp2_poly_pair(s[2 * i] + 12329.f, s[2 * i + 1] + 12329.f, c);
    }
  }
}

__device__ __forceinline__ void store_o(__nv_bfloat16* o, int row0, int head, int lane, const uint32_t (&r)[4]) {
  const int g = lane >> 2, t = lane & 3;
  uint32_t* p0 = reinterpret_cast<uint32_t*>(o + (size_t)(row0 + g) * DM + head * 16) + t;
  uint32_t* p1 = reinterpret_cast<uint32_t*>(o + (size_t)(row0 + g + 8) * DM + head * 16) + t;
  p0[0] = r[0];
  p1[0] = r[1];
  p0[4] = r[2];
  p1[4] = r[3];
}

__device__ __forceinline__ void safe_exp(const float (&s)[32], uint32_t (&p)[16], float (&o)[12], float& m0, float& m1) {
  float x0 = s[0], x1 = s[2];
#pragma unroll
  for (int i = 0; i < 8; i++) {
    x0 = fmaxf(x0, fmaxf(s[4 * i], s[4 * i + 1]));
    x1 = fmaxf(x1, fmaxf(s[4 * i + 2], s[4 * i + 3]));
  }
  x0 = fmaxf(x0, __shfl_xor_sync(0xffffffffu, x0, 1));
  x1 = fmaxf(x1, __shfl_xor_sync(0xffffffffu, x1, 1));
  x0 = fmaxf(x0, __shfl_xor_sync(0xffffffffu, x0, 2));
  x1 = fmaxf(x1, __shfl_xor_sync(0xffffffffu, x1, 2));
  const float n0 = fmaxf(m0, x0), n1 = fmaxf(m1, x1);
  const float c0 = ex2f(m0 - n0), c1 = ex2f(m1 - n1);
  m0 = n0;
  m1 = n1;
#pragma unroll
  for (int i = 0; i < 3; i++) {
    o[4 * i] *= c0;
    o[4 * i + 1] *= c0;
    o[4 * i + 2] *= c1;
    o[4 * i + 3] *= c1;
  }
#pragma unroll
  for (int i = 0; i < 8; i++) {
    p[2 * i] = pack_bf16(ex2f(s[4 * i] - n0), ex2f(s[4 * i + 1] - n0));
    p[2 * i + 1] = pack_bf16(ex2f(s[4 * i + 2] - n1), ex2f(s[4 * i + 3] - n1));
  }
}

__device__ __forceinline__ void attn_step(float (&sx)[32], float (&sy)[32], float (&o)[12], const uint4& qf, uint64_t dK, uint64_t dV,
                                          const ExpC& ec) {
  uint32_t pa[16], pb[16];
  wg_fence();
  wgmma_rs_n64_z(sy, qf.x, qf.y, qf.z, qf.w, dK + 128);
  wg_commit();
  exp_tile<ATT_NPOLY, 16, ATT_CH, ATT_D>(sx, pa, ec);
  wg_fence();
  wgmma_rs_n24_tb(o, pa[12], pa[13], pa[14], pa[15], dV + 3 * 48, 1);
  wg_commit();
  wg_wait<1>();
  fence_regs(sy);
  exp_tile<ATT_NPOLY, 16, ATT_CH, ATT_D>(sy, pb, ec);
  wg_fence();
#pragma unroll
  for (int k = 0; k < 3; k++) wgmma_rs_n24_tb(o, pa[4 * k], pa[4 * k + 1], pa[4 * k + 2], pa[4 * k + 3], dV + k * 48, 1);
#pragma unroll
  for (int k = 0; k < 4; k++) wgmma_rs_n24_tb(o, pb[4 * k], pb[4 * k + 1], pb[4 * k + 2], pb[4 * k + 3], dV + (4 + k) * 48, 1);
  wgmma_rs_n64_z(sy, qf.x, qf.y, qf.z, qf.w, dK + 256);
  wg_commit();
  wg_wait<0>();
  fence_regs(sy);
}

template <bool SAFE>
__device__ __forceinline__ void attn_tile(uint64_t dK, uint64_t dV, uint32_t bar, const uint4 qf, const ExpC& ec, uint32_t (&outp)[4]) {
  float o[12];
#pragma unroll
  for (int i = 0; i < 12; i++) asm volatile("mov.f32 %0, 0f00000000;" : "=f"(o[i]));
  mbar_wait(bar, 0);
  if (threadIdx.x == 0 && !g_prof_dummy(8)) PROF_T(1, 8);
  if (!SAFE) {
    float s0[32], s1[32];
    wg_fence();
    wgmma_rs_n64_z(s0, qf.x, qf.y, qf.z, qf.w, dK);
    wg_commit();
    wg_wait<0>();
    fence_regs(s0);
#pragma unroll 1
    for (int p = 0; p < 8; p++) {
      if (p & 1) mbar_wait(bar + 8 * min((p + 1) >> 1, 3), 0);
      attn_step(s0, s1, o, qf, dK, dV, ec);
      attn_step(s1, s0, o, qf, dK + 256, dV + 384, ec);
      dK += 512;
      dV += 768;
    }
  } else {
    float m0 = -INFINITY, m1 = -INFINITY;
#pragma unroll 1
    for (int j = 0; j < 32; j++) {
      if (j == 4) { mbar_wait(bar + 8, 0); mbar_wait(bar + 16, 0); mbar_wait(bar + 24, 0); }
      float s[32];
      uint32_t p[16];
      wg_fence();
      wgmma_rs_n64_z(s, qf.x, qf.y, qf.z, qf.w, dK);
      wg_commit();
      wg_wait<0>();
      fence_regs(s);
      safe_exp(s, p, o, m0, m1);
      wg_fence();
#pragma unroll
      for (int k = 0; k < 4; k++) wgmma_rs_n24_tb(o, p[4 * k], p[4 * k + 1], p[4 * k + 2], p[4 * k + 3], dV + k * 48, 1);
      wg_commit();
      wg_wait<0>();
      fence_regs(o);
      dK += 128;
      dV += 192;
    }
  }
  fence_regs(o);
  const float r0 = 1.0f / o[8], r1 = 1.0f / o[10];
  outp[0] = pack_bf16(o[0] * r0, o[1] * r0);
  outp[1] = pack_bf16(o[2] * r1, o[3] * r1);
  outp[2] = pack_bf16(o[4] * r0, o[5] * r0);
  outp[3] = pack_bf16(o[6] * r1, o[7] * r1);
}

__device__ __forceinline__ void linear_attn_cta(uint8_t* smem_raw, uint32_t sbase, const CUtensorMap* mo16, int cta) {
  const int warp = threadIdx.x >> 5, lane = threadIdx.x & 31;
  float* red = reinterpret_cast<float*>(smem_raw + (sbase - smem_u32(smem_raw)) + 131072);
  {
    const float* src = g_kvpart + (size_t)cta * 8 * 384;
    float sum[6];
#pragma unroll
    for (int i = 0; i < 6; i++) sum[i] = 0.f;
#pragma unroll
    for (int r = 0; r < 16; r++) {
#pragma unroll
      for (int i = 0; i < 6; i++) sum[i] += src[(size_t)r * NH * 384 + threadIdx.x + i * 512];
    }
#pragma unroll
    for (int i = 0; i < 6; i++) red[threadIdx.x + i * 512] = round_bf16(sum[i]);
  }
  __syncthreads();
  uint32_t bf[8][6];
  {
    const int g = lane >> 2, t = lane & 3;
#pragma unroll
    for (int h = 0; h < 8; h++) {
#pragma unroll
      for (int f = 0; f < 6; f++) {
        const int blk = f >> 1, half = f & 1;
        const int e = (blk == 2) ? 0 : g;
        const int d = 2 * t + 8 * half;
        const int base = h * 384 + (blk * 4 + half * 2 + (e & 1)) * 32 + (e >> 1);
        bf[h][f] = pack_bf16(red[base + (d & 7) * 4], red[base + ((d + 1) & 7) * 4]);
      }
    }
  }
  const uint32_t stg = sbase + warp * 8192;
#pragma unroll 1
  for (int rb = 0; rb < 8; rb++) {
    const int blk16 = rb * 16 + warp;
    const uint4* qp = g_qfrag + ((size_t)(NH + cta * 8) * 32 + (blk16 >> 2)) * 128 + (blk16 & 3) * 32 + lane;
    uint4 q[8];
#pragma unroll
    for (int h = 0; h < 8; h++) q[h] = qp[h * 32 * 128];
    const uint32_t buf = stg + (rb & 1) * 4096;
    if (rb >= 2) {
      if (lane == 0) asm volatile("cp.async.bulk.wait_group.read 1;" ::: "memory");
      __syncwarp();
    }
#pragma unroll
    for (int h = 0; h < 8; h++) {
      float n0[4] = {0, 0, 0, 0}, n1[4] = {0, 0, 0, 0}, dn[4] = {0, 0, 0, 0};
      hmma(n0, q[h].x, q[h].y, q[h].z, q[h].w, bf[h][0], bf[h][1]);
      hmma(n1, q[h].x, q[h].y, q[h].z, q[h].w, bf[h][2], bf[h][3]);
      hmma(dn, q[h].x, q[h].y, q[h].z, q[h].w, bf[h][4], bf[h][5]);
      const float d0 = round_bf16(round_bf16(dn[0]) + 1e-6f), d1 = round_bf16(round_bf16(dn[2]) + 1e-6f);
      const uint32_t r0 = pack_bf16(__fdividef(round_bf16(n0[0]), d0), __fdividef(round_bf16(n0[1]), d0));
      const uint32_t r1 = pack_bf16(__fdividef(round_bf16(n0[2]), d1), __fdividef(round_bf16(n0[3]), d1));
      const uint32_t r2 = pack_bf16(__fdividef(round_bf16(n1[0]), d0), __fdividef(round_bf16(n1[1]), d0));
      const uint32_t r3 = pack_bf16(__fdividef(round_bf16(n1[2]), d1), __fdividef(round_bf16(n1[3]), d1));
      const int row = lane & 15;
      const int chunk = (h & 3) * 2 + (lane >> 4);
      const uint32_t addr = buf + (h >> 2) * 2048 + row * 128 + ((chunk ^ (row & 7)) << 4);
      asm volatile("stmatrix.sync.aligned.m8n8.x4.shared.b16 [%0], {%1,%2,%3,%4};" ::"r"(addr), "r"(r0), "r"(r1), "r"(r2), "r"(r3)
                   : "memory");
    }
    fence_proxy_async();
    __syncwarp();
    if (lane == 0) {
      tma_store_2d(mo16, buf, cta * 128, blk16 * 16);
      tma_store_2d(mo16, buf + 2048, cta * 128 + 64, blk16 * 16);
      asm volatile("cp.async.bulk.commit_group;" ::: "memory");
    }
  }
  if (lane == 0) asm volatile("cp.async.bulk.wait_group 0;" ::: "memory");
}

__global__ void __launch_bounds__(512, 1) attn_kernel(const __grid_constant__ CUtensorMap mo16) {
  extern __shared__ uint8_t smem_raw[];
  const uint32_t sbase = (smem_u32(smem_raw) + 1023) & ~1023u;
  const uint32_t bar = sbase + KV_HEAD_BYTES;
  if (threadIdx.x == 0) { PROF_G(1, 30); PROF_T(1, 0); }
  if (threadIdx.x == 0) {
    for (int i = 0; i < 4; i++) mbar_init(bar + 8 * i, 2);
    fence_barrier_init();
    fence_proxy_async();
  }
  __syncthreads();
  cluster_sync_relaxed();
  if (threadIdx.x == 0) PROF_T(1, 6);
  pdl_launch_dependents();
  pdl_wait();
  if (threadIdx.x == 0) { PROF_T(1, 7); PROF_G(1, 29); }
  if (blockIdx.x >= 128) {
    linear_attn_cta(smem_raw, sbase, &mo16, blockIdx.x - 128);
    if (threadIdx.x == 0) { PROF_T(1, 5); PROF_G(1, 31); }
    return;
  }
  const int head = blockIdx.x >> 2, qb = blockIdx.x & 3;
  if ((threadIdx.x & 63) == 0) {
    const uint8_t* img = reinterpret_cast<const uint8_t*>(g_kv) + (size_t)head * KV_HEAD_BYTES;
    const int half = blockIdx.x & 1;
    const int piece = threadIdx.x >> 6;
    const int g = piece >> 1, isv = piece & 1;
    const int e0 = g == 0 ? 0 : (isv ? 256 : 320) + (g - 1) * 512;
    const int e1 = g == 3 ? 2048 : (isv ? 256 : 320) + g * 512;
    const int bytes = (e1 - e0) * (isv ? 48 : 32);
    const int off = (isv ? KV_K_BYTES + e0 * 48 : e0 * 32) + half * (bytes / 2);
    mbar_expect_tx(bar + 8 * g, bytes);
    bulk_load_mc(sbase + off, img + off, bytes / 2, bar + 8 * g, (uint16_t)3);
  }
  const int lane = threadIdx.x & 31;
  bool safe_path;
  {
    float4 n = make_float4(0.f, 0.f, 0.f, 0.f);
    if (lane < 16) n = *reinterpret_cast<const float4*>(&g_nrm[(head * 16 + lane) * 4]);
    uint32_t qm = ((lane >> 2) == qb) ? __float_as_uint(n.x) : 0u;
    qm = __reduce_max_sync(0xffffffffu, qm);
    const uint32_t km = __reduce_max_sync(0xffffffffu, __float_as_uint(n.y));
    const uint32_t vm = __reduce_max_sync(0xffffffffu, __float_as_uint(n.z));
    const float b2 = __uint_as_float(qm) * (QSCALE * QSCALE) * __uint_as_float(km) * 1.02f;
    const float vmax = __uint_as_float(vm);
    const bool ok = (b2 <= 21.5f * 21.5f) && (vmax <= 1.0e24f) && (vmax >= 1.0e-18f || vmax == 0.f);
    safe_path = !ok;
  }
  const int wg = threadIdx.x >> 7, warp = (threadIdx.x >> 5) & 3;
  uint32_t zero;
  asm volatile("mov.u32 %0, %%smid;" : "=r"(zero));
  zero >>= 16;
  const ExpC ec{0x3C003C00u + zero, 0x00070000u + zero, 7u + zero, (ATT_DEG == 3 ? 0x2cfd2cfdu : 0x35623562u) + zero};
  const uint64_t dK = mkdesc(sbase, 128, 256, 0);
  const uint64_t dV = mkdesc(sbase + KV_K_BYTES, 384, 128, 0);
  uint4 qnext = g_qfrag[(head * 32 + qb * 8 + wg * 2) * 128 + (threadIdx.x & 127)];
#pragma unroll 1
  for (int t = 0; t < 2; t++) {
    const int tile64 = qb * 8 + wg * 2 + t;
    const uint4 qf = qnext;
    if (t == 0) qnext = g_qfrag[(head * 32 + tile64 + 1) * 128 + (threadIdx.x & 127)];
    uint32_t r[4];
    if (threadIdx.x == 0) PROF_T(1, 1 + t);
    if (!safe_path) attn_tile<false>(dK, dV, bar, qf, ec, r);
    else attn_tile<true>(dK, dV, bar, qf, ec, r);
    store_o(g_o + (size_t)S_LEN * DM, tile64 * 64 + warp * 16, head, lane, r);
  }
  if (threadIdx.x == 0) { PROF_T(1, 5); PROF_G(1, 31); }
}

constexpr int K3_STAGES = 5;
constexpr int K3_W_BYTES = 8 * 16384;
constexpr int K3_BAR_OFF = K3_W_BYTES + K3_STAGES * 16384;
constexpr int K3_SMEM = K3_BAR_OFF + 256 + 1024;

__global__ void __launch_bounds__(288, 1)
out_gemm_kernel(const __grid_constant__ CUtensorMap mo, const __grid_constant__ CUtensorMap mwA,
                const __grid_constant__ CUtensorMap mwB, const __grid_constant__ CUtensorMap mout) {
  extern __shared__ uint8_t smem_raw[];
  const uint32_t sbase = (smem_u32(smem_raw) + 1023) & ~1023u;
  const uint32_t bar_full = sbase + K3_BAR_OFF;
  const uint32_t bar_empty = bar_full + 8 * K3_STAGES;
  const uint32_t bar_w = bar_empty + 8 * K3_STAGES;
  const int branch = blockIdx.x >> 6;
  const int rt = (blockIdx.x & 63) >> 2;
  const int ct = blockIdx.x & 3;
  const int warp = threadIdx.x >> 5;
  if (threadIdx.x == 0) { PROF_G(2, 30); PROF_T(2, 0); }
  if (threadIdx.x == 256) {
    const CUtensorMap* mw = branch ? &mwB : &mwA;
    asm volatile("prefetch.tensormap [%0];" ::"l"(mw) : "memory");
    asm volatile("prefetch.tensormap [%0];" ::"l"(&mo) : "memory");
    asm volatile("prefetch.tensormap [%0];" ::"l"(&mout) : "memory");
    for (int i = 0; i < K3_STAGES; i++) {
      mbar_init(bar_full + 8 * i, 1);
      mbar_init(bar_empty + 8 * i, 2);
    }
    for (int i = 0; i < 8; i++) mbar_init(bar_w + 8 * i, 1);
    fence_barrier_init();
    fence_proxy_async();
    for (int kb = 0; kb < 8; kb++) {
      mbar_expect_tx(bar_w + 8 * kb, 16384);
      tma_load_2d(sbase + kb * 16384, mw, ct * 128, kb * 64, bar_w + 8 * kb);
      tma_load_2d(sbase + kb * 16384 + 8192, mw, ct * 128 + 64, kb * 64, bar_w + 8 * kb);
    }
  }
  __syncthreads();
  if (warp == 8) {
    if ((threadIdx.x & 31) == 0) {
      pdl_wait();
      PROF_T(2, 1);
      for (int kb = 0; kb < 8; kb++) {
        const int s = kb % K3_STAGES;
        if (kb >= K3_STAGES) mbar_wait(bar_empty + 8 * s, ((kb / K3_STAGES) - 1) & 1);
        mbar_expect_tx(bar_full + 8 * s, 16384);
        tma_load_2d(sbase + K3_W_BYTES + s * 16384, &mo, kb * 64, branch * S_LEN + rt * 128, bar_full + 8 * s);
      }
    }
  } else {
    const int wg = warp >> 2;
    float acc[64];
    for (int kb = 0; kb < 8; kb++) {
      const int s = kb % K3_STAGES;
      mbar_wait(bar_w + 8 * kb, 0);
      mbar_wait(bar_full + 8 * s, (kb / K3_STAGES) & 1);
      if (threadIdx.x == 0) PROF_T(2, 2 + kb);
      const uint64_t dA = mkdesc(sbase + K3_W_BYTES + s * 16384 + wg * 8192, 16, 1024, 1);
      const uint64_t dB = mkdesc(sbase + kb * 16384, 8192, 1024, 1);
      wg_fence();
#pragma unroll
      for (int k = 0; k < 4; k++) wgmma_ss_n128_tb(acc, dA + k * 2, dB + k * 128, (kb | k) != 0);
      wg_commit();
      if (kb > 0) {
        wg_wait<1>();
        if ((threadIdx.x & 127) == 0) mbar_arrive(bar_empty + 8 * ((kb - 1) % K3_STAGES));
      }
    }
    wg_wait<0>();
    fence_regs(acc);
    if (threadIdx.x == 0) PROF_T(2, 10);
    const uint32_t stg = sbase + K3_W_BYTES + wg * 8192;
    asm volatile("bar.sync 1, 256;" ::: "memory");
    const int lane = threadIdx.x & 31;
    const int rloc = (warp & 3) * 16 + (lane & 15);
#pragma unroll
    for (int c16 = 0; c16 < 8; c16++) {
      const float* a = &acc[c16 * 8];
      const uint32_t r0 = pack_bf16(a[0], a[1]), r1 = pack_bf16(a[2], a[3]), r2 = pack_bf16(a[4], a[5]), r3 = pack_bf16(a[6], a[7]);
      const int chunk = (c16 & 3) * 2 + (lane >> 4);
      const uint32_t addr = stg + (c16 >> 2) * 16384 + rloc * 128 + ((chunk ^ (rloc & 7)) << 4);
      asm volatile("stmatrix.sync.aligned.m8n8.x4.shared.b16 [%0], {%1,%2,%3,%4};" ::"r"(addr), "r"(r0), "r"(r1), "r"(r2), "r"(r3)
                   : "memory");
    }
    fence_proxy_async();
    asm volatile("bar.sync %0, 128;" ::"r"(2 + wg) : "memory");
    if ((threadIdx.x & 127) == 0) {
      tma_store_2d(&mout, stg, branch * DM + ct * 128, rt * 128 + wg * 64);
      tma_store_2d(&mout, stg + 16384, branch * DM + ct * 128 + 64, rt * 128 + wg * 64);
      asm volatile("cp.async.bulk.commit_group;" ::: "memory");
      asm volatile("cp.async.bulk.wait_group.read 0;" ::: "memory");
      if (threadIdx.x == 0) { PROF_T(2, 12); PROF_G(2, 31); }
    }
  }
}

typedef CUresult (*EncodeFn)(CUtensorMap*, CUtensorMapDataType, cuuint32_t, void*, const cuuint64_t*, const cuuint64_t*,
                             const cuuint32_t*, const cuuint32_t*, CUtensorMapInterleave, CUtensorMapSwizzle,
                             CUtensorMapL2promotion, CUtensorMapFloatOOBfill);

void make_map(EncodeFn enc, CUtensorMap* m, const void* ptr, uint64_t inner, uint64_t outer, uint32_t box_inner, uint32_t box_outer) {
  cuuint64_t dims[2] = {inner, outer};
  cuuint64_t strides[1] = {inner * 2};
  cuuint32_t box[2] = {box_inner, box_outer};
  cuuint32_t es[2] = {1, 1};
  enc(m, CU_TENSOR_MAP_DATA_TYPE_BFLOAT16, 2, const_cast<void*>(ptr), dims, strides, box, es, CU_TENSOR_MAP_INTERLEAVE_NONE,
      CU_TENSOR_MAP_SWIZZLE_128B, CU_TENSOR_MAP_L2_PROMOTION_L2_256B, CU_TENSOR_MAP_FLOAT_OOB_FILL_NONE);
}

struct HostState {
  bool init;
  const void* key[7];
  CUtensorMap mxA, mxB, mwA, mwB, mo, mo16, mwoA, mwoB, mout;
};
HostState g_hs;

}

extern "C" void kernel_launch(void* const* d_in, const int* in_sizes, int n_in, void* d_out, int out_size) {
  (void)in_sizes; (void)n_in; (void)out_size;
  HostState& hs = g_hs;
  bool same = hs.init && hs.key[6] == d_out;
  for (int i = 0; i < 6 && same; i++) same = hs.key[i] == d_in[i];
  if (!same) {
    void* fn = nullptr;
    cudaDriverEntryPointQueryResult qr;
    cudaGetDriverEntryPoint("cuTensorMapEncodeTiled", &fn, cudaEnableDefault, &qr);
    EncodeFn enc = (EncodeFn)fn;
    void* go = nullptr;
    cudaGetSymbolAddress(&go, g_o);
    make_map(enc, &hs.mxA, d_in[0], 512, 2048, 64, 128);
    make_map(enc, &hs.mwA, d_in[1], 1536, 512, 64, 32);
    make_map(enc, &hs.mwoA, d_in[2], 512, 512, 64, 64);
    make_map(enc, &hs.mxB, d_in[3], 512, 2048, 64, 128);
    make_map(enc, &hs.mwB, d_in[4], 1536, 512, 64, 32);
    make_map(enc, &hs.mwoB, d_in[5], 512, 512, 64, 64);
    make_map(enc, &hs.mo, go, 512, 4096, 64, 128);
    make_map(enc, &hs.mo16, go, 512, 4096, 64, 16);
    make_map(enc, &hs.mout, d_out, 1024, 2048, 64, 64);
    cudaFuncSetAttribute(qkv_gemm_kernel, cudaFuncAttributeMaxDynamicSharedMemorySize, K1_SMEM);
    cudaFuncSetAttribute(attn_kernel, cudaFuncAttributeMaxDynamicSharedMemorySize, K2_SMEM);
    cudaFuncSetAttribute(out_gemm_kernel, cudaFuncAttributeMaxDynamicSharedMemorySize, K3_SMEM);
    for (int i = 0; i < 6; i++) hs.key[i] = d_in[i];
    hs.key[6] = d_out;
    hs.init = true;
  }
  cudaStream_t st = cudaStreamPerThread;
  {
    cudaLaunchConfig_t cfg = {};
    cfg.gridDim = dim3(128);
    cfg.blockDim = dim3(384);
    cfg.dynamicSmemBytes = K1_SMEM;
    cfg.stream = st;
    cudaLaunchAttribute at[1];
    at[0].id = cudaLaunchAttributeClusterDimension;
    at[0].val.clusterDim.x = 2;
    at[0].val.clusterDim.y = 1;
    at[0].val.clusterDim.z = 1;
    cfg.attrs = at;
    cfg.numAttrs = 1;
    cudaLaunchKernelEx(&cfg, qkv_gemm_kernel, hs.mxA, hs.mxB, hs.mwA, hs.mwB);
  }
  {
    cudaLaunchConfig_t cfg = {};
    cfg.gridDim = dim3(132);
    cfg.blockDim = dim3(512);
    cfg.dynamicSmemBytes = K2_SMEM;
    cfg.stream = st;
    cudaLaunchAttribute at[1];
    at[0].id = cudaLaunchAttributeProgrammaticStreamSerialization;
    at[0].val.programmaticStreamSerializationAllowed = 1;
    cudaLaunchAttribute at2[2];
    at2[0] = at[0];
    at2[1].id = cudaLaunchAttributeClusterDimension;
    at2[1].val.clusterDim.x = 2;
    at2[1].val.clusterDim.y = 1;
    at2[1].val.clusterDim.z = 1;
    cfg.attrs = at2;
    cfg.numAttrs = 2;
    cudaLaunchKernelEx(&cfg, attn_kernel, hs.mo16);
    cfg.attrs = at;
    cfg.numAttrs = 1;
    cfg.gridDim = dim3(128);
    cfg.blockDim = dim3(288);
    cfg.dynamicSmemBytes = K3_SMEM;
    cudaLaunchKernelEx(&cfg, out_gemm_kernel, hs.mo, hs.mwoA, hs.mwoB, hs.mout);
  }
}
```

```cpp
#include <cuda_runtime.h>
#include <cuda_bf16.h>
#include <cuda.h>
#include <stdint.h>

namespace {

constexpr int S_LEN = 2048;
constexpr int DM = 512;
constexpr int NH = 32;

constexpr int KV_K_BYTES = 65536;
constexpr int KV_HEAD_BYTES = KV_K_BYTES + 98304;
__device__ uint4 g_qfrag[2 * NH * 32 * 128];
__device__ uint4 g_kv[NH * KV_HEAD_BYTES / 16];
__device__ float g_kvpart[16 * NH * 384];
__device__ float g_nrm[NH * 16 * 4];
__device__ __nv_bfloat16 g_o[2 * S_LEN * DM];

#define g_prof_set(k, i, v)
#define g_prof_dummy(i) true
#define PROF_T(k, i) do {} while (0)
#define PROF_G(k, i) do {} while (0)
__device__ __forceinline__ uint32_t smem_u32(const void* p) { return (uint32_t)__cvta_generic_to_shared(p); }
__device__ __forceinline__ void mbar_init(uint32_t bar, int cnt) {
  asm volatile("mbarrier.init.shared::cta.b64 [%0], %1;" ::"r"(bar), "r"(cnt) : "memory");
}
__device__ __forceinline__ void mbar_expect_tx(uint32_t bar, uint32_t bytes) {
  asm volatile("mbarrier.arrive.expect_tx.shared::cta.b64 _, [%0], %1;" ::"r"(bar), "r"(bytes) : "memory");
}
__device__ __forceinline__ void mbar_arrive(uint32_t bar) {
  asm volatile("mbarrier.arrive.shared::cta.b64 _, [%0];" ::"r"(bar) : "memory");
}
__device__ __forceinline__ void mbar_arrive_cluster(uint32_t bar, uint32_t cta) {
  asm volatile(
      "{\n.reg .b32 ra;\nmapa.shared::cluster.u32 ra, %0, %1;\n"
      "mbarrier.arrive.shared::cluster.b64 _, [ra];\n}" ::"r"(bar), "r"(cta) : "memory");
}
__device__ __forceinline__ void mbar_wait(uint32_t bar, uint32_t parity) {
  asm volatile(
      "{\n.reg .pred p;\n"
      "WAIT_LOOP:\n"
      "mbarrier.try_wait.parity.shared::cta.b64 p, [%0], %1, 0x989680;\n"
      "@p bra WAIT_DONE;\n"
      "bra WAIT_LOOP;\n"
      "WAIT_DONE:\n}" ::"r"(bar), "r"(parity) : "memory");
}
__device__ __forceinline__ void mbar_wait_cluster(uint32_t bar, uint32_t parity) {
  asm volatile(
      "{\n.reg .pred p;\n"
      "WAIT_LOOP:\n"
      "mbarrier.try_wait.parity.acquire.cluster.shared::cta.b64 p, [%0], %1, 0x989680;\n"
      "@p bra WAIT_DONE;\n"
      "bra WAIT_LOOP;\n"
      "WAIT_DONE:\n}" ::"r"(bar), "r"(parity) : "memory");
}
__device__ __forceinline__ void fence_barrier_init() {
  asm volatile("fence.mbarrier_init.release.cluster;" ::: "memory");
}
__device__ __forceinline__ void fence_proxy_async() { asm volatile("fence.proxy.async.shared::cta;" ::: "memory"); }
__device__ __forceinline__ void cluster_sync_relaxed() {
  asm volatile("barrier.cluster.arrive.relaxed.aligned;\nbarrier.cluster.wait.aligned;" ::: "memory");
}
__device__ __forceinline__ void tma_load_2d(uint32_t dst, const CUtensorMap* m, int x, int y, uint32_t bar) {
  asm volatile(
      "cp.async.bulk.tensor.2d.shared::cluster.global.mbarrier::complete_tx::bytes [%0], [%1, {%3, %4}], [%2];" ::"r"(dst),
      "l"(m), "r"(bar), "r"(x), "r"(y)
      : "memory");
}
__device__ __forceinline__ void tma_load_2d_mc(uint32_t dst, const CUtensorMap* m, int x, int y, uint32_t bar, uint16_t mask) {
  asm volatile(
      "cp.async.bulk.tensor.2d.shared::cluster.global.mbarrier::complete_tx::bytes.multicast::cluster [%0], [%1, {%3, %4}], "
      "[%2], %5;" ::"r"(dst),
      "l"(m), "r"(bar), "r"(x), "r"(y), "h"(mask)
      : "memory");
}
__device__ __forceinline__ void tma_store_2d(const CUtensorMap* m, uint32_t src, int x, int y) {
  asm volatile("cp.async.bulk.tensor.2d.global.shared::cta.bulk_group [%0, {%2, %3}], [%1];" ::"l"(m), "r"(src), "r"(x),
               "r"(y)
               : "memory");
}
__device__ __forceinline__ void bulk_load(uint32_t dst, const void* src, uint32_t bytes, uint32_t bar) {
  asm volatile("cp.async.bulk.shared::cluster.global.mbarrier::complete_tx::bytes [%0], [%1], %2, [%3];" ::"r"(dst),
               "l"(src), "r"(bytes), "r"(bar)
               : "memory");
}
__device__ __forceinline__ void bulk_load_mc(uint32_t dst, const void* src, uint32_t bytes, uint32_t bar, uint16_t mask) {
  asm volatile("cp.async.bulk.shared::cluster.global.mbarrier::complete_tx::bytes.multicast::cluster [%0], [%1], %2, [%3], %4;" ::"r"(dst),
               "l"(src), "r"(bytes), "r"(bar), "h"(mask)
               : "memory");
}
__device__ __forceinline__ void pdl_launch_dependents() { asm volatile("griddepcontrol.launch_dependents;" ::: "memory"); }
__device__ __forceinline__ void pdl_wait() { asm volatile("griddepcontrol.wait;" ::: "memory"); }
__device__ __forceinline__ void wg_fence() { asm volatile("wgmma.fence.sync.aligned;" ::: "memory"); }
__device__ __forceinline__ void wg_commit() { asm volatile("wgmma.commit_group.sync.aligned;" ::: "memory"); }
template <int N>
__device__ __forceinline__ void wg_wait() {
  asm volatile("wgmma.wait_group.sync.aligned %0;" ::"n"(N) : "memory");
}
template <int M>
__device__ __forceinline__ void fence_regs(float (&r)[M]) {
#pragma unroll
  for (int i = 0; i < M; i++) asm volatile("" : "+f"(r[i])::"memory");
}
__device__ __forceinline__ uint64_t mkdesc(uint32_t addr, uint32_t lbo, uint32_t sbo, uint32_t layout) {
  return (uint64_t)((addr & 0x3FFFF) >> 4) | ((uint64_t)(lbo >> 4) << 16) | ((uint64_t)(sbo >> 4) << 32) |
         ((uint64_t)layout << 62);
}
__device__ __forceinline__ uint32_t pack_bf16(float lo, float hi) {
  uint32_t r;
  asm("cvt.rn.bf16x2.f32 %0, %1, %2;" : "=r"(r) : "f"(hi), "f"(lo));
  return r;
}
__device__ __forceinline__ float bf_lo(uint32_t v) { return __uint_as_float(v << 16); }
__device__ __forceinline__ float bf_hi(uint32_t v) { return __uint_as_float(v & 0xFFFF0000u); }
__device__ __forceinline__ float round_bf16(float x) { return bf_lo(pack_bf16(x, 0.f)); }
__device__ __forceinline__ float ex2f(float x) {
  float y;
  asm("ex2.approx.ftz.f32 %0, %1;" : "=f"(y) : "f"(x));
  return y;
}

__device__ __forceinline__ void wgmma_rs_n24_tb(float (&d)[12], uint32_t a0, uint32_t a1, uint32_t a2, uint32_t a3, uint64_t descB, int scaleD) {
  asm volatile("{\n.reg .pred p;\nsetp.ne.b32 p, %17, 0;\n"
    "wgmma.mma_async.sync.aligned.m64n24k16.f32.bf16.bf16 "
    "{%0, %1, %2, %3, %4, %5, %6, %7, %8, %9, %10, %11}, {%12, %13, %14, %15}, %16, p, 1, 1, 1;\n}\n"
    : "+f"(d[0]), "+f"(d[1]), "+f"(d[2]), "+f"(d[3]), "+f"(d[4]), "+f"(d[5]), "+f"(d[6]), "+f"(d[7]),
      "+f"(d[8]), "+f"(d[9]), "+f"(d[10]), "+f"(d[11])
    : "r"(a0), "r"(a1), "r"(a2), "r"(a3), "l"(descB), "r"(scaleD));
}
__device__ __forceinline__ void wgmma_rs_n64_z(float (&d)[32], uint32_t a0, uint32_t a1, uint32_t a2, uint32_t a3, uint64_t descB) {
  asm volatile("{\n.reg .pred p;\nsetp.ne.b32 p, %37, 0;\n"
    "wgmma.mma_async.sync.aligned.m64n64k16.f32.bf16.bf16 "
    "{%0, %1, %2, %3, %4, %5, %6, %7, %8, %9, %10, %11, %12, %13, %14, %15, %16, %17, %18, %19, %20, %21, %22, %23, %24, %25, %26, %27, %28, %29, %30, %31}, {%32, %33, %34, %35}, %36, p, 1, 1, 0;\n}\n"
    : "=f"(d[0]), "=f"(d[1]), "=f"(d[2]), "=f"(d[3]), "=f"(d[4]), "=f"(d[5]), "=f"(d[6]), "=f"(d[7]),
      "=f"(d[8]), "=f"(d[9]), "=f"(d[10]), "=f"(d[11]), "=f"(d[12]), "=f"(d[13]), "=f"(d[14]), "=f"(d[15]),
      "=f"(d[16]), "=f"(d[17]), "=f"(d[18]), "=f"(d[19]), "=f"(d[20]), "=f"(d[21]), "=f"(d[22]), "=f"(d[23]),
      "=f"(d[24]), "=f"(d[25]), "=f"(d[26]), "=f"(d[27]), "=f"(d[28]), "=f"(d[29]), "=f"(d[30]), "=f"(d[31])
    : "r"(a0), "r"(a1), "r"(a2), "r"(a3), "l"(descB), "n"(0));
}
__device__ __forceinline__ void wgmma_ss_n128_tb(float (&d)[64], uint64_t descA, uint64_t descB, int scaleD) {
  asm volatile("{\n.reg .pred p;\nsetp.ne.b32 p, %66, 0;\n"
    "wgmma.mma_async.sync.aligned.m64n128k16.f32.bf16.bf16 "
    "{%0, %1, %2, %3, %4, %5, %6, %7, %8, %9, %10, %11, %12, %13, %14, %15, %16, %17, %18, %19, %20, %21, %22, %23, %24, %25, %26, %27, %28, %29, %30, %31, %32, %33, %34, %35, %36, %37, %38, %39, %40, %41, %42, %43, %44, %45, %46, %47, %48, %49, %50, %51, %52, %53, %54, %55, %56, %57, %58, %59, %60, %61, %62, %63}, %64, %65, p, 1, 1, 0, 1;\n}\n"
    : "+f"(d[0]), "+f"(d[1]), "+f"(d[2]), "+f"(d[3]), "+f"(d[4]), "+f"(d[5]), "+f"(d[6]), "+f"(d[7]),
      "+f"(d[8]), "+f"(d[9]), "+f"(d[10]), "+f"(d[11]), "+f"(d[12]), "+f"(d[13]), "+f"(d[14]), "+f"(d[15]),
      "+f"(d[16]), "+f"(d[17]), "+f"(d[18]), "+f"(d[19]), "+f"(d[20]), "+f"(d[21]), "+f"(d[22]), "+f"(d[23]),
      "+f"(d[24]), "+f"(d[25]), "+f"(d[26]), "+f"(d[27]), "+f"(d[28]), "+f"(d[29]), "+f"(d[30]), "+f"(d[31]),
      "+f"(d[32]), "+f"(d[33]), "+f"(d[34]), "+f"(d[35]), "+f"(d[36]), "+f"(d[37]), "+f"(d[38]), "+f"(d[39]),
      "+f"(d[40]), "+f"(d[41]), "+f"(d[42]), "+f"(d[43]), "+f"(d[44]), "+f"(d[45]), "+f"(d[46]), "+f"(d[47]),
      "+f"(d[48]), "+f"(d[49]), "+f"(d[50]), "+f"(d[51]), "+f"(d[52]), "+f"(d[53]), "+f"(d[54]), "+f"(d[55]),
      "+f"(d[56]), "+f"(d[57]), "+f"(d[58]), "+f"(d[59]), "+f"(d[60]), "+f"(d[61]), "+f"(d[62]), "+f"(d[63])
    : "l"(descA), "l"(descB), "r"(scaleD));
}
__device__ __forceinline__ void wgmma_ss_n192_tb(float (&d)[96], uint64_t descA, uint64_t descB, int scaleD) {
  asm volatile("{\n.reg .pred p;\nsetp.ne.b32 p, %98, 0;\n"
    "wgmma.mma_async.sync.aligned.m64n192k16.f32.bf16.bf16 "
    "{%0, %1, %2, %3, %4, %5, %6, %7, %8, %9, %10, %11, %12, %13, %14, %15, %16, %17, %18, %19, %20, %21, %22, %23, %24, %25, %26, %27, %28, %29, %30, %31, %32, %33, %34, %35, %36, %37, %38, %39, %40, %41, %42, %43, %44, %45, %46, %47, %48, %49, %50, %51, %52, %53, %54, %55, %56, %57, %58, %59, %60, %61, %62, %63, %64, %65, %66, %67, %68, %69, %70, %71, %72, %73, %74, %75, %76, %77, %78, %79, %80, %81, %82, %83, %84, %85, %86, %87, %88, %89, %90, %91, %92, %93, %94, %95}, %96, %97, p, 1, 1, 0, 1;\n}\n"
    : "+f"(d[0]), "+f"(d[1]), "+f"(d[2]), "+f"(d[3]), "+f"(d[4]), "+f"(d[5]), "+f"(d[6]), "+f"(d[7]),
      "+f"(d[8]), "+f"(d[9]), "+f"(d[10]), "+f"(d[11]), "+f"(d[12]), "+f"(d[13]), "+f"(d[14]), "+f"(d[15]),
      "+f"(d[16]), "+f"(d[17]), "+f"(d[18]), "+f"(d[19]), "+f"(d[20]), "+f"(d[21]), "+f"(d[22]), "+f"(d[23]),
      "+f"(d[24]), "+f"(d[25]), "+f"(d[26]), "+f"(d[27]), "+f"(d[28]), "+f"(d[29]), "+f"(d[30]), "+f"(d[31]),
      "+f"(d[32]), "+f"(d[33]), "+f"(d[34]), "+f"(d[35]), "+f"(d[36]), "+f"(d[37]), "+f"(d[38]), "+f"(d[39]),
      "+f"(d[40]), "+f"(d[41]), "+f"(d[42]), "+f"(d[43]), "+f"(d[44]), "+f"(d[45]), "+f"(d[46]), "+f"(d[47]),
      "+f"(d[48]), "+f"(d[49]), "+f"(d[50]), "+f"(d[51]), "+f"(d[52]), "+f"(d[53]), "+f"(d[54]), "+f"(d[55]),
      "+f"(d[56]), "+f"(d[57]), "+f"(d[58]), "+f"(d[59]), "+f"(d[60]), "+f"(d[61]), "+f"(d[62]), "+f"(d[63]),
      "+f"(d[64]), "+f"(d[65]), "+f"(d[66]), "+f"(d[67]), "+f"(d[68]), "+f"(d[69]), "+f"(d[70]), "+f"(d[71]),
      "+f"(d[72]), "+f"(d[73]), "+f"(d[74]), "+f"(d[75]), "+f"(d[76]), "+f"(d[77]), "+f"(d[78]), "+f"(d[79]),
      "+f"(d[80]), "+f"(d[81]), "+f"(d[82]), "+f"(d[83]), "+f"(d[84]), "+f"(d[85]), "+f"(d[86]), "+f"(d[87]),
      "+f"(d[88]), "+f"(d[89]), "+f"(d[90]), "+f"(d[91]), "+f"(d[92]), "+f"(d[93]), "+f"(d[94]), "+f"(d[95])
    : "l"(descA), "l"(descB), "r"(scaleD));
}

__device__ __forceinline__ void ldsm4t(uint32_t (&b)[4], uint32_t addr) {
  asm volatile("ldmatrix.sync.aligned.m8n8.x4.trans.shared.b16 {%0,%1,%2,%3}, [%4];"
               : "=r"(b[0]), "=r"(b[1]), "=r"(b[2]), "=r"(b[3])
               : "r"(addr));
}
__device__ __forceinline__ void hmma(float (&c)[4], uint32_t a0, uint32_t a1, uint32_t a2, uint32_t a3, uint32_t b0, uint32_t b1) {
  asm("mma.sync.aligned.m16n8k16.row.col.f32.bf16.bf16.f32 {%0,%1,%2,%3}, {%4,%5,%6,%7}, {%8,%9}, {%0,%1,%2,%3};"
      : "+f"(c[0]), "+f"(c[1]), "+f"(c[2]), "+f"(c[3])
      : "r"(a0), "r"(a1), "r"(a2), "r"(a3), "r"(b0), "r"(b1));
}

__device__ __forceinline__ uint32_t movm(uint32_t a) {
  uint32_t d;
  asm volatile("movmatrix.sync.aligned.m8n8.trans.b16 %0, %1;" : "=r"(d) : "r"(a));
  return d;
}

constexpr int K1_STAGES = 4;
constexpr int K1_W_BYTES = 3 * 8192;
constexpr int K1_X_BYTES = 8 * 16384;
constexpr int K1_BAR_OFF = K1_X_BYTES + K1_STAGES * K1_W_BYTES;
constexpr int K1_SMEM = K1_BAR_OFF + 192 + 1024;
constexpr float QSCALE = 0.25f * 1.4426950408889634f;

__device__ __forceinline__ uint32_t phi2(uint32_t t2) {
  uint32_t a2, mask, r2, o2;
  asm("add.rn.bf16x2 %0, %1, %2;" : "=r"(a2) : "r"(t2), "r"(0x3F803F80u));
  const uint32_t e2 = pack_bf16(ex2f(bf_lo(t2) * 1.4426950408889634f), ex2f(bf_hi(t2) * 1.4426950408889634f));
  asm("set.gt.u32.bf16x2 %0, %1, %2;" : "=r"(mask) : "r"(t2), "r"(0u));
  r2 = (a2 & mask) | (e2 & ~mask);
  asm("add.rn.bf16x2 %0, %1, %2;" : "=r"(o2) : "r"(r2), "r"(0x35863586u));
  return o2;
}

#define K1_SLOT_KB(h) ((h) < 4 ? 2 * (h) : 2 * ((h) - 4) + 1)
struct EpiCtx {
  uint4* qf;
  uint32_t* kp;
  uint32_t* vp;
  uint32_t* s_red;
  float* red;
  int lane;
};

template <bool LINEAR, int J, int HH, int PART>
__device__ __forceinline__ void epi_slice(const float (&acc)[96], const EpiCtx& c, uint32_t (&pk)[4], float& vmax) {
  constexpr int h = J * 4 + HH;
  const float* a = &acc[HH * 8];
  const float* k = &acc[32 + HH * 8];
  const float* v = &acc[64 + HH * 8];
  if (!LINEAR) {
    if (PART == 0) {
      c.qf[h * 32 * 128] = make_uint4(pack_bf16(a[0] * QSCALE, a[1] * QSCALE), pack_bf16(a[2] * QSCALE, a[3] * QSCALE),
                                      pack_bf16(a[4] * QSCALE, a[5] * QSCALE), pack_bf16(a[6] * QSCALE, a[7] * QSCALE));
      uint32_t* kh = c.kp + h * (KV_HEAD_BYTES / 4);
      kh[0] = pack_bf16(k[0], k[1]);
      kh[64] = pack_bf16(k[2], k[3]);
      kh[32] = pack_bf16(k[4], k[5]);
      kh[96] = pack_bf16(k[6], k[7]);
      float q0 = a[0] * a[0] + a[1] * a[1] + a[4] * a[4] + a[5] * a[5];
      float q1 = a[2] * a[2] + a[3] * a[3] + a[6] * a[6] + a[7] * a[7];
      float k0 = k[0] * k[0] + k[1] * k[1] + k[4] * k[4] + k[5] * k[5];
      float k1 = k[2] * k[2] + k[3] * k[3] + k[6] * k[6] + k[7] * k[7];
#pragma unroll
      for (int o = 1; o <= 2; o <<= 1) {
        q0 += __shfl_xor_sync(0xffffffffu, q0, o);
        q1 += __shfl_xor_sync(0xffffffffu, q1, o);
        k0 += __shfl_xor_sync(0xffffffffu, k0, o);
        k1 += __shfl_xor_sync(0xffffffffu, k1, o);
      }
      const uint32_t qm = __reduce_max_sync(0xffffffffu, max(__float_as_uint(q0) & 0x7FFFFFFFu, __float_as_uint(q1) & 0x7FFFFFFFu));
      const uint32_t km = __reduce_max_sync(0xffffffffu, max(__float_as_uint(k0) & 0x7FFFFFFFu, __float_as_uint(k1) & 0x7FFFFFFFu));
      if (c.lane == 0) {
        atomicMax(&c.s_red[h * 2 + 0], qm);
        atomicMax(&c.s_red[h * 2 + 1], km);
      }
    } else {
      uint32_t* vh = c.vp + h * (KV_HEAD_BYTES / 4);
      vh[0] = pack_bf16(v[0], v[1]);
      vh[96] = pack_bf16(v[2], v[3]);
      vh[32] = pack_bf16(v[4], v[5]);
      vh[128] = pack_bf16(v[6], v[7]);
      vh[64] = 0x3F803F80u;
      vh[160] = 0x3F803F80u;
#pragma unroll
      for (int i = 0; i < 8; i++) asm("max.NaN.f32 %0, %0, %1;" : "+f"(vmax) : "f"(fabsf(v[i])));
    }
  } else {
    if (PART == 0) {
      c.qf[h * 32 * 128] = make_uint4(phi2(pack_bf16(a[0], a[1])), phi2(pack_bf16(a[2], a[3])), phi2(pack_bf16(a[4], a[5])),
                                      phi2(pack_bf16(a[6], a[7])));
      pk[0] = movm(phi2(pack_bf16(k[0], k[1])));
      pk[2] = movm(phi2(pack_bf16(k[2], k[3])));
      pk[1] = movm(phi2(pack_bf16(k[4], k[5])));
      pk[3] = movm(phi2(pack_bf16(k[6], k[7])));
    } else {
      const uint32_t b0 = movm(pack_bf16(v[0], v[1]));
      const uint32_t b1 = movm(pack_bf16(v[2], v[3]));
      const uint32_t b2 = movm(pack_bf16(v[4], v[5]));
      const uint32_t b3 = movm(pack_bf16(v[6], v[7]));
      float c0[4] = {0, 0, 0, 0}, c1[4] = {0, 0, 0, 0}, c2[4] = {0, 0, 0, 0};
      hmma(c0, pk[0], pk[1], pk[2], pk[3], b0, b1);
      hmma(c1, pk[0], pk[1], pk[2], pk[3], b2, b3);
      hmma(c2, pk[0], pk[1], pk[2], pk[3], 0x3F803F80u, 0x3F803F80u);
      float* slot = c.red + K1_SLOT_KB(h) * 4096;
#pragma unroll
      for (int i = 0; i < 4; i++) {
        slot[i * 32] = c0[i];
        slot[(4 + i) * 32] = c1[i];
        slot[(8 + i) * 32] = c2[i];
      }
    }
  }
}

template <bool LINEAR>
__device__ __forceinline__ void qkv_consumer(uint32_t sbase, uint8_t* smem_gen, uint32_t* s_red, int cp, int rt) {
  const uint32_t bar_full = sbase + K1_BAR_OFF;
  const uint32_t bar_empty = bar_full + 8 * K1_STAGES;
  const int warp = threadIdx.x >> 5;
  const int wg = warp >> 2;
  const int lane = threadIdx.x & 31;
  float acc0[96], acc1[96];
#pragma unroll 1
  for (int kb = 0; kb < 8; kb++) {
    const int s = kb % K1_STAGES;
    mbar_wait(bar_full + 8 * s, (kb / K1_STAGES) & 1);
    if (threadIdx.x == 0) PROF_T(0, 2 + (kb >> 1));
    const uint64_t dA = mkdesc(sbase + kb * 16384 + wg * 8192, 16, 1024, 1);
    const uint64_t dB = mkdesc(sbase + K1_X_BYTES + s * K1_W_BYTES, 8192, 1024, 1);
    wg_fence();
#pragma unroll
    for (int k = 0; k < 4; k++) wgmma_ss_n192_tb(acc0, dA + k * 2, dB + k * 128, (kb | k) != 0);
    wg_commit();
    if (kb > 0) {
      wg_wait<1>();
      if ((threadIdx.x & 127) == 0) {
        const int sp = (kb - 1) % K1_STAGES;
        mbar_arrive_cluster(bar_empty + 8 * sp, 0);
        mbar_arrive_cluster(bar_empty + 8 * sp, 1);
      }
    }
  }
  wg_wait<0>();
  fence_regs(acc0);
  if ((threadIdx.x & 127) == 0) {
    mbar_arrive_cluster(bar_empty + 8 * (7 % K1_STAGES), 0);
    mbar_arrive_cluster(bar_empty + 8 * (7 % K1_STAGES), 1);
  }
  if (threadIdx.x == 0) PROF_T(0, 6);

  EpiCtx c;
  {
    const int row0 = rt * 128 + wg * 64 + (warp & 3) * 16;
    c.qf = g_qfrag + ((size_t)((LINEAR ? NH : 0) + cp * 8) * 32 + (rt * 2 + wg)) * 128 + (threadIdx.x & 127);
    uint32_t* img = reinterpret_cast<uint32_t*>(reinterpret_cast<uint8_t*>(g_kv) + (size_t)(cp * 8) * KV_HEAD_BYTES);
    c.kp = img + (row0 >> 3) * 64 + lane;
    c.vp = img + KV_K_BYTES / 4 + (row0 >> 3) * 96 + lane;
    c.s_red = s_red;
    c.red = reinterpret_cast<float*>(smem_gen + wg * 8192) + (warp & 3) * 384 + lane;
    c.lane = lane;
  }
  uint32_t pk[4];
  float vmax = 0.f;
#define K1_T1_STEP(KB)                                                                           \
  {                                                                                              \
    constexpr int g = 8 + KB;                                                                    \
    constexpr int s = g % K1_STAGES;                                                             \
    mbar_wait(bar_full + 8 * s, (g / K1_STAGES) & 1);                                            \
    const uint64_t dA = mkdesc(sbase + KB * 16384 + wg * 8192, 16, 1024, 1);                     \
    const uint64_t dB = mkdesc(sbase + K1_X_BYTES + s * K1_W_BYTES, 8192, 1024, 1);              \
    wg_fence();                                                                                  \
    _Pragma("unroll") for (int k = 0; k < 4; k++) wgmma_ss_n192_tb(acc1, dA + k * 2, dB + k * 128, (KB | k) != 0); \
    wg_commit();                                                                                 \
    epi_slice<LINEAR, 0, KB / 2, KB & 1>(acc0, c, pk, vmax);                                     \
    wg_wait<0>();                                                                                \
    if (KB + K1_STAGES < 8 && (threadIdx.x & 127) == 0) {                                        \
      mbar_arrive_cluster(bar_empty + 8 * s, 0);                                                 \
      mbar_arrive_cluster(bar_empty + 8 * s, 1);                                                 \
    }                                                                                            \
  }
  K1_T1_STEP(0) K1_T1_STEP(1) K1_T1_STEP(2) K1_T1_STEP(3) K1_T1_STEP(4) K1_T1_STEP(5) K1_T1_STEP(6) K1_T1_STEP(7)
#undef K1_T1_STEP
  fence_regs(acc1);
  if (threadIdx.x == 0) PROF_T(0, 10);
  epi_slice<LINEAR, 1, 0, 0>(acc1, c, pk, vmax);
  epi_slice<LINEAR, 1, 0, 1>(acc1, c, pk, vmax);
  epi_slice<LINEAR, 1, 1, 0>(acc1, c, pk, vmax);
  epi_slice<LINEAR, 1, 1, 1>(acc1, c, pk, vmax);
  epi_slice<LINEAR, 1, 2, 0>(acc1, c, pk, vmax);
  epi_slice<LINEAR, 1, 2, 1>(acc1, c, pk, vmax);
  epi_slice<LINEAR, 1, 3, 0>(acc1, c, pk, vmax);
  epi_slice<LINEAR, 1, 3, 1>(acc1, c, pk, vmax);
  if (!LINEAR) {
    const uint32_t vm = __reduce_max_sync(0xffffffffu, __float_as_uint(vmax) & 0x7FFFFFFFu);
    if (lane == 0) atomicMax(&s_red[16], vm);
    asm volatile("bar.sync 1, 256;" ::: "memory");
    if (threadIdx.x < 8) {
      *reinterpret_cast<float4*>(&g_nrm[((cp * 8 + threadIdx.x) * 16 + rt) * 4]) =
          make_float4(__uint_as_float(s_red[threadIdx.x * 2]), __uint_as_float(s_red[threadIdx.x * 2 + 1]), __uint_as_float(s_red[16]), 0.f);
    }
  } else {
    asm volatile("bar.sync 1, 256;" ::: "memory");
    float* dst = g_kvpart + ((size_t)rt * NH + cp * 8) * 384;
#pragma unroll
    for (int i = 0; i < 12; i++) {
      const int o = threadIdx.x + i * 256;
      const int h = o / 384, e = o - h * 384;
      const float* src = reinterpret_cast<const float*>(smem_gen) + K1_SLOT_KB(h) * 4096 + e;
      float sum = 0.f;
#pragma unroll
      for (int w = 0; w < 8; w++) sum += src[(w >> 2) * 2048 + (w & 3) * 384];
      dst[o] = sum;
    }
  }
}

__global__ void __launch_bounds__(384, 1)
qkv_gemm_kernel(const __grid_constant__ CUtensorMap mxA, const __grid_constant__ CUtensorMap mxB,
                const __grid_constant__ CUtensorMap mwA, const __grid_constant__ CUtensorMap mwB) {
  extern __shared__ uint8_t smem_raw[];
  const uint32_t sbase = (smem_u32(smem_raw) + 1023) & ~1023u;
  uint8_t* smem_gen = smem_raw + (sbase - smem_u32(smem_raw));
  const uint32_t bar_full = sbase + K1_BAR_OFF;
  const uint32_t bar_empty = bar_full + 8 * K1_STAGES;
  uint32_t* s_red = reinterpret_cast<uint32_t*>(smem_gen + K1_BAR_OFF + 64);

  const int rank = blockIdx.x & 1;
  const int pair = blockIdx.x >> 1;
  const int branch = pair >> 5;
  const int rp = (pair & 31) >> 2;
  const int cp = pair & 3;
  const int rt = rp * 2 + rank;
  const int warp = threadIdx.x >> 5;
  if (threadIdx.x == 0) { PROF_G(0, 30); PROF_T(0, 0); }
  const CUtensorMap* mx = branch ? &mxA : &mxB;
  const CUtensorMap* mw = branch ? &mwA : &mwB;

  if (threadIdx.x == 256) {
    asm volatile("prefetch.tensormap [%0];" ::"l"(mx) : "memory");
    asm volatile("prefetch.tensormap [%0];" ::"l"(mw) : "memory");
    for (int i = 0; i < K1_STAGES; i++) {
      mbar_init(bar_full + 8 * i, 1);
      mbar_init(bar_empty + 8 * i, 4);
    }
    fence_barrier_init();
    fence_proxy_async();
    for (int kb = 0; kb < K1_STAGES; kb++) mbar_expect_tx(bar_full + 8 * kb, 16384 + K1_W_BYTES);
    tma_load_2d(sbase, mx, 0, rt * 128, bar_full);
  }
  pdl_launch_dependents();
  if (threadIdx.x < 32) s_red[threadIdx.x] = 0;
  __syncthreads();
  cluster_sync_relaxed();
  if (threadIdx.x == 0) PROF_T(0, 1);

  if (warp >= 8) {
    asm volatile("setmaxnreg.dec.sync.aligned.u32 40;");
    if (threadIdx.x == 256) {
      for (int g = 0; g < 16; g++) {
        const int s = g % K1_STAGES;
        const int kb = g & 7;
        if (g >= K1_STAGES) {
          mbar_wait(bar_empty + 8 * s, ((g / K1_STAGES) - 1) & 1);
          mbar_expect_tx(bar_full + 8 * s, (g < 8 ? 16384 : 0) + K1_W_BYTES);
        }
        if (g > 0 && g < 8) tma_load_2d(sbase + kb * 16384, mx, kb * 64, rt * 128, bar_full + 8 * s);
        const int h0 = cp * 8 + (g >> 3) * 4;
        const uint32_t st = sbase + K1_X_BYTES + s * K1_W_BYTES + rank * 4096;
#pragma unroll
        for (int p = 0; p < 3; p++)
          tma_load_2d_mc(st + p * 8192, mw, p * 512 + h0 * 16, kb * 64 + rank * 32, bar_full + 8 * s, (uint16_t)3);
      }
    }
    __syncwarp();
    cluster_sync_relaxed();
  } else {
    asm volatile("setmaxnreg.inc.sync.aligned.u32 232;");
    if (branch == 0) qkv_consumer<false>(sbase, smem_gen, s_red, cp, rt);
    else qkv_consumer<true>(sbase, smem_gen, s_red, cp, rt);
    if (threadIdx.x == 0) PROF_T(0, 11);
    __syncwarp();
    cluster_sync_relaxed();
    if (threadIdx.x == 0) { PROF_T(0, 12); PROF_G(0, 31); }
  }
}

constexpr int K2_SMEM = KV_HEAD_BYTES + 1024 + 256;

#define ATT_NPOLY 18
#define ATT_CH 8
#define ATT_D 1
#define ATT_PIN 1
#define ATT_GM 1
#define ATT_DEG 2
struct ExpC {
  uint32_t k3c00, kmask, seven, c3;
};
__device__ __forceinline__ uint32_t hfma2(uint32_t a, uint32_t b, uint32_t c) {
  uint32_t r;
  asm("fma.rn.f16x2 %0, %1, %2, %3;" : "=r"(r) : "r"(a), "r"(b), "r"(c));
  return r;
}
__device__ __forceinline__ uint32_t exp2_poly_pair(float t0, float t1, const ExpC& c) {
  uint32_t u;
  asm("prmt.b32 %0, %1, %2, 0x5410;" : "=r"(u) : "r"(__float_as_uint(t0)), "r"(__float_as_uint(t1)));
  uint32_t m;
  asm("lop3.b32 %0, %1, 0x03FF03FF, %2, 0xEA;" : "=r"(m) : "r"(u), "r"(c.k3c00));
  uint32_t p = hfma2(m, c.c3, 0xa385a385u);
  p = hfma2(p, m, 0x4ad64ad7u);
  uint32_t mu;
  asm("lop3.b32 %0, %1, 0xFC00FC00, %2, 0xEA;" : "=r"(mu) : "r"(u), "r"(c.kmask));
  uint32_t r;
  asm("{.reg .b32 t; shf.r.wrap.b32 t, %1, %2, 3; add.u32 %0, t, %3;}" : "=r"(r) : "r"(mu), "r"(c.seven), "r"(p));
  return r;
}
__device__ __forceinline__ float gadd(float x, float M, uint32_t g) {
  float r = x;
  asm("{.reg .pred p; setp.ne.b32 p, %2, -1; @p add.f32 %0, %0, %1;}" : "+f"(r) : "f"(M), "r"(g));
  return r;
}
__device__ __forceinline__ float gex2(float x, uint32_t g) {
  float r = x;
  asm("{.reg .pred p; setp.ne.b32 p, %1, -1; @p ex2.approx.ftz.f32 %0, %0;}" : "+f"(r) : "r"(g));
  return r;
}
template <int NPOLY, int NPAIR, int CH, int D, bool G0 = false>
__device__ __forceinline__ void exp_tile(const float (&s)[2 * NPAIR], uint32_t (&p)[NPAIR], const ExpC& c, uint32_t g0 = 0) {
#pragma unroll
  for (int i = 0; i < NPAIR; i++) {
    const bool isPoly = ((i + 1) * NPOLY / 32) != (i * NPOLY / 32);
    const int ch = i / CH;
    const bool gated = ch >= D || G0;
    int gi = (ch - D) * CH + CH - 1;
    if (ch >= D) {
      while (gi > (ch - D) * CH && !(((gi + 1) * NPOLY / 32) != (gi * NPOLY / 32))) gi--;
    }
    const uint32_t g = ch >= D ? p[gi] : g0;
    if (!isPoly) {
      if (gated && ATT_GM) p[i] = pack_bf16(gex2(s[2 * i], g), gex2(s[2 * i + 1], g));
      else p[i] = pack_bf16(ex2f(s[2 * i]), ex2f(s[2 * i + 1]));
    } else {
      if (gated) p[i] = exp2_poly_pair(gadd(s[2 * i], 12329.f, g), gadd(s[2 * i + 1], 12329.f, g), c);
      else p[i] = exp2_poly_pair(s[2 * i] + 12329.f, s[2 * i + 1] + 12329.f, c);
    }
  }
}

__device__ __forceinline__ void store_o(__nv_bfloat16* o, int row0, int head, int lane, const uint32_t (&r)[4]) {
  const int g = lane >> 2, t = lane & 3;
  uint32_t* p0 = reinterpret_cast<uint32_t*>(o + (size_t)(row0 + g) * DM + head * 16) + t;
  uint32_t* p1 = reinterpret_cast<uint32_t*>(o + (size_t)(row0 + g + 8) * DM + head * 16) + t;
  p0[0] = r[0];
  p1[0] = r[1];
  p0[4] = r[2];
  p1[4] = r[3];
}

__device__ __forceinline__ void safe_exp(const float (&s)[32], uint32_t (&p)[16], float (&o)[12], float& m0, float& m1) {
  float x0 = s[0], x1 = s[2];
#pragma unroll
  for (int i = 0; i < 8; i++) {
    x0 = fmaxf(x0, fmaxf(s[4 * i], s[4 * i + 1]));
    x1 = fmaxf(x1, fmaxf(s[4 * i + 2], s[4 * i + 3]));
  }
  x0 = fmaxf(x0, __shfl_xor_sync(0xffffffffu, x0, 1));
  x1 = fmaxf(x1, __shfl_xor_sync(0xffffffffu, x1, 1));
  x0 = fmaxf(x0, __shfl_xor_sync(0xffffffffu, x0, 2));
  x1 = fmaxf(x1, __shfl_xor_sync(0xffffffffu, x1, 2));
  const float n0 = fmaxf(m0, x0), n1 = fmaxf(m1, x1);
  const float c0 = ex2f(m0 - n0), c1 = ex2f(m1 - n1);
  m0 = n0;
  m1 = n1;
#pragma unroll
  for (int i = 0; i < 3; i++) {
    o[4 * i] *= c0;
    o[4 * i + 1] *= c0;
    o[4 * i + 2] *= c1;
    o[4 * i + 3] *= c1;
  }
#pragma unroll
  for (int i = 0; i < 8; i++) {
    p[2 * i] = pack_bf16(ex2f(s[4 * i] - n0), ex2f(s[4 * i + 1] - n0));
    p[2 * i + 1] = pack_bf16(ex2f(s[4 * i + 2] - n1), ex2f(s[4 * i + 3] - n1));
  }
}

__device__ __forceinline__ void attn_step(float (&sx)[32], float (&sy)[32], float (&o)[12], const uint4& qf, uint64_t dK, uint64_t dV,
                                          const ExpC& ec) {
  uint32_t pa[16], pb[16];
  wg_fence();
  wgmma_rs_n64_z(sy, qf.x, qf.y, qf.z, qf.w, dK + 128);
  wg_commit();
  uint32_t clk;
  asm volatile("mov.u32 %0, %%clock;" : "=r"(clk)::"memory");
  exp_tile<ATT_NPOLY, 16, ATT_CH, ATT_D, true>(sx, pa, ec, clk & ec.k3c00);
  wg_fence();
#pragma unroll
  for (int k = 0; k < 4; k++) wgmma_rs_n24_tb(o, pa[4 * k], pa[4 * k + 1], pa[4 * k + 2], pa[4 * k + 3], dV + k * 48, 1);
  wg_commit();
  wg_wait<1>();
  fence_regs(sy);
  exp_tile<ATT_NPOLY, 16, ATT_CH, ATT_D>(sy, pb, ec);
  wg_fence();
#pragma unroll
  for (int k = 0; k < 4; k++) wgmma_rs_n24_tb(o, pb[4 * k], pb[4 * k + 1], pb[4 * k + 2], pb[4 * k + 3], dV + (4 + k) * 48, 1);
  wgmma_rs_n64_z(sy, qf.x, qf.y, qf.z, qf.w, dK + 256);
  wg_commit();
  wg_wait<0>();
  fence_regs(sy);
}

template <bool SAFE>
__device__ __forceinline__ void attn_tile(uint64_t dK, uint64_t dV, uint32_t bar, const uint4 qf, const ExpC& ec, uint32_t (&outp)[4]) {
  float o[12];
#pragma unroll
  for (int i = 0; i < 12; i++) asm volatile("mov.f32 %0, 0f00000000;" : "=f"(o[i]));
  mbar_wait(bar, 0);
  if (!SAFE) {
    float s0[32], s1[32];
    wg_fence();
    wgmma_rs_n64_z(s0, qf.x, qf.y, qf.z, qf.w, dK);
    wg_commit();
    wg_wait<0>();
    fence_regs(s0);
#pragma unroll 1
    for (int p = 0; p < 8; p++) {
      if (p & 1) mbar_wait(bar + 8 * min((p + 1) >> 1, 3), 0);
      attn_step(s0, s1, o, qf, dK, dV, ec);
      attn_step(s1, s0, o, qf, dK + 256, dV + 384, ec);
      dK += 512;
      dV += 768;
    }
  } else {
    float m0 = -INFINITY, m1 = -INFINITY;
#pragma unroll 1
    for (int j = 0; j < 32; j++) {
      if (j == 4) { mbar_wait(bar + 8, 0); mbar_wait(bar + 16, 0); mbar_wait(bar + 24, 0); }
      float s[32];
      uint32_t p[16];
      wg_fence();
      wgmma_rs_n64_z(s, qf.x, qf.y, qf.z, qf.w, dK);
      wg_commit();
      wg_wait<0>();
      fence_regs(s);
      safe_exp(s, p, o, m0, m1);
      wg_fence();
#pragma unroll
      for (int k = 0; k < 4; k++) wgmma_rs_n24_tb(o, p[4 * k], p[4 * k + 1], p[4 * k + 2], p[4 * k + 3], dV + k * 48, 1);
      wg_commit();
      wg_wait<0>();
      fence_regs(o);
      dK += 128;
      dV += 192;
    }
  }
  fence_regs(o);
  const float r0 = 1.0f / o[8], r1 = 1.0f / o[10];
  outp[0] = pack_bf16(o[0] * r0, o[1] * r0);
  outp[1] = pack_bf16(o[2] * r1, o[3] * r1);
  outp[2] = pack_bf16(o[4] * r0, o[5] * r0);
  outp[3] = pack_bf16(o[6] * r1, o[7] * r1);
}

__device__ __forceinline__ void linear_attn_cta(uint8_t* smem_raw, uint32_t sbase, const CUtensorMap* mo16, int cta) {
  const int warp = threadIdx.x >> 5, lane = threadIdx.x & 31;
  float* red = reinterpret_cast<float*>(smem_raw + (sbase - smem_u32(smem_raw)) + 131072);
  {
    const float* src = g_kvpart + (size_t)cta * 8 * 384;
    float sum[6];
#pragma unroll
    for (int i = 0; i < 6; i++) sum[i] = 0.f;
#pragma unroll
    for (int r = 0; r < 16; r++) {
#pragma unroll
      for (int i = 0; i < 6; i++) sum[i] += src[(size_t)r * NH * 384 + threadIdx.x + i * 512];
    }
#pragma unroll
    for (int i = 0; i < 6; i++) red[threadIdx.x + i * 512] = round_bf16(sum[i]);
  }
  __syncthreads();
  uint32_t bf[8][6];
  {
    const int g = lane >> 2, t = lane & 3;
#pragma unroll
    for (int h = 0; h < 8; h++) {
#pragma unroll
      for (int f = 0; f < 6; f++) {
        const int blk = f >> 1, half = f & 1;
        const int e = (blk == 2) ? 0 : g;
        const int d = 2 * t + 8 * half;
        const int base = h * 384 + (blk * 4 + half * 2 + (e & 1)) * 32 + (e >> 1);
        bf[h][f] = pack_bf16(red[base + (d & 7) * 4], red[base + ((d + 1) & 7) * 4]);
      }
    }
  }
  const uint32_t stg = sbase + warp * 8192;
#pragma unroll 1
  for (int rb = 0; rb < 8; rb++) {
    const int blk16 = rb * 16 + warp;
    const uint4* qp = g_qfrag + ((size_t)(NH + cta * 8) * 32 + (blk16 >> 2)) * 128 + (blk16 & 3) * 32 + lane;
    uint4 q[8];
#pragma unroll
    for (int h = 0; h < 8; h++) q[h] = qp[h * 32 * 128];
    const uint32_t buf = stg + (rb & 1) * 4096;
    if (rb >= 2) {
      if (lane == 0) asm volatile("cp.async.bulk.wait_group.read 1;" ::: "memory");
      __syncwarp();
    }
#pragma unroll
    for (int h = 0; h < 8; h++) {
      float n0[4] = {0, 0, 0, 0}, n1[4] = {0, 0, 0, 0}, dn[4] = {0, 0, 0, 0};
      hmma(n0, q[h].x, q[h].y, q[h].z, q[h].w, bf[h][0], bf[h][1]);
      hmma(n1, q[h].x, q[h].y, q[h].z, q[h].w, bf[h][2], bf[h][3]);
      hmma(dn, q[h].x, q[h].y, q[h].z, q[h].w, bf[h][4], bf[h][5]);
      const float d0 = round_bf16(round_bf16(dn[0]) + 1e-6f), d1 = round_bf16(round_bf16(dn[2]) + 1e-6f);
      const uint32_t r0 = pack_bf16(__fdividef(round_bf16(n0[0]), d0), __fdividef(round_bf16(n0[1]), d0));
      const uint32_t r1 = pack_bf16(__fdividef(round_bf16(n0[2]), d1), __fdividef(round_bf16(n0[3]), d1));
      const uint32_t r2 = pack_bf16(__fdividef(round_bf16(n1[0]), d0), __fdividef(round_bf16(n1[1]), d0));
      const uint32_t r3 = pack_bf16(__fdividef(round_bf16(n1[2]), d1), __fdividef(round_bf16(n1[3]), d1));
      const int row = lane & 15;
      const int chunk = (h & 3) * 2 + (lane >> 4);
      const uint32_t addr = buf + (h >> 2) * 2048 + row * 128 + ((chunk ^ (row & 7)) << 4);
      asm volatile("stmatrix.sync.aligned.m8n8.x4.shared.b16 [%0], {%1,%2,%3,%4};" ::"r"(addr), "r"(r0), "r"(r1), "r"(r2), "r"(r3)
                   : "memory");
    }
    fence_proxy_async();
    __syncwarp();
    if (lane == 0) {
      tma_store_2d(mo16, buf, cta * 128, blk16 * 16);
      tma_store_2d(mo16, buf + 2048, cta * 128 + 64, blk16 * 16);
      asm volatile("cp.async.bulk.commit_group;" ::: "memory");
    }
  }
  if (lane == 0) asm volatile("cp.async.bulk.wait_group 0;" ::: "memory");
}

__global__ void __launch_bounds__(512, 1) attn_kernel(const __grid_constant__ CUtensorMap mo16) {
  extern __shared__ uint8_t smem_raw[];
  const uint32_t sbase = (smem_u32(smem_raw) + 1023) & ~1023u;
  const uint32_t bar = sbase + KV_HEAD_BYTES;
  if (threadIdx.x == 0) { PROF_G(1, 30); PROF_T(1, 0); }
  if (threadIdx.x == 0) {
    for (int i = 0; i < 4; i++) mbar_init(bar + 8 * i, 2);
    asm volatile("st.shared.v4.u32 [%0], {%1, %2, %3, %4};" ::"r"(bar + 64), "r"(0x3C003C00u), "r"(0x00070000u), "r"(7u),
                 "r"(ATT_DEG == 3 ? 0x2cfd2cfdu : 0x35623562u)
                 : "memory");
    fence_barrier_init();
    fence_proxy_async();
  }
  __syncthreads();
  cluster_sync_relaxed();
  if (threadIdx.x == 0) PROF_T(1, 6);
  pdl_launch_dependents();
  pdl_wait();
  if (threadIdx.x == 0) { PROF_T(1, 7); PROF_G(1, 29); }
  if (blockIdx.x >= 128) {
    linear_attn_cta(smem_raw, sbase, &mo16, blockIdx.x - 128);
    if (threadIdx.x == 0) { PROF_T(1, 5); PROF_G(1, 31); }
    return;
  }
  const int head = blockIdx.x >> 2, qb = blockIdx.x & 3;
  const int lane = threadIdx.x & 31;
  const int wg = threadIdx.x >> 7, warp = (threadIdx.x >> 5) & 3;
  uint4 qnext = g_qfrag[(head * 32 + qb * 8 + wg * 2) * 128 + (threadIdx.x & 127)];
  float4 nrm = make_float4(0.f, 0.f, 0.f, 0.f);
  if (lane < 16) nrm = *reinterpret_cast<const float4*>(&g_nrm[(head * 16 + lane) * 4]);
  if ((threadIdx.x & 63) == 0) {
    const uint8_t* img = reinterpret_cast<const uint8_t*>(g_kv) + (size_t)head * KV_HEAD_BYTES;
    const int half = blockIdx.x & 1;
    const int piece = threadIdx.x >> 6;
    const int g = piece >> 1, isv = piece & 1;
    const int e0 = g == 0 ? 0 : (isv ? 256 : 320) + (g - 1) * 512;
    const int e1 = g == 3 ? 2048 : (isv ? 256 : 320) + g * 512;
    const int bytes = (e1 - e0) * (isv ? 48 : 32);
    const int off = (isv ? KV_K_BYTES + e0 * 48 : e0 * 32) + half * (bytes / 2);
    mbar_expect_tx(bar + 8 * g, bytes);
    bulk_load_mc(sbase + off, img + off, bytes / 2, bar + 8 * g, (uint16_t)3);
  }
  bool safe_path;
  {
    const float4 n = nrm;
    uint32_t qm = ((lane >> 2) == qb) ? __float_as_uint(n.x) : 0u;
    qm = __reduce_max_sync(0xffffffffu, qm);
    const uint32_t km = __reduce_max_sync(0xffffffffu, __float_as_uint(n.y));
    const uint32_t vm = __reduce_max_sync(0xffffffffu, __float_as_uint(n.z));
    const float b2 = __uint_as_float(qm) * (QSCALE * QSCALE) * __uint_as_float(km) * 1.02f;
    const float vmax = __uint_as_float(vm);
    const bool ok = (b2 <= 21.5f * 21.5f) && (vmax <= 1.0e24f) && (vmax >= 1.0e-18f || vmax == 0.f);
    safe_path = !ok;
  }
  ExpC ec;
  asm volatile("ld.volatile.shared.v4.u32 {%0, %1, %2, %3}, [%4];" : "=r"(ec.k3c00), "=r"(ec.kmask), "=r"(ec.seven), "=r"(ec.c3) : "r"(bar + 64));
  const uint64_t dK = mkdesc(sbase, 128, 256, 0);
  const uint64_t dV = mkdesc(sbase + KV_K_BYTES, 384, 128, 0);
#pragma unroll 1
  for (int t = 0; t < 2; t++) {
    const int tile64 = qb * 8 + wg * 2 + t;
    const uint4 qf = qnext;
    if (t == 0) qnext = g_qfrag[(head * 32 + tile64 + 1) * 128 + (threadIdx.x & 127)];
    uint32_t r[4];
    if (threadIdx.x == 0) PROF_T(1, 1 + t);
    if (!safe_path) attn_tile<false>(dK, dV, bar, qf, ec, r);
    else attn_tile<true>(dK, dV, bar, qf, ec, r);
    store_o(g_o + (size_t)S_LEN * DM, tile64 * 64 + warp * 16, head, lane, r);
  }
  if (threadIdx.x == 0) { PROF_T(1, 5); PROF_G(1, 31); }
}

constexpr int K3_STAGES = 5;
constexpr int K3_W_BYTES = 8 * 16384;
constexpr int K3_BAR_OFF = K3_W_BYTES + K3_STAGES * 16384;
constexpr int K3_SMEM = K3_BAR_OFF + 256 + 1024;

__global__ void __launch_bounds__(288, 1)
out_gemm_kernel(const __grid_constant__ CUtensorMap mo, const __grid_constant__ CUtensorMap mwA,
                const __grid_constant__ CUtensorMap mwB, const __grid_constant__ CUtensorMap mout) {
  extern __shared__ uint8_t smem_raw[];
  const uint32_t sbase = (smem_u32(smem_raw) + 1023) & ~1023u;
  const uint32_t bar_full = sbase + K3_BAR_OFF;
  const uint32_t bar_empty = bar_full + 8 * K3_STAGES;
  const uint32_t bar_w = bar_empty + 8 * K3_STAGES;
  const int branch = blockIdx.x >> 6;
  const int rt = (blockIdx.x & 63) >> 2;
  const int ct = blockIdx.x & 3;
  const int warp = threadIdx.x >> 5;
  if (threadIdx.x == 0) { PROF_G(2, 30); PROF_T(2, 0); }
  if (threadIdx.x == 256) {
    const CUtensorMap* mw = branch ? &mwB : &mwA;
    asm volatile("prefetch.tensormap [%0];" ::"l"(mw) : "memory");
    asm volatile("prefetch.tensormap [%0];" ::"l"(&mo) : "memory");
    asm volatile("prefetch.tensormap [%0];" ::"l"(&mout) : "memory");
    for (int i = 0; i < K3_STAGES; i++) {
      mbar_init(bar_full + 8 * i, 1);
      mbar_init(bar_empty + 8 * i, 2);
    }
    for (int i = 0; i < 8; i++) mbar_init(bar_w + 8 * i, 1);
    fence_barrier_init();
    fence_proxy_async();
    for (int kb = 0; kb < 8; kb++) {
      mbar_expect_tx(bar_w + 8 * kb, 16384);
      tma_load_2d(sbase + kb * 16384, mw, ct * 128, kb * 64, bar_w + 8 * kb);
      tma_load_2d(sbase + kb * 16384 + 8192, mw, ct * 128 + 64, kb * 64, bar_w + 8 * kb);
    }
  }
  __syncthreads();
  if (warp == 8) {
    if ((threadIdx.x & 31) == 0) {
      pdl_wait();
      PROF_T(2, 1);
      for (int kb = 0; kb < 8; kb++) {
        const int s = kb % K3_STAGES;
        if (kb >= K3_STAGES) mbar_wait(bar_empty + 8 * s, ((kb / K3_STAGES) - 1) & 1);
        mbar_expect_tx(bar_full + 8 * s, 16384);
        tma_load_2d(sbase + K3_W_BYTES + s * 16384, &mo, kb * 64, branch * S_LEN + rt * 128, bar_full + 8 * s);
      }
    }
  } else {
    const int wg = warp >> 2;
    float acc[64];
    for (int kb = 0; kb < 8; kb++) {
      const int s = kb % K3_STAGES;
      mbar_wait(bar_w + 8 * kb, 0);
      mbar_wait(bar_full + 8 * s, (kb / K3_STAGES) & 1);
      if (threadIdx.x == 0) PROF_T(2, 2 + kb);
      const uint64_t dA = mkdesc(sbase + K3_W_BYTES + s * 16384 + wg * 8192, 16, 1024, 1);
      const uint64_t dB = mkdesc(sbase + kb * 16384, 8192, 1024, 1);
      wg_fence();
#pragma unroll
      for (int k = 0; k < 4; k++) wgmma_ss_n128_tb(acc, dA + k * 2, dB + k * 128, (kb | k) != 0);
      wg_commit();
      if (kb > 0) {
        wg_wait<1>();
        if ((threadIdx.x & 127) == 0) mbar_arrive(bar_empty + 8 * ((kb - 1) % K3_STAGES));
      }
    }
    wg_wait<0>();
    fence_regs(acc);
    if (threadIdx.x == 0) PROF_T(2, 10);
    const uint32_t stg = sbase + K3_W_BYTES + wg * 8192;
    asm volatile("bar.sync 1, 256;" ::: "memory");
    const int lane = threadIdx.x & 31;
    const int rloc = (warp & 3) * 16 + (lane & 15);
#pragma unroll
    for (int c16 = 0; c16 < 8; c16++) {
      const float* a = &acc[c16 * 8];
      const uint32_t r0 = pack_bf16(a[0], a[1]), r1 = pack_bf16(a[2], a[3]), r2 = pack_bf16(a[4], a[5]), r3 = pack_bf16(a[6], a[7]);
      const int chunk = (c16 & 3) * 2 + (lane >> 4);
      const uint32_t addr = stg + (c16 >> 2) * 16384 + rloc * 128 + ((chunk ^ (rloc & 7)) << 4);
      asm volatile("stmatrix.sync.aligned.m8n8.x4.shared.b16 [%0], {%1,%2,%3,%4};" ::"r"(addr), "r"(r0), "r"(r1), "r"(r2), "r"(r3)
                   : "memory");
    }
    fence_proxy_async();
    asm volatile("bar.sync %0, 128;" ::"r"(2 + wg) : "memory");
    if ((threadIdx.x & 127) == 0) {
      tma_store_2d(&mout, stg, branch * DM + ct * 128, rt * 128 + wg * 64);
      tma_store_2d(&mout, stg + 16384, branch * DM + ct * 128 + 64, rt * 128 + wg * 64);
      asm volatile("cp.async.bulk.commit_group;" ::: "memory");
      asm volatile("cp.async.bulk.wait_group.read 0;" ::: "memory");
      if (threadIdx.x == 0) { PROF_T(2, 12); PROF_G(2, 31); }
    }
  }
}

typedef CUresult (*EncodeFn)(CUtensorMap*, CUtensorMapDataType, cuuint32_t, void*, const cuuint64_t*, const cuuint64_t*,
                             const cuuint32_t*, const cuuint32_t*, CUtensorMapInterleave, CUtensorMapSwizzle,
                             CUtensorMapL2promotion, CUtensorMapFloatOOBfill);

void make_map(EncodeFn enc, CUtensorMap* m, const void* ptr, uint64_t inner, uint64_t outer, uint32_t box_inner, uint32_t box_outer) {
  cuuint64_t dims[2] = {inner, outer};
  cuuint64_t strides[1] = {inner * 2};
  cuuint32_t box[2] = {box_inner, box_outer};
  cuuint32_t es[2] = {1, 1};
  enc(m, CU_TENSOR_MAP_DATA_TYPE_BFLOAT16, 2, const_cast<void*>(ptr), dims, strides, box, es, CU_TENSOR_MAP_INTERLEAVE_NONE,
      CU_TENSOR_MAP_SWIZZLE_128B, CU_TENSOR_MAP_L2_PROMOTION_L2_256B, CU_TENSOR_MAP_FLOAT_OOB_FILL_NONE);
}

struct HostState {
  bool init;
  const void* key[7];
  CUtensorMap mxA, mxB, mwA, mwB, mo, mo16, mwoA, mwoB, mout;
};
HostState g_hs;

}

extern "C" void kernel_launch(void* const* d_in, const int* in_sizes, int n_in, void* d_out, int out_size) {
  (void)in_sizes; (void)n_in; (void)out_size;
  HostState& hs = g_hs;
  bool same = hs.init && hs.key[6] == d_out;
  for (int i = 0; i < 6 && same; i++) same = hs.key[i] == d_in[i];
  if (!same) {
    void* fn = nullptr;
    cudaDriverEntryPointQueryResult qr;
    cudaGetDriverEntryPoint("cuTensorMapEncodeTiled", &fn, cudaEnableDefault, &qr);
    EncodeFn enc = (EncodeFn)fn;
    void* go = nullptr;
    cudaGetSymbolAddress(&go, g_o);
    make_map(enc, &hs.mxA, d_in[0], 512, 2048, 64, 128);
    make_map(enc, &hs.mwA, d_in[1], 1536, 512, 64, 32);
    make_map(enc, &hs.mwoA, d_in[2], 512, 512, 64, 64);
    make_map(enc, &hs.mxB, d_in[3], 512, 2048, 64, 128);
    make_map(enc, &hs.mwB, d_in[4], 1536, 512, 64, 32);
    make_map(enc, &hs.mwoB, d_in[5], 512, 512, 64, 64);
    make_map(enc, &hs.mo, go, 512, 4096, 64, 128);
    make_map(enc, &hs.mo16, go, 512, 4096, 64, 16);
    make_map(enc, &hs.mout, d_out, 1024, 2048, 64, 64);
    cudaFuncSetAttribute(qkv_gemm_kernel, cudaFuncAttributeMaxDynamicSharedMemorySize, K1_SMEM);
    cudaFuncSetAttribute(attn_kernel, cudaFuncAttributeMaxDynamicSharedMemorySize, K2_SMEM);
    cudaFuncSetAttribute(out_gemm_kernel, cudaFuncAttributeMaxDynamicSharedMemorySize, K3_SMEM);
    for (int i = 0; i < 6; i++) hs.key[i] = d_in[i];
    hs.key[6] = d_out;
    hs.init = true;
  }
  cudaStream_t st = cudaStreamPerThread;
  {
    cudaLaunchConfig_t cfg = {};
    cfg.gridDim = dim3(128);
    cfg.blockDim = dim3(384);
    cfg.dynamicSmemBytes = K1_SMEM;
    cfg.stream = st;
    cudaLaunchAttribute at[1];
    at[0].id = cudaLaunchAttributeClusterDimension;
    at[0].val.clusterDim.x = 2;
    at[0].val.clusterDim.y = 1;
    at[0].val.clusterDim.z = 1;
    cfg.attrs = at;
    cfg.numAttrs = 1;
    cudaLaunchKernelEx(&cfg, qkv_gemm_kernel, hs.mxA, hs.mxB, hs.mwA, hs.mwB);
  }
  {
    cudaLaunchConfig_t cfg = {};
    cfg.gridDim = dim3(132);
    cfg.blockDim = dim3(512);
    cfg.dynamicSmemBytes = K2_SMEM;
    cfg.stream = st;
    cudaLaunchAttribute at[1];
    at[0].id = cudaLaunchAttributeProgrammaticStreamSerialization;
    at[0].val.programmaticStreamSerializationAllowed = 1;
    cudaLaunchAttribute at2[2];
    at2[0] = at[0];
    at2[1].id = cudaLaunchAttributeClusterDimension;
    at2[1].val.clusterDim.x = 2;
    at2[1].val.clusterDim.y = 1;
    at2[1].val.clusterDim.z = 1;
    cfg.attrs = at2;
    cfg.numAttrs = 2;
    cudaLaunchKernelEx(&cfg, attn_kernel, hs.mo16);
    cfg.attrs = at;
    cfg.numAttrs = 1;
    cfg.gridDim = dim3(128);
    cfg.blockDim = dim3(288);
    cfg.dynamicSmemBytes = K3_SMEM;
    cudaLaunchKernelEx(&cfg, out_gemm_kernel, hs.mo, hs.mwoA, hs.mwoB, hs.mout);
  }
}
```

```cpp
#include <cuda_runtime.h>
#include <cuda_bf16.h>
#include <cuda.h>
#include <stdint.h>

namespace {

constexpr int S_LEN = 2048;
constexpr int DM = 512;
constexpr int NH = 32;

constexpr int KV_K_BYTES = 65536;
constexpr int KV_HEAD_BYTES = KV_K_BYTES + 98304;
__device__ uint4 g_qfrag[2 * NH * 32 * 128];
__device__ uint4 g_kv[NH * KV_HEAD_BYTES / 16];
__device__ float g_kvpart[16 * NH * 384];
__device__ float g_nrm[NH * 16 * 4];
__device__ __nv_bfloat16 g_o[2 * S_LEN * DM];

#define g_prof_set(k, i, v)
#define g_prof_dummy(i) true
#define PROF_T(k, i) do {} while (0)
#define PROF_G(k, i) do {} while (0)
__device__ __forceinline__ uint32_t smem_u32(const void* p) { return (uint32_t)__cvta_generic_to_shared(p); }
__device__ __forceinline__ void mbar_init(uint32_t bar, int cnt) {
  asm volatile("mbarrier.init.shared::cta.b64 [%0], %1;" ::"r"(bar), "r"(cnt) : "memory");
}
__device__ __forceinline__ void mbar_expect_tx(uint32_t bar, uint32_t bytes) {
  asm volatile("mbarrier.arrive.expect_tx.shared::cta.b64 _, [%0], %1;" ::"r"(bar), "r"(bytes) : "memory");
}
__device__ __forceinline__ void mbar_arrive(uint32_t bar) {
  asm volatile("mbarrier.arrive.shared::cta.b64 _, [%0];" ::"r"(bar) : "memory");
}
__device__ __forceinline__ void mbar_arrive_cluster(uint32_t bar, uint32_t cta) {
  asm volatile(
      "{\n.reg .b32 ra;\nmapa.shared::cluster.u32 ra, %0, %1;\n"
      "mbarrier.arrive.shared::cluster.b64 _, [ra];\n}" ::"r"(bar), "r"(cta) : "memory");
}
__device__ __forceinline__ void mbar_wait(uint32_t bar, uint32_t parity) {
  asm volatile(
      "{\n.reg .pred p;\n"
      "WAIT_LOOP:\n"
      "mbarrier.try_wait.parity.shared::cta.b64 p, [%0], %1, 0x989680;\n"
      "@p bra WAIT_DONE;\n"
      "bra WAIT_LOOP;\n"
      "WAIT_DONE:\n}" ::"r"(bar), "r"(parity) : "memory");
}
__device__ __forceinline__ void mbar_wait_cluster(uint32_t bar, uint32_t parity) {
  asm volatile(
      "{\n.reg .pred p;\n"
      "WAIT_LOOP:\n"
      "mbarrier.try_wait.parity.acquire.cluster.shared::cta.b64 p, [%0], %1, 0x989680;\n"
      "@p bra WAIT_DONE;\n"
      "bra WAIT_LOOP;\n"
      "WAIT_DONE:\n}" ::"r"(bar), "r"(parity) : "memory");
}
__device__ __forceinline__ void fence_barrier_init() {
  asm volatile("fence.mbarrier_init.release.cluster;" ::: "memory");
}
__device__ __forceinline__ void fence_proxy_async() { asm volatile("fence.proxy.async.shared::cta;" ::: "memory"); }
__device__ __forceinline__ void cluster_sync_relaxed() {
  asm volatile("barrier.cluster.arrive.relaxed.aligned;\nbarrier.cluster.wait.aligned;" ::: "memory");
}
__device__ __forceinline__ void tma_load_2d(uint32_t dst, const CUtensorMap* m, int x, int y, uint32_t bar) {
  asm volatile(
      "cp.async.bulk.tensor.2d.shared::cluster.global.mbarrier::complete_tx::bytes [%0], [%1, {%3, %4}], [%2];" ::"r"(dst),
      "l"(m), "r"(bar), "r"(x), "r"(y)
      : "memory");
}
__device__ __forceinline__ void tma_load_2d_mc(uint32_t dst, const CUtensorMap* m, int x, int y, uint32_t bar, uint16_t mask) {
  asm volatile(
      "cp.async.bulk.tensor.2d.shared::cluster.global.mbarrier::complete_tx::bytes.multicast::cluster [%0], [%1, {%3, %4}], "
      "[%2], %5;" ::"r"(dst),
      "l"(m), "r"(bar), "r"(x), "r"(y), "h"(mask)
      : "memory");
}
__device__ __forceinline__ void tma_store_2d(const CUtensorMap* m, uint32_t src, int x, int y) {
  asm volatile("cp.async.bulk.tensor.2d.global.shared::cta.bulk_group [%0, {%2, %3}], [%1];" ::"l"(m), "r"(src), "r"(x),
               "r"(y)
               : "memory");
}
__device__ __forceinline__ void bulk_load(uint32_t dst, const void* src, uint32_t bytes, uint32_t bar) {
  asm volatile("cp.async.bulk.shared::cluster.global.mbarrier::complete_tx::bytes [%0], [%1], %2, [%3];" ::"r"(dst),
               "l"(src), "r"(bytes), "r"(bar)
               : "memory");
}
__device__ __forceinline__ void bulk_load_mc(uint32_t dst, const void* src, uint32_t bytes, uint32_t bar, uint16_t mask) {
  asm volatile("cp.async.bulk.shared::cluster.global.mbarrier::complete_tx::bytes.multicast::cluster [%0], [%1], %2, [%3], %4;" ::"r"(dst),
               "l"(src), "r"(bytes), "r"(bar), "h"(mask)
               : "memory");
}
__device__ __forceinline__ void pdl_launch_dependents() { asm volatile("griddepcontrol.launch_dependents;" ::: "memory"); }
__device__ __forceinline__ void pdl_wait() { asm volatile("griddepcontrol.wait;" ::: "memory"); }
__device__ __forceinline__ void wg_fence() { asm volatile("wgmma.fence.sync.aligned;" ::: "memory"); }
__device__ __forceinline__ void wg_commit() { asm volatile("wgmma.commit_group.sync.aligned;" ::: "memory"); }
template <int N>
__device__ __forceinline__ void wg_wait() {
  asm volatile("wgmma.wait_group.sync.aligned %0;" ::"n"(N) : "memory");
}
template <int M>
__device__ __forceinline__ void fence_regs(float (&r)[M]) {
#pragma unroll
  for (int i = 0; i < M; i++) asm volatile("" : "+f"(r[i])::"memory");
}
__device__ __forceinline__ uint64_t mkdesc(uint32_t addr, uint32_t lbo, uint32_t sbo, uint32_t layout) {
  return (uint64_t)((addr & 0x3FFFF) >> 4) | ((uint64_t)(lbo >> 4) << 16) | ((uint64_t)(sbo >> 4) << 32) |
         ((uint64_t)layout << 62);
}
__device__ __forceinline__ uint32_t pack_bf16(float lo, float hi) {
  uint32_t r;
  asm("cvt.rn.bf16x2.f32 %0, %1, %2;" : "=r"(r) : "f"(hi), "f"(lo));
  return r;
}
__device__ __forceinline__ float bf_lo(uint32_t v) { return __uint_as_float(v << 16); }
__device__ __forceinline__ float bf_hi(uint32_t v) { return __uint_as_float(v & 0xFFFF0000u); }
__device__ __forceinline__ float round_bf16(float x) { return bf_lo(pack_bf16(x, 0.f)); }
__device__ __forceinline__ float ex2f(float x) {
  float y;
  asm("ex2.approx.ftz.f32 %0, %1;" : "=f"(y) : "f"(x));
  return y;
}

__device__ __forceinline__ void wgmma_rs_n24_tb(float (&d)[12], uint32_t a0, uint32_t a1, uint32_t a2, uint32_t a3, uint64_t descB, int scaleD) {
  asm volatile("{\n.reg .pred p;\nsetp.ne.b32 p, %17, 0;\n"
    "wgmma.mma_async.sync.aligned.m64n24k16.f32.bf16.bf16 "
    "{%0, %1, %2, %3, %4, %5, %6, %7, %8, %9, %10, %11}, {%12, %13, %14, %15}, %16, p, 1, 1, 1;\n}\n"
    : "+f"(d[0]), "+f"(d[1]), "+f"(d[2]), "+f"(d[3]), "+f"(d[4]), "+f"(d[5]), "+f"(d[6]), "+f"(d[7]),
      "+f"(d[8]), "+f"(d[9]), "+f"(d[10]), "+f"(d[11])
    : "r"(a0), "r"(a1), "r"(a2), "r"(a3), "l"(descB), "r"(scaleD));
}
__device__ __forceinline__ void wgmma_rs_n64_z(float (&d)[32], uint32_t a0, uint32_t a1, uint32_t a2, uint32_t a3, uint64_t descB) {
  asm volatile("{\n.reg .pred p;\nsetp.ne.b32 p, %37, 0;\n"
    "wgmma.mma_async.sync.aligned.m64n64k16.f32.bf16.bf16 "
    "{%0, %1, %2, %3, %4, %5, %6, %7, %8, %9, %10, %11, %12, %13, %14, %15, %16, %17, %18, %19, %20, %21, %22, %23, %24, %25, %26, %27, %28, %29, %30, %31}, {%32, %33, %34, %35}, %36, p, 1, 1, 0;\n}\n"
    : "=f"(d[0]), "=f"(d[1]), "=f"(d[2]), "=f"(d[3]), "=f"(d[4]), "=f"(d[5]), "=f"(d[6]), "=f"(d[7]),
      "=f"(d[8]), "=f"(d[9]), "=f"(d[10]), "=f"(d[11]), "=f"(d[12]), "=f"(d[13]), "=f"(d[14]), "=f"(d[15]),
      "=f"(d[16]), "=f"(d[17]), "=f"(d[18]), "=f"(d[19]), "=f"(d[20]), "=f"(d[21]), "=f"(d[22]), "=f"(d[23]),
      "=f"(d[24]), "=f"(d[25]), "=f"(d[26]), "=f"(d[27]), "=f"(d[28]), "=f"(d[29]), "=f"(d[30]), "=f"(d[31])
    : "r"(a0), "r"(a1), "r"(a2), "r"(a3), "l"(descB), "n"(0));
}
__device__ __forceinline__ void wgmma_ss_n128_tb(float (&d)[64], uint64_t descA, uint64_t descB, int scaleD) {
  asm volatile("{\n.reg .pred p;\nsetp.ne.b32 p, %66, 0;\n"
    "wgmma.mma_async.sync.aligned.m64n128k16.f32.bf16.bf16 "
    "{%0, %1, %2, %3, %4, %5, %6, %7, %8, %9, %10, %11, %12, %13, %14, %15, %16, %17, %18, %19, %20, %21, %22, %23, %24, %25, %26, %27, %28, %29, %30, %31, %32, %33, %34, %35, %36, %37, %38, %39, %40, %41, %42, %43, %44, %45, %46, %47, %48, %49, %50, %51, %52, %53, %54, %55, %56, %57, %58, %59, %60, %61, %62, %63}, %64, %65, p, 1, 1, 0, 1;\n}\n"
    : "+f"(d[0]), "+f"(d[1]), "+f"(d[2]), "+f"(d[3]), "+f"(d[4]), "+f"(d[5]), "+f"(d[6]), "+f"(d[7]),
      "+f"(d[8]), "+f"(d[9]), "+f"(d[10]), "+f"(d[11]), "+f"(d[12]), "+f"(d[13]), "+f"(d[14]), "+f"(d[15]),
      "+f"(d[16]), "+f"(d[17]), "+f"(d[18]), "+f"(d[19]), "+f"(d[20]), "+f"(d[21]), "+f"(d[22]), "+f"(d[23]),
      "+f"(d[24]), "+f"(d[25]), "+f"(d[26]), "+f"(d[27]), "+f"(d[28]), "+f"(d[29]), "+f"(d[30]), "+f"(d[31]),
      "+f"(d[32]), "+f"(d[33]), "+f"(d[34]), "+f"(d[35]), "+f"(d[36]), "+f"(d[37]), "+f"(d[38]), "+f"(d[39]),
      "+f"(d[40]), "+f"(d[41]), "+f"(d[42]), "+f"(d[43]), "+f"(d[44]), "+f"(d[45]), "+f"(d[46]), "+f"(d[47]),
      "+f"(d[48]), "+f"(d[49]), "+f"(d[50]), "+f"(d[51]), "+f"(d[52]), "+f"(d[53]), "+f"(d[54]), "+f"(d[55]),
      "+f"(d[56]), "+f"(d[57]), "+f"(d[58]), "+f"(d[59]), "+f"(d[60]), "+f"(d[61]), "+f"(d[62]), "+f"(d[63])
    : "l"(descA), "l"(descB), "r"(scaleD));
}
__device__ __forceinline__ void wgmma_ss_n192_tb(float (&d)[96], uint64_t descA, uint64_t descB, int scaleD) {
  asm volatile("{\n.reg .pred p;\nsetp.ne.b32 p, %98, 0;\n"
    "wgmma.mma_async.sync.aligned.m64n192k16.f32.bf16.bf16 "
    "{%0, %1, %2, %3, %4, %5, %6, %7, %8, %9, %10, %11, %12, %13, %14, %15, %16, %17, %18, %19, %20, %21, %22, %23, %24, %25, %26, %27, %28, %29, %30, %31, %32, %33, %34, %35, %36, %37, %38, %39, %40, %41, %42, %43, %44, %45, %46, %47, %48, %49, %50, %51, %52, %53, %54, %55, %56, %57, %58, %59, %60, %61, %62, %63, %64, %65, %66, %67, %68, %69, %70, %71, %72, %73, %74, %75, %76, %77, %78, %79, %80, %81, %82, %83, %84, %85, %86, %87, %88, %89, %90, %91, %92, %93, %94, %95}, %96, %97, p, 1, 1, 0, 1;\n}\n"
    : "+f"(d[0]), "+f"(d[1]), "+f"(d[2]), "+f"(d[3]), "+f"(d[4]), "+f"(d[5]), "+f"(d[6]), "+f"(d[7]),
      "+f"(d[8]), "+f"(d[9]), "+f"(d[10]), "+f"(d[11]), "+f"(d[12]), "+f"(d[13]), "+f"(d[14]), "+f"(d[15]),
      "+f"(d[16]), "+f"(d[17]), "+f"(d[18]), "+f"(d[19]), "+f"(d[20]), "+f"(d[21]), "+f"(d[22]), "+f"(d[23]),
      "+f"(d[24]), "+f"(d[25]), "+f"(d[26]), "+f"(d[27]), "+f"(d[28]), "+f"(d[29]), "+f"(d[30]), "+f"(d[31]),
      "+f"(d[32]), "+f"(d[33]), "+f"(d[34]), "+f"(d[35]), "+f"(d[36]), "+f"(d[37]), "+f"(d[38]), "+f"(d[39]),
      "+f"(d[40]), "+f"(d[41]), "+f"(d[42]), "+f"(d[43]), "+f"(d[44]), "+f"(d[45]), "+f"(d[46]), "+f"(d[47]),
      "+f"(d[48]), "+f"(d[49]), "+f"(d[50]), "+f"(d[51]), "+f"(d[52]), "+f"(d[53]), "+f"(d[54]), "+f"(d[55]),
      "+f"(d[56]), "+f"(d[57]), "+f"(d[58]), "+f"(d[59]), "+f"(d[60]), "+f"(d[61]), "+f"(d[62]), "+f"(d[63]),
      "+f"(d[64]), "+f"(d[65]), "+f"(d[66]), "+f"(d[67]), "+f"(d[68]), "+f"(d[69]), "+f"(d[70]), "+f"(d[71]),
      "+f"(d[72]), "+f"(d[73]), "+f"(d[74]), "+f"(d[75]), "+f"(d[76]), "+f"(d[77]), "+f"(d[78]), "+f"(d[79]),
      "+f"(d[80]), "+f"(d[81]), "+f"(d[82]), "+f"(d[83]), "+f"(d[84]), "+f"(d[85]), "+f"(d[86]), "+f"(d[87]),
      "+f"(d[88]), "+f"(d[89]), "+f"(d[90]), "+f"(d[91]), "+f"(d[92]), "+f"(d[93]), "+f"(d[94]), "+f"(d[95])
    : "l"(descA), "l"(descB), "r"(scaleD));
}

__device__ __forceinline__ void ldsm4t(uint32_t (&b)[4], uint32_t addr) {
  asm volatile("ldmatrix.sync.aligned.m8n8.x4.trans.shared.b16 {%0,%1,%2,%3}, [%4];"
               : "=r"(b[0]), "=r"(b[1]), "=r"(b[2]), "=r"(b[3])
               : "r"(addr));
}
__device__ __forceinline__ void hmma(float (&c)[4], uint32_t a0, uint32_t a1, uint32_t a2, uint32_t a3, uint32_t b0, uint32_t b1) {
  asm("mma.sync.aligned.m16n8k16.row.col.f32.bf16.bf16.f32 {%0,%1,%2,%3}, {%4,%5,%6,%7}, {%8,%9}, {%0,%1,%2,%3};"
      : "+f"(c[0]), "+f"(c[1]), "+f"(c[2]), "+f"(c[3])
      : "r"(a0), "r"(a1), "r"(a2), "r"(a3), "r"(b0), "r"(b1));
}

__device__ __forceinline__ uint32_t movm(uint32_t a) {
  uint32_t d;
  asm volatile("movmatrix.sync.aligned.m8n8.trans.b16 %0, %1;" : "=r"(d) : "r"(a));
  return d;
}

constexpr int K1_STAGES = 4;
constexpr int K1_W_BYTES = 3 * 8192;
constexpr int K1_X_BYTES = 8 * 16384;
constexpr int K1_BAR_OFF = K1_X_BYTES + K1_STAGES * K1_W_BYTES;
constexpr int K1_SMEM = K1_BAR_OFF + 192 + 1024;
constexpr float QSCALE = 0.25f * 1.4426950408889634f;

__device__ __forceinline__ uint32_t phi2(uint32_t t2) {
  uint32_t a2, mask, r2, o2;
  asm("add.rn.bf16x2 %0, %1, %2;" : "=r"(a2) : "r"(t2), "r"(0x3F803F80u));
  const uint32_t e2 = pack_bf16(ex2f(bf_lo(t2) * 1.4426950408889634f), ex2f(bf_hi(t2) * 1.4426950408889634f));
  asm("set.gt.u32.bf16x2 %0, %1, %2;" : "=r"(mask) : "r"(t2), "r"(0u));
  r2 = (a2 & mask) | (e2 & ~mask);
  asm("add.rn.bf16x2 %0, %1, %2;" : "=r"(o2) : "r"(r2), "r"(0x35863586u));
  return o2;
}

#define K1_SLOT_KB(h) ((h) < 4 ? 2 * (h) : 2 * ((h) - 4) + 1)
struct EpiCtx {
  uint4* qf;
  uint32_t* kp;
  uint32_t* vp;
  uint32_t* s_red;
  float* red;
  int lane;
};

template <bool LINEAR, int J, int HH, int PART>
__device__ __forceinline__ void epi_slice(const float (&acc)[96], const EpiCtx& c, uint32_t (&pk)[4], float& vmax) {
  constexpr int h = J * 4 + HH;
  const float* a = &acc[HH * 8];
  const float* k = &acc[32 + HH * 8];
  const float* v = &acc[64 + HH * 8];
  if (!LINEAR) {
    if (PART == 0) {
      c.qf[h * 32 * 128] = make_uint4(pack_bf16(a[0] * QSCALE, a[1] * QSCALE), pack_bf16(a[2] * QSCALE, a[3] * QSCALE),
                                      pack_bf16(a[4] * QSCALE, a[5] * QSCALE), pack_bf16(a[6] * QSCALE, a[7] * QSCALE));
      uint32_t* kh = c.kp + h * (KV_HEAD_BYTES / 4);
      kh[0] = pack_bf16(k[0], k[1]);
      kh[64] = pack_bf16(k[2], k[3]);
      kh[32] = pack_bf16(k[4], k[5]);
      kh[96] = pack_bf16(k[6], k[7]);
      float q0 = a[0] * a[0] + a[1] * a[1] + a[4] * a[4] + a[5] * a[5];
      float q1 = a[2] * a[2] + a[3] * a[3] + a[6] * a[6] + a[7] * a[7];
      float k0 = k[0] * k[0] + k[1] * k[1] + k[4] * k[4] + k[5] * k[5];
      float k1 = k[2] * k[2] + k[3] * k[3] + k[6] * k[6] + k[7] * k[7];
#pragma unroll
      for (int o = 1; o <= 2; o <<= 1) {
        q0 += __shfl_xor_sync(0xffffffffu, q0, o);
        q1 += __shfl_xor_sync(0xffffffffu, q1, o);
        k0 += __shfl_xor_sync(0xffffffffu, k0, o);
        k1 += __shfl_xor_sync(0xffffffffu, k1, o);
      }
      const uint32_t qm = __reduce_max_sync(0xffffffffu, max(__float_as_uint(q0) & 0x7FFFFFFFu, __float_as_uint(q1) & 0x7FFFFFFFu));
      const uint32_t km = __reduce_max_sync(0xffffffffu, max(__float_as_uint(k0) & 0x7FFFFFFFu, __float_as_uint(k1) & 0x7FFFFFFFu));
      if (c.lane == 0) {
        atomicMax(&c.s_red[h * 2 + 0], qm);
        atomicMax(&c.s_red[h * 2 + 1], km);
      }
    } else {
      uint32_t* vh = c.vp + h * (KV_HEAD_BYTES / 4);
      vh[0] = pack_bf16(v[0], v[1]);
      vh[96] = pack_bf16(v[2], v[3]);
      vh[32] = pack_bf16(v[4], v[5]);
      vh[128] = pack_bf16(v[6], v[7]);
      vh[64] = 0x3F803F80u;
      vh[160] = 0x3F803F80u;
#pragma unroll
      for (int i = 0; i < 8; i++) asm("max.NaN.f32 %0, %0, %1;" : "+f"(vmax) : "f"(fabsf(v[i])));
    }
  } else {
    if (PART == 0) {
      c.qf[h * 32 * 128] = make_uint4(phi2(pack_bf16(a[0], a[1])), phi2(pack_bf16(a[2], a[3])), phi2(pack_bf16(a[4], a[5])),
                                      phi2(pack_bf16(a[6], a[7])));
      pk[0] = movm(phi2(pack_bf16(k[0], k[1])));
      pk[2] = movm(phi2(pack_bf16(k[2], k[3])));
      pk[1] = movm(phi2(pack_bf16(k[4], k[5])));
      pk[3] = movm(phi2(pack_bf16(k[6], k[7])));
    } else {
      const uint32_t b0 = movm(pack_bf16(v[0], v[1]));
      const uint32_t b1 = movm(pack_bf16(v[2], v[3]));
      const uint32_t b2 = movm(pack_bf16(v[4], v[5]));
      const uint32_t b3 = movm(pack_bf16(v[6], v[7]));
      float c0[4] = {0, 0, 0, 0}, c1[4] = {0, 0, 0, 0}, c2[4] = {0, 0, 0, 0};
      hmma(c0, pk[0], pk[1], pk[2], pk[3], b0, b1);
      hmma(c1, pk[0], pk[1], pk[2], pk[3], b2, b3);
      hmma(c2, pk[0], pk[1], pk[2], pk[3], 0x3F803F80u, 0x3F803F80u);
      float* slot = c.red + K1_SLOT_KB(h) * 4096;
#pragma unroll
      for (int i = 0; i < 4; i++) {
        slot[i * 32] = c0[i];
        slot[(4 + i) * 32] = c1[i];
        slot[(8 + i) * 32] = c2[i];
      }
    }
  }
}

template <bool LINEAR>
__device__ __forceinline__ void qkv_consumer(uint32_t sbase, uint8_t* smem_gen, uint32_t* s_red, int cp, int rt) {
  const uint32_t bar_full = sbase + K1_BAR_OFF;
  const uint32_t bar_empty = bar_full + 8 * K1_STAGES;
  const int warp = threadIdx.x >> 5;
  const int wg = warp >> 2;
  const int lane = threadIdx.x & 31;
  float acc0[96], acc1[96];
#pragma unroll 1
  for (int kb = 0; kb < 8; kb++) {
    const int s = kb % K1_STAGES;
    mbar_wait(bar_full + 8 * s, (kb / K1_STAGES) & 1);
    if (threadIdx.x == 0) PROF_T(0, 2 + (kb >> 1));
    const uint64_t dA = mkdesc(sbase + kb * 16384 + wg * 8192, 16, 1024, 1);
    const uint64_t dB = mkdesc(sbase + K1_X_BYTES + s * K1_W_BYTES, 8192, 1024, 1);
    wg_fence();
#pragma unroll
    for (int k = 0; k < 4; k++) wgmma_ss_n192_tb(acc0, dA + k * 2, dB + k * 128, (kb | k) != 0);
    wg_commit();
    if (kb > 0) {
      wg_wait<1>();
      if ((threadIdx.x & 127) == 0) {
        const int sp = (kb - 1) % K1_STAGES;
        mbar_arrive_cluster(bar_empty + 8 * sp, 0);
        mbar_arrive_cluster(bar_empty + 8 * sp, 1);
      }
    }
  }
  wg_wait<0>();
  fence_regs(acc0);
  if ((threadIdx.x & 127) == 0) {
    mbar_arrive_cluster(bar_empty + 8 * (7 % K1_STAGES), 0);
    mbar_arrive_cluster(bar_empty + 8 * (7 % K1_STAGES), 1);
  }
  if (threadIdx.x == 0) PROF_T(0, 6);

  EpiCtx c;
  {
    const int row0 = rt * 128 + wg * 64 + (warp & 3) * 16;
    c.qf = g_qfrag + ((size_t)((LINEAR ? NH : 0) + cp * 8) * 32 + (rt * 2 + wg)) * 128 + (threadIdx.x & 127);
    uint32_t* img = reinterpret_cast<uint32_t*>(reinterpret_cast<uint8_t*>(g_kv) + (size_t)(cp * 8) * KV_HEAD_BYTES);
    c.kp = img + (row0 >> 3) * 64 + lane;
    c.vp = img + KV_K_BYTES / 4 + (row0 >> 3) * 96 + lane;
    c.s_red = s_red;
    c.red = reinterpret_cast<float*>(smem_gen + wg * 8192) + (warp & 3) * 384 + lane;
    c.lane = lane;
  }
  uint32_t pk[4];
  float vmax = 0.f;
#define K1_T1_STEP(KB)                                                                           \
  {                                                                                              \
    constexpr int g = 8 + KB;                                                                    \
    constexpr int s = g % K1_STAGES;                                                             \
    mbar_wait(bar_full + 8 * s, (g / K1_STAGES) & 1);                                            \
    const uint64_t dA = mkdesc(sbase + KB * 16384 + wg * 8192, 16, 1024, 1);                     \
    const uint64_t dB = mkdesc(sbase + K1_X_BYTES + s * K1_W_BYTES, 8192, 1024, 1);              \
    wg_fence();                                                                                  \
    _Pragma("unroll") for (int k = 0; k < 4; k++) wgmma_ss_n192_tb(acc1, dA + k * 2, dB + k * 128, (KB | k) != 0); \
    wg_commit();                                                                                 \
    epi_slice<LINEAR, 0, KB / 2, KB & 1>(acc0, c, pk, vmax);                                     \
    wg_wait<0>();                                                                                \
    if (KB + K1_STAGES < 8 && (threadIdx.x & 127) == 0) {                                        \
      mbar_arrive_cluster(bar_empty + 8 * s, 0);                                                 \
      mbar_arrive_cluster(bar_empty + 8 * s, 1);                                                 \
    }                                                                                            \
  }
  K1_T1_STEP(0) K1_T1_STEP(1) K1_T1_STEP(2) K1_T1_STEP(3) K1_T1_STEP(4) K1_T1_STEP(5) K1_T1_STEP(6) K1_T1_STEP(7)
#undef K1_T1_STEP
  fence_regs(acc1);
  if (threadIdx.x == 0) PROF_T(0, 10);
  epi_slice<LINEAR, 1, 0, 0>(acc1, c, pk, vmax);
  epi_slice<LINEAR, 1, 0, 1>(acc1, c, pk, vmax);
  epi_slice<LINEAR, 1, 1, 0>(acc1, c, pk, vmax);
  epi_slice<LINEAR, 1, 1, 1>(acc1, c, pk, vmax);
  epi_slice<LINEAR, 1, 2, 0>(acc1, c, pk, vmax);
  epi_slice<LINEAR, 1, 2, 1>(acc1, c, pk, vmax);
  epi_slice<LINEAR, 1, 3, 0>(acc1, c, pk, vmax);
  epi_slice<LINEAR, 1, 3, 1>(acc1, c, pk, vmax);
  if (!LINEAR) {
    const uint32_t vm = __reduce_max_sync(0xffffffffu, __float_as_uint(vmax) & 0x7FFFFFFFu);
    if (lane == 0) atomicMax(&s_red[16], vm);
    asm volatile("bar.sync 1, 256;" ::: "memory");
    if (threadIdx.x < 8) {
      *reinterpret_cast<float4*>(&g_nrm[((cp * 8 + threadIdx.x) * 16 + rt) * 4]) =
          make_float4(__uint_as_float(s_red[threadIdx.x * 2]), __uint_as_float(s_red[threadIdx.x * 2 + 1]), __uint_as_float(s_red[16]), 0.f);
    }
  } else {
    asm volatile("bar.sync 1, 256;" ::: "memory");
    float* dst = g_kvpart + ((size_t)rt * NH + cp * 8) * 384;
#pragma unroll
    for (int i = 0; i < 12; i++) {
      const int o = threadIdx.x + i * 256;
      const int h = o / 384, e = o - h * 384;
      const float* src = reinterpret_cast<const float*>(smem_gen) + K1_SLOT_KB(h) * 4096 + e;
      float sum = 0.f;
#pragma unroll
      for (int w = 0; w < 8; w++) sum += src[(w >> 2) * 2048 + (w & 3) * 384];
      dst[o] = sum;
    }
  }
}

__global__ void __launch_bounds__(384, 1)
qkv_gemm_kernel(const __grid_constant__ CUtensorMap mxA, const __grid_constant__ CUtensorMap mxB,
                const __grid_constant__ CUtensorMap mwA, const __grid_constant__ CUtensorMap mwB) {
  extern __shared__ uint8_t smem_raw[];
  const uint32_t sbase = (smem_u32(smem_raw) + 1023) & ~1023u;
  uint8_t* smem_gen = smem_raw + (sbase - smem_u32(smem_raw));
  const uint32_t bar_full = sbase + K1_BAR_OFF;
  const uint32_t bar_empty = bar_full + 8 * K1_STAGES;
  uint32_t* s_red = reinterpret_cast<uint32_t*>(smem_gen + K1_BAR_OFF + 64);

  const int rank = blockIdx.x & 1;
  const int pair = blockIdx.x >> 1;
  const int branch = pair >> 5;
  const int rp = (pair & 31) >> 2;
  const int cp = pair & 3;
  const int rt = rp * 2 + rank;
  const int warp = threadIdx.x >> 5;
  if (threadIdx.x == 0) { PROF_G(0, 30); PROF_T(0, 0); }
  const CUtensorMap* mx = branch ? &mxA : &mxB;
  const CUtensorMap* mw = branch ? &mwA : &mwB;

  if (threadIdx.x == 256) {
    asm volatile("prefetch.tensormap [%0];" ::"l"(mx) : "memory");
    asm volatile("prefetch.tensormap [%0];" ::"l"(mw) : "memory");
    for (int i = 0; i < K1_STAGES; i++) {
      mbar_init(bar_full + 8 * i, 1);
      mbar_init(bar_empty + 8 * i, 4);
    }
    fence_barrier_init();
    fence_proxy_async();
    for (int kb = 0; kb < K1_STAGES; kb++) mbar_expect_tx(bar_full + 8 * kb, 16384 + K1_W_BYTES);
    tma_load_2d(sbase, mx, 0, rt * 128, bar_full);
  }
  pdl_launch_dependents();
  if (threadIdx.x < 32) s_red[threadIdx.x] = 0;
  __syncthreads();
  cluster_sync_relaxed();
  if (threadIdx.x == 0) PROF_T(0, 1);

  if (warp >= 8) {
    asm volatile("setmaxnreg.dec.sync.aligned.u32 40;");
    if (threadIdx.x == 256) {
      for (int g = 0; g < 16; g++) {
        const int s = g % K1_STAGES;
        const int kb = g & 7;
        if (g >= K1_STAGES) {
          mbar_wait(bar_empty + 8 * s, ((g / K1_STAGES) - 1) & 1);
          mbar_expect_tx(bar_full + 8 * s, (g < 8 ? 16384 : 0) + K1_W_BYTES);
        }
        if (g > 0 && g < 8) tma_load_2d(sbase + kb * 16384, mx, kb * 64, rt * 128, bar_full + 8 * s);
        const int h0 = cp * 8 + (g >> 3) * 4;
        const uint32_t st = sbase + K1_X_BYTES + s * K1_W_BYTES + rank * 4096;
#pragma unroll
        for (int p = 0; p < 3; p++)
          tma_load_2d_mc(st + p * 8192, mw, p * 512 + h0 * 16, kb * 64 + rank * 32, bar_full + 8 * s, (uint16_t)3);
      }
    }
    __syncwarp();
    cluster_sync_relaxed();
  } else {
    asm volatile("setmaxnreg.inc.sync.aligned.u32 232;");
    if (branch == 0) qkv_consumer<false>(sbase, smem_gen, s_red, cp, rt);
    else qkv_consumer<true>(sbase, smem_gen, s_red, cp, rt);
    if (threadIdx.x == 0) PROF_T(0, 11);
    __syncwarp();
    cluster_sync_relaxed();
    if (threadIdx.x == 0) { PROF_T(0, 12); PROF_G(0, 31); }
  }
}

constexpr int K2_SMEM = KV_HEAD_BYTES + 1024 + 256;

#define ATT_NPOLY 18
#define ATT_CH 8
#define ATT_D 1
#define PRO_MODE 1
#define STAGGER 0
#define CONST_SMID 0
#define ATT_STRUCT 1
#define ATT_PIN 0
#define ATT_GM 1
#define ATT_DEG 2
struct ExpC {
  uint32_t k3c00, kmask, seven, c3;
};
__device__ __forceinline__ uint32_t hfma2(uint32_t a, uint32_t b, uint32_t c) {
  uint32_t r;
  asm("fma.rn.f16x2 %0, %1, %2, %3;" : "=r"(r) : "r"(a), "r"(b), "r"(c));
  return r;
}
__device__ __forceinline__ uint32_t exp2_poly_pair(float t0, float t1, const ExpC& c) {
  uint32_t u;
  asm("prmt.b32 %0, %1, %2, 0x5410;" : "=r"(u) : "r"(__float_as_uint(t0)), "r"(__float_as_uint(t1)));
  uint32_t m;
  asm("lop3.b32 %0, %1, 0x03FF03FF, %2, 0xEA;" : "=r"(m) : "r"(u), "r"(c.k3c00));
  uint32_t p = hfma2(m, c.c3, 0xa385a385u);
  p = hfma2(p, m, 0x4ad64ad7u);
  uint32_t mu;
  asm("lop3.b32 %0, %1, 0xFC00FC00, %2, 0xEA;" : "=r"(mu) : "r"(u), "r"(c.kmask));
  uint32_t r;
  asm("{.reg .b32 t; shf.r.wrap.b32 t, %1, %2, 3; add.u32 %0, t, %3;}" : "=r"(r) : "r"(mu), "r"(c.seven), "r"(p));
  return r;
}
__device__ __forceinline__ float gadd(float x, float M, uint32_t g) {
  float r = x;
  asm("{.reg .pred p; setp.ne.b32 p, %2, -1; @p add.f32 %0, %0, %1;}" : "+f"(r) : "f"(M), "r"(g));
  return r;
}
__device__ __forceinline__ float gex2(float x, uint32_t g) {
  float r = x;
  asm("{.reg .pred p; setp.ne.b32 p, %1, -1; @p ex2.approx.ftz.f32 %0, %0;}" : "+f"(r) : "r"(g));
  return r;
}
template <int NPOLY, int NPAIR, int CH, int D, bool G0 = false>
__device__ __forceinline__ void exp_tile(const float (&s)[2 * NPAIR], uint32_t (&p)[NPAIR], const ExpC& c, uint32_t g0 = 0) {
#pragma unroll
  for (int i = 0; i < NPAIR; i++) {
    const bool isPoly = ((i + 1) * NPOLY / 32) != (i * NPOLY / 32);
    const int ch = i / CH;
    const bool gated = ch >= D || G0;
    int gi = (ch - D) * CH + CH - 1;
    if (ch >= D) {
      while (gi > (ch - D) * CH && !(((gi + 1) * NPOLY / 32) != (gi * NPOLY / 32))) gi--;
    }
    const uint32_t g = ch >= D ? p[gi] : g0;
    if (!isPoly) {
      if (gated && ATT_GM) p[i] = pack_bf16(gex2(s[2 * i], g), gex2(s[2 * i + 1], g));
      else p[i] = pack_bf16(ex2f(s[2 * i]), ex2f(s[2 * i + 1]));
    } else {
      if (gated) p[i] = exp2_poly_pair(gadd(s[2 * i], 12329.f, g), gadd(s[2 * i + 1], 12329.f, g), c);
      else p[i] = exp2_poly_pair(s[2 * i] + 12329.f, s[2 * i + 1] + 12329.f, c);
    }
  }
}

__device__ __forceinline__ void store_o(__nv_bfloat16* o, int row0, int head, int lane, const uint32_t (&r)[4]) {
  const int g = lane >> 2, t = lane & 3;
  uint32_t* p0 = reinterpret_cast<uint32_t*>(o + (size_t)(row0 + g) * DM + head * 16) + t;
  uint32_t* p1 = reinterpret_cast<uint32_t*>(o + (size_t)(row0 + g + 8) * DM + head * 16) + t;
  p0[0] = r[0];
  p1[0] = r[1];
  p0[4] = r[2];
  p1[4] = r[3];
}

__device__ __forceinline__ void kv_fetch_piece(uint32_t sbase, uint32_t bar, int piece) {
  const uint8_t* img = reinterpret_cast<const uint8_t*>(g_kv) + (size_t)(blockIdx.x >> 2) * KV_HEAD_BYTES;
  const int half = blockIdx.x & 1;
  const int g = piece >> 1, isv = piece & 1;
  const int e0 = g == 0 ? 0 : (isv ? 256 : 320) + (g - 1) * 512;
  const int e1 = g == 3 ? 2048 : (isv ? 256 : 320) + g * 512;
  const int bytes = (e1 - e0) * (isv ? 48 : 32);
  const int off = (isv ? KV_K_BYTES + e0 * 48 : e0 * 32) + half * (bytes / 2);
  mbar_expect_tx(bar + 8 * g, bytes);
  bulk_load_mc(sbase + off, img + off, bytes / 2, bar + 8 * g, (uint16_t)3);
}

__device__ __forceinline__ void safe_exp(const float (&s)[32], uint32_t (&p)[16], float (&o)[12], float& m0, float& m1) {
  float x0 = s[0], x1 = s[2];
#pragma unroll
  for (int i = 0; i < 8; i++) {
    x0 = fmaxf(x0, fmaxf(s[4 * i], s[4 * i + 1]));
    x1 = fmaxf(x1, fmaxf(s[4 * i + 2], s[4 * i + 3]));
  }
  x0 = fmaxf(x0, __shfl_xor_sync(0xffffffffu, x0, 1));
  x1 = fmaxf(x1, __shfl_xor_sync(0xffffffffu, x1, 1));
  x0 = fmaxf(x0, __shfl_xor_sync(0xffffffffu, x0, 2));
  x1 = fmaxf(x1, __shfl_xor_sync(0xffffffffu, x1, 2));
  const float n0 = fmaxf(m0, x0), n1 = fmaxf(m1, x1);
  const float c0 = ex2f(m0 - n0), c1 = ex2f(m1 - n1);
  m0 = n0;
  m1 = n1;
#pragma unroll
  for (int i = 0; i < 3; i++) {
    o[4 * i] *= c0;
    o[4 * i + 1] *= c0;
    o[4 * i + 2] *= c1;
    o[4 * i + 3] *= c1;
  }
#pragma unroll
  for (int i = 0; i < 8; i++) {
    p[2 * i] = pack_bf16(ex2f(s[4 * i] - n0), ex2f(s[4 * i + 1] - n0));
    p[2 * i + 1] = pack_bf16(ex2f(s[4 * i + 2] - n1), ex2f(s[4 * i + 3] - n1));
  }
}

__device__ __forceinline__ void attn_step(float (&sx)[32], float (&sy)[32], float (&o)[12], const uint4& qf, uint64_t dK, uint64_t dV,
                                          const ExpC& ec) {
  uint32_t pa[16], pb[16];
  wg_fence();
  wgmma_rs_n64_z(sy, qf.x, qf.y, qf.z, qf.w, dK + 128);
  wg_commit();
  exp_tile<ATT_NPOLY, 16, ATT_CH, ATT_D>(sx, pa, ec);
  wg_fence();
  wgmma_rs_n24_tb(o, pa[12], pa[13], pa[14], pa[15], dV + 3 * 48, 1);
  wg_commit();
  wg_wait<1>();
  fence_regs(sy);
  exp_tile<ATT_NPOLY, 16, ATT_CH, ATT_D>(sy, pb, ec);
  wg_fence();
#pragma unroll
  for (int k = 0; k < 3; k++) wgmma_rs_n24_tb(o, pa[4 * k], pa[4 * k + 1], pa[4 * k + 2], pa[4 * k + 3], dV + k * 48, 1);
#pragma unroll
  for (int k = 0; k < 4; k++) wgmma_rs_n24_tb(o, pb[4 * k], pb[4 * k + 1], pb[4 * k + 2], pb[4 * k + 3], dV + (4 + k) * 48, 1);
  wgmma_rs_n64_z(sy, qf.x, qf.y, qf.z, qf.w, dK + 256);
  wg_commit();
  wg_wait<0>();
  fence_regs(sy);
}

template <bool SAFE>
__device__ __forceinline__ void attn_tile(uint64_t dK, uint64_t dV, uint32_t bar, const uint4 qf, const ExpC& ec, uint32_t (&outp)[4],
                                          uint32_t sbase, bool first) {
  float o[12];
#pragma unroll
  for (int i = 0; i < 12; i++) asm volatile("mov.f32 %0, 0f00000000;" : "=f"(o[i]));
  mbar_wait(bar, 0);
  const int wg = threadIdx.x >> 7;
  const bool leader = first && (threadIdx.x & 127) == 0;
  if (leader && wg >= 2) kv_fetch_piece(sbase, bar, wg);
  if (SAFE && leader) {
    kv_fetch_piece(sbase, bar, 4 + wg);
  }
  if (!SAFE) {
    float s0[32], s1[32];
    wg_fence();
    wgmma_rs_n64_z(s0, qf.x, qf.y, qf.z, qf.w, dK);
    wg_commit();
    wg_wait<0>();
    fence_regs(s0);
#pragma unroll 1
    for (int p = 0; p < 8; p++) {
      if (leader && (p == 1 || p == 2) && (wg >> 1) == p - 1) kv_fetch_piece(sbase, bar, 4 + wg);
      if (p & 1) mbar_wait(bar + 8 * min((p + 1) >> 1, 3), 0);
      attn_step(s0, s1, o, qf, dK, dV, ec);
      attn_step(s1, s0, o, qf, dK + 256, dV + 384, ec);
      dK += 512;
      dV += 768;
    }
  } else {
    float m0 = -INFINITY, m1 = -INFINITY;
#pragma unroll 1
    for (int j = 0; j < 32; j++) {
      if (j == 4) { mbar_wait(bar + 8, 0); mbar_wait(bar + 16, 0); mbar_wait(bar + 24, 0); }
      float s[32];
      uint32_t p[16];
      wg_fence();
      wgmma_rs_n64_z(s, qf.x, qf.y, qf.z, qf.w, dK);
      wg_commit();
      wg_wait<0>();
      fence_regs(s);
      safe_exp(s, p, o, m0, m1);
      wg_fence();
#pragma unroll
      for (int k = 0; k < 4; k++) wgmma_rs_n24_tb(o, p[4 * k], p[4 * k + 1], p[4 * k + 2], p[4 * k + 3], dV + k * 48, 1);
      wg_commit();
      wg_wait<0>();
      fence_regs(o);
      dK += 128;
      dV += 192;
    }
  }
  fence_regs(o);
  const float r0 = 1.0f / o[8], r1 = 1.0f / o[10];
  outp[0] = pack_bf16(o[0] * r0, o[1] * r0);
  outp[1] = pack_bf16(o[2] * r1, o[3] * r1);
  outp[2] = pack_bf16(o[4] * r0, o[5] * r0);
  outp[3] = pack_bf16(o[6] * r1, o[7] * r1);
}

__device__ __forceinline__ void linear_attn_cta(uint8_t* smem_raw, uint32_t sbase, const CUtensorMap* mo16, int cta) {
  const int warp = threadIdx.x >> 5, lane = threadIdx.x & 31;
  float* red = reinterpret_cast<float*>(smem_raw + (sbase - smem_u32(smem_raw)) + 131072);
  {
    const float* src = g_kvpart + (size_t)cta * 8 * 384;
    float sum[6];
#pragma unroll
    for (int i = 0; i < 6; i++) sum[i] = 0.f;
#pragma unroll
    for (int r = 0; r < 16; r++) {
#pragma unroll
      for (int i = 0; i < 6; i++) sum[i] += src[(size_t)r * NH * 384 + threadIdx.x + i * 512];
    }
#pragma unroll
    for (int i = 0; i < 6; i++) red[threadIdx.x + i * 512] = round_bf16(sum[i]);
  }
  __syncthreads();
  uint32_t bf[8][6];
  {
    const int g = lane >> 2, t = lane & 3;
#pragma unroll
    for (int h = 0; h < 8; h++) {
#pragma unroll
      for (int f = 0; f < 6; f++) {
        const int blk = f >> 1, half = f & 1;
        const int e = (blk == 2) ? 0 : g;
        const int d = 2 * t + 8 * half;
        const int base = h * 384 + (blk * 4 + half * 2 + (e & 1)) * 32 + (e >> 1);
        bf[h][f] = pack_bf16(red[base + (d & 7) * 4], red[base + ((d + 1) & 7) * 4]);
      }
    }
  }
  const uint32_t stg = sbase + warp * 8192;
#pragma unroll 1
  for (int rb = 0; rb < 8; rb++) {
    const int blk16 = rb * 16 + warp;
    const uint4* qp = g_qfrag + ((size_t)(NH + cta * 8) * 32 + (blk16 >> 2)) * 128 + (blk16 & 3) * 32 + lane;
    uint4 q[8];
#pragma unroll
    for (int h = 0; h < 8; h++) q[h] = qp[h * 32 * 128];
    const uint32_t buf = stg + (rb & 1) * 4096;
    if (rb >= 2) {
      if (lane == 0) asm volatile("cp.async.bulk.wait_group.read 1;" ::: "memory");
      __syncwarp();
    }
#pragma unroll
    for (int h = 0; h < 8; h++) {
      float n0[4] = {0, 0, 0, 0}, n1[4] = {0, 0, 0, 0}, dn[4] = {0, 0, 0, 0};
      hmma(n0, q[h].x, q[h].y, q[h].z, q[h].w, bf[h][0], bf[h][1]);
      hmma(n1, q[h].x, q[h].y, q[h].z, q[h].w, bf[h][2], bf[h][3]);
      hmma(dn, q[h].x, q[h].y, q[h].z, q[h].w, bf[h][4], bf[h][5]);
      const float d0 = round_bf16(round_bf16(dn[0]) + 1e-6f), d1 = round_bf16(round_bf16(dn[2]) + 1e-6f);
      const uint32_t r0 = pack_bf16(__fdividef(round_bf16(n0[0]), d0), __fdividef(round_bf16(n0[1]), d0));
      const uint32_t r1 = pack_bf16(__fdividef(round_bf16(n0[2]), d1), __fdividef(round_bf16(n0[3]), d1));
      const uint32_t r2 = pack_bf16(__fdividef(round_bf16(n1[0]), d0), __fdividef(round_bf16(n1[1]), d0));
      const uint32_t r3 = pack_bf16(__fdividef(round_bf16(n1[2]), d1), __fdividef(round_bf16(n1[3]), d1));
      const int row = lane & 15;
      const int chunk = (h & 3) * 2 + (lane >> 4);
      const uint32_t addr = buf + (h >> 2) * 2048 + row * 128 + ((chunk ^ (row & 7)) << 4);
      asm volatile("stmatrix.sync.aligned.m8n8.x4.shared.b16 [%0], {%1,%2,%3,%4};" ::"r"(addr), "r"(r0), "r"(r1), "r"(r2), "r"(r3)
                   : "memory");
    }
    fence_proxy_async();
    __syncwarp();
    if (lane == 0) {
      tma_store_2d(mo16, buf, cta * 128, blk16 * 16);
      tma_store_2d(mo16, buf + 2048, cta * 128 + 64, blk16 * 16);
      asm volatile("cp.async.bulk.commit_group;" ::: "memory");
    }
  }
  if (lane == 0) asm volatile("cp.async.bulk.wait_group 0;" ::: "memory");
}

__global__ void __launch_bounds__(512, 1) attn_kernel(const __grid_constant__ CUtensorMap mo16) {
  extern __shared__ uint8_t smem_raw[];
  const uint32_t sbase = (smem_u32(smem_raw) + 1023) & ~1023u;
  const uint32_t bar = sbase + KV_HEAD_BYTES;
  if (threadIdx.x == 0) { PROF_G(1, 30); PROF_T(1, 0); }
  if (threadIdx.x == 0) {
    for (int i = 0; i < 4; i++) mbar_init(bar + 8 * i, 2);
    asm volatile("st.shared.v4.u32 [%0], {%1, %2, %3, %4};" ::"r"(bar + 64), "r"(0x3C003C00u), "r"(0x00070000u), "r"(7u),
                 "r"(ATT_DEG == 3 ? 0x2cfd2cfdu : 0x35623562u)
                 : "memory");
    fence_barrier_init();
    fence_proxy_async();
  }
  __syncthreads();
  cluster_sync_relaxed();
  if (threadIdx.x == 0) PROF_T(1, 6);
  pdl_launch_dependents();
  pdl_wait();
  if (threadIdx.x == 0) { PROF_T(1, 7); PROF_G(1, 29); }
  if (blockIdx.x >= 128) {
    linear_attn_cta(smem_raw, sbase, &mo16, blockIdx.x - 128);
    if (threadIdx.x == 0) { PROF_T(1, 5); PROF_G(1, 31); }
    return;
  }
  const int head = blockIdx.x >> 2, qb = blockIdx.x & 3;
  const int lane = threadIdx.x & 31;
  const int wg = threadIdx.x >> 7, warp = (threadIdx.x >> 5) & 3;
  uint4 qnext = g_qfrag[(head * 32 + qb * 8 + wg * 2) * 128 + (threadIdx.x & 127)];
  float4 nrm = make_float4(0.f, 0.f, 0.f, 0.f);
  if (lane < 16) nrm = *reinterpret_cast<const float4*>(&g_nrm[(head * 16 + lane) * 4]);
  if ((threadIdx.x & 127) == 0 && wg < 2) kv_fetch_piece(sbase, bar, wg);
  bool safe_path;
  {
    const float4 n = nrm;
    uint32_t qm = ((lane >> 2) == qb) ? __float_as_uint(n.x) : 0u;
    qm = __reduce_max_sync(0xffffffffu, qm);
    const uint32_t km = __reduce_max_sync(0xffffffffu, __float_as_uint(n.y));
    const uint32_t vm = __reduce_max_sync(0xffffffffu, __float_as_uint(n.z));
    const float b2 = __uint_as_float(qm) * (QSCALE * QSCALE) * __uint_as_float(km) * 1.02f;
    const float vmax = __uint_as_float(vm);
    const bool ok = (b2 <= 21.5f * 21.5f) && (vmax <= 1.0e24f) && (vmax >= 1.0e-18f || vmax == 0.f);
    safe_path = !ok;
  }
  ExpC ec;
  asm volatile("ld.volatile.shared.v4.u32 {%0, %1, %2, %3}, [%4];" : "=r"(ec.k3c00), "=r"(ec.kmask), "=r"(ec.seven), "=r"(ec.c3) : "r"(bar + 64));
  const uint64_t dK = mkdesc(sbase, 128, 256, 0);
  const uint64_t dV = mkdesc(sbase + KV_K_BYTES, 384, 128, 0);
#pragma unroll 1
  for (int t = 0; t < 2; t++) {
    const int tile64 = qb * 8 + wg * 2 + t;
    const uint4 qf = qnext;
    if (t == 0) qnext = g_qfrag[(head * 32 + tile64 + 1) * 128 + (threadIdx.x & 127)];
    uint32_t r[4];
    if (threadIdx.x == 0) PROF_T(1, 1 + t);
    if (!safe_path) attn_tile<false>(dK, dV, bar, qf, ec, r, sbase, t == 0);
    else attn_tile<true>(dK, dV, bar, qf, ec, r, sbase, t == 0);
    store_o(g_o + (size_t)S_LEN * DM, tile64 * 64 + warp * 16, head, lane, r);
  }
  if (threadIdx.x == 0) { PROF_T(1, 5); PROF_G(1, 31); }
}

constexpr int K3_STAGES = 5;
constexpr int K3_W_BYTES = 8 * 16384;
constexpr int K3_BAR_OFF = K3_W_BYTES + K3_STAGES * 16384;
constexpr int K3_SMEM = K3_BAR_OFF + 256 + 1024;

__global__ void __launch_bounds__(288, 1)
out_gemm_kernel(const __grid_constant__ CUtensorMap mo, const __grid_constant__ CUtensorMap mwA,
                const __grid_constant__ CUtensorMap mwB, const __grid_constant__ CUtensorMap mout) {
  extern __shared__ uint8_t smem_raw[];
  const uint32_t sbase = (smem_u32(smem_raw) + 1023) & ~1023u;
  const uint32_t bar_full = sbase + K3_BAR_OFF;
  const uint32_t bar_empty = bar_full + 8 * K3_STAGES;
  const uint32_t bar_w = bar_empty + 8 * K3_STAGES;
  const int branch = blockIdx.x >> 6;
  const int rt = (blockIdx.x & 63) >> 2;
  const int ct = blockIdx.x & 3;
  const int warp = threadIdx.x >> 5;
  if (threadIdx.x == 0) { PROF_G(2, 30); PROF_T(2, 0); }
  if (threadIdx.x == 256) {
    const CUtensorMap* mw = branch ? &mwB : &mwA;
    asm volatile("prefetch.tensormap [%0];" ::"l"(mw) : "memory");
    asm volatile("prefetch.tensormap [%0];" ::"l"(&mo) : "memory");
    asm volatile("prefetch.tensormap [%0];" ::"l"(&mout) : "memory");
    for (int i = 0; i < K3_STAGES; i++) {
      mbar_init(bar_full + 8 * i, 1);
      mbar_init(bar_empty + 8 * i, 2);
    }
    for (int i = 0; i < 8; i++) mbar_init(bar_w + 8 * i, 1);
    fence_barrier_init();
    fence_proxy_async();
    for (int kb = 0; kb < 8; kb++) {
      mbar_expect_tx(bar_w + 8 * kb, 16384);
      tma_load_2d(sbase + kb * 16384, mw, ct * 128, kb * 64, bar_w + 8 * kb);
      tma_load_2d(sbase + kb * 16384 + 8192, mw, ct * 128 + 64, kb * 64, bar_w + 8 * kb);
    }
  }
  __syncthreads();
  if (warp == 8) {
    if ((threadIdx.x & 31) == 0) {
      pdl_wait();
      PROF_T(2, 1);
      for (int kb = 0; kb < 8; kb++) {
        const int s = kb % K3_STAGES;
        if (kb >= K3_STAGES) mbar_wait(bar_empty + 8 * s, ((kb / K3_STAGES) - 1) & 1);
        mbar_expect_tx(bar_full + 8 * s, 16384);
        tma_load_2d(sbase + K3_W_BYTES + s * 16384, &mo, kb * 64, branch * S_LEN + rt * 128, bar_full + 8 * s);
      }
    }
  } else {
    const int wg = warp >> 2;
    float acc[64];
    for (int kb = 0; kb < 8; kb++) {
      const int s = kb % K3_STAGES;
      mbar_wait(bar_w + 8 * kb, 0);
      mbar_wait(bar_full + 8 * s, (kb / K3_STAGES) & 1);
      if (threadIdx.x == 0) PROF_T(2, 2 + kb);
      const uint64_t dA = mkdesc(sbase + K3_W_BYTES + s * 16384 + wg * 8192, 16, 1024, 1);
      const uint64_t dB = mkdesc(sbase + kb * 16384, 8192, 1024, 1);
      wg_fence();
#pragma unroll
      for (int k = 0; k < 4; k++) wgmma_ss_n128_tb(acc, dA + k * 2, dB + k * 128, (kb | k) != 0);
      wg_commit();
      if (kb > 0) {
        wg_wait<1>();
        if ((threadIdx.x & 127) == 0) mbar_arrive(bar_empty + 8 * ((kb - 1) % K3_STAGES));
      }
    }
    wg_wait<0>();
    fence_regs(acc);
    if (threadIdx.x == 0) PROF_T(2, 10);
    const uint32_t stg = sbase + K3_W_BYTES + wg * 8192;
    asm volatile("bar.sync 1, 256;" ::: "memory");
    const int lane = threadIdx.x & 31;
    const int rloc = (warp & 3) * 16 + (lane & 15);
#pragma unroll
    for (int c16 = 0; c16 < 8; c16++) {
      const float* a = &acc[c16 * 8];
      const uint32_t r0 = pack_bf16(a[0], a[1]), r1 = pack_bf16(a[2], a[3]), r2 = pack_bf16(a[4], a[5]), r3 = pack_bf16(a[6], a[7]);
      const int chunk = (c16 & 3) * 2 + (lane >> 4);
      const uint32_t addr = stg + (c16 >> 2) * 16384 + rloc * 128 + ((chunk ^ (rloc & 7)) << 4);
      asm volatile("stmatrix.sync.aligned.m8n8.x4.shared.b16 [%0], {%1,%2,%3,%4};" ::"r"(addr), "r"(r0), "r"(r1), "r"(r2), "r"(r3)
                   : "memory");
    }
    fence_proxy_async();
    asm volatile("bar.sync %0, 128;" ::"r"(2 + wg) : "memory");
    if ((threadIdx.x & 127) == 0) {
      tma_store_2d(&mout, stg, branch * DM + ct * 128, rt * 128 + wg * 64);
      tma_store_2d(&mout, stg + 16384, branch * DM + ct * 128 + 64, rt * 128 + wg * 64);
      asm volatile("cp.async.bulk.commit_group;" ::: "memory");
      asm volatile("cp.async.bulk.wait_group.read 0;" ::: "memory");
      if (threadIdx.x == 0) { PROF_T(2, 12); PROF_G(2, 31); }
    }
  }
}

typedef CUresult (*EncodeFn)(CUtensorMap*, CUtensorMapDataType, cuuint32_t, void*, const cuuint64_t*, const cuuint64_t*,
                             const cuuint32_t*, const cuuint32_t*, CUtensorMapInterleave, CUtensorMapSwizzle,
                             CUtensorMapL2promotion, CUtensorMapFloatOOBfill);

void make_map(EncodeFn enc, CUtensorMap* m, const void* ptr, uint64_t inner, uint64_t outer, uint32_t box_inner, uint32_t box_outer) {
  cuuint64_t dims[2] = {inner, outer};
  cuuint64_t strides[1] = {inner * 2};
  cuuint32_t box[2] = {box_inner, box_outer};
  cuuint32_t es[2] = {1, 1};
  enc(m, CU_TENSOR_MAP_DATA_TYPE_BFLOAT16, 2, const_cast<void*>(ptr), dims, strides, box, es, CU_TENSOR_MAP_INTERLEAVE_NONE,
      CU_TENSOR_MAP_SWIZZLE_128B, CU_TENSOR_MAP_L2_PROMOTION_L2_256B, CU_TENSOR_MAP_FLOAT_OOB_FILL_NONE);
}

struct HostState {
  bool init;
  const void* key[7];
  CUtensorMap mxA, mxB, mwA, mwB, mo, mo16, mwoA, mwoB, mout;
};
HostState g_hs;

}

extern "C" void kernel_launch(void* const* d_in, const int* in_sizes, int n_in, void* d_out, int out_size) {
  (void)in_sizes; (void)n_in; (void)out_size;
  HostState& hs = g_hs;
  bool same = hs.init && hs.key[6] == d_out;
  for (int i = 0; i < 6 && same; i++) same = hs.key[i] == d_in[i];
  if (!same) {
    void* fn = nullptr;
    cudaDriverEntryPointQueryResult qr;
    cudaGetDriverEntryPoint("cuTensorMapEncodeTiled", &fn, cudaEnableDefault, &qr);
    EncodeFn enc = (EncodeFn)fn;
    void* go = nullptr;
    cudaGetSymbolAddress(&go, g_o);
    make_map(enc, &hs.mxA, d_in[0], 512, 2048, 64, 128);
    make_map(enc, &hs.mwA, d_in[1], 1536, 512, 64, 32);
    make_map(enc, &hs.mwoA, d_in[2], 512, 512, 64, 64);
    make_map(enc, &hs.mxB, d_in[3], 512, 2048, 64, 128);
    make_map(enc, &hs.mwB, d_in[4], 1536, 512, 64, 32);
    make_map(enc, &hs.mwoB, d_in[5], 512, 512, 64, 64);
    make_map(enc, &hs.mo, go, 512, 4096, 64, 128);
    make_map(enc, &hs.mo16, go, 512, 4096, 64, 16);
    make_map(enc, &hs.mout, d_out, 1024, 2048, 64, 64);
    cudaFuncSetAttribute(qkv_gemm_kernel, cudaFuncAttributeMaxDynamicSharedMemorySize, K1_SMEM);
    cudaFuncSetAttribute(attn_kernel, cudaFuncAttributeMaxDynamicSharedMemorySize, K2_SMEM);
    cudaFuncSetAttribute(out_gemm_kernel, cudaFuncAttributeMaxDynamicSharedMemorySize, K3_SMEM);
    for (int i = 0; i < 6; i++) hs.key[i] = d_in[i];
    hs.key[6] = d_out;
    hs.init = true;
  }
  cudaStream_t st = cudaStreamPerThread;
  {
    cudaLaunchConfig_t cfg = {};
    cfg.gridDim = dim3(128);
    cfg.blockDim = dim3(384);
    cfg.dynamicSmemBytes = K1_SMEM;
    cfg.stream = st;
    cudaLaunchAttribute at[1];
    at[0].id = cudaLaunchAttributeClusterDimension;
    at[0].val.clusterDim.x = 2;
    at[0].val.clusterDim.y = 1;
    at[0].val.clusterDim.z = 1;
    cfg.attrs = at;
    cfg.numAttrs = 1;
    cudaLaunchKernelEx(&cfg, qkv_gemm_kernel, hs.mxA, hs.mxB, hs.mwA, hs.mwB);
  }
  {
    cudaLaunchConfig_t cfg = {};
    cfg.gridDim = dim3(132);
    cfg.blockDim = dim3(512);
    cfg.dynamicSmemBytes = K2_SMEM;
    cfg.stream = st;
    cudaLaunchAttribute at[1];
    at[0].id = cudaLaunchAttributeProgrammaticStreamSerialization;
    at[0].val.programmaticStreamSerializationAllowed = 1;
    cudaLaunchAttribute at2[2];
    at2[0] = at[0];
    at2[1].id = cudaLaunchAttributeClusterDimension;
    at2[1].val.clusterDim.x = 2;
    at2[1].val.clusterDim.y = 1;
    at2[1].val.clusterDim.z = 1;
    cfg.attrs = at2;
    cfg.numAttrs = 2;
    cudaLaunchKernelEx(&cfg, attn_kernel, hs.mo16);
    cfg.attrs = at;
    cfg.numAttrs = 1;
    cfg.gridDim = dim3(128);
    cfg.blockDim = dim3(288);
    cfg.dynamicSmemBytes = K3_SMEM;
    cudaLaunchKernelEx(&cfg, out_gemm_kernel, hs.mo, hs.mwoA, hs.mwoB, hs.mout);
  }
}
```

```cpp
#include <cuda_runtime.h>
#include <cuda_bf16.h>
#include <cuda.h>
#include <stdint.h>

namespace {

constexpr int S_LEN = 2048;
constexpr int DM = 512;
constexpr int NH = 32;

constexpr int KV_K_BYTES = 65536;
constexpr int KV_HEAD_BYTES = KV_K_BYTES + 98304;
__device__ uint4 g_qfrag[2 * NH * 32 * 128];
__device__ uint4 g_kv[NH * KV_HEAD_BYTES / 16];
__device__ float g_kvpart[16 * NH * 384];
__device__ float g_nrm[NH * 16 * 4];
__device__ __nv_bfloat16 g_o[2 * S_LEN * DM];

#define g_prof_set(k, i, v)
#define g_prof_dummy(i) true
#define PROF_T(k, i) do {} while (0)
#define PROF_G(k, i) do {} while (0)
__device__ __forceinline__ uint32_t smem_u32(const void* p) { return (uint32_t)__cvta_generic_to_shared(p); }
__device__ __forceinline__ void mbar_init(uint32_t bar, int cnt) {
  asm volatile("mbarrier.init.shared::cta.b64 [%0], %1;" ::"r"(bar), "r"(cnt) : "memory");
}
__device__ __forceinline__ void mbar_expect_tx(uint32_t bar, uint32_t bytes) {
  asm volatile("mbarrier.arrive.expect_tx.shared::cta.b64 _, [%0], %1;" ::"r"(bar), "r"(bytes) : "memory");
}
__device__ __forceinline__ void mbar_arrive(uint32_t bar) {
  asm volatile("mbarrier.arrive.shared::cta.b64 _, [%0];" ::"r"(bar) : "memory");
}
__device__ __forceinline__ void mbar_arrive_cluster(uint32_t bar, uint32_t cta) {
  asm volatile(
      "{\n.reg .b32 ra;\nmapa.shared::cluster.u32 ra, %0, %1;\n"
      "mbarrier.arrive.shared::cluster.b64 _, [ra];\n}" ::"r"(bar), "r"(cta) : "memory");
}
__device__ __forceinline__ void mbar_wait(uint32_t bar, uint32_t parity) {
  asm volatile(
      "{\n.reg .pred p;\n.reg .u32 n;\n"
      "mov.u32 n, 0;\n"
      "WAIT_LOOP:\n"
      "mbarrier.try_wait.parity.shared::cta.b64 p, [%0], %1, 0x400000;\n"
      "@p bra WAIT_DONE;\n"
      "add.u32 n, n, 1;\n"
      "setp.lt.u32 p, n, 4000000;\n"
      "@p bra WAIT_LOOP;\n"
      "trap;\n"
      "WAIT_DONE:\n}" ::"r"(bar), "r"(parity) : "memory");
}
__device__ __forceinline__ void fence_barrier_init() {
  asm volatile("fence.mbarrier_init.release.cluster;" ::: "memory");
}
__device__ __forceinline__ void fence_proxy_async() { asm volatile("fence.proxy.async.shared::cta;" ::: "memory"); }
__device__ __forceinline__ void cluster_sync_relaxed() {
  asm volatile("barrier.cluster.arrive.relaxed.aligned;\nbarrier.cluster.wait.aligned;" ::: "memory");
}
__device__ __forceinline__ void tma_load_2d(uint32_t dst, const CUtensorMap* m, int x, int y, uint32_t bar) {
  asm volatile(
      "cp.async.bulk.tensor.2d.shared::cluster.global.mbarrier::complete_tx::bytes [%0], [%1, {%3, %4}], [%2];" ::"r"(dst),
      "l"(m), "r"(bar), "r"(x), "r"(y)
      : "memory");
}
__device__ __forceinline__ void tma_load_2d_mc(uint32_t dst, const CUtensorMap* m, int x, int y, uint32_t bar, uint16_t mask) {
  asm volatile(
      "cp.async.bulk.tensor.2d.shared::cluster.global.mbarrier::complete_tx::bytes.multicast::cluster [%0], [%1, {%3, %4}], "
      "[%2], %5;" ::"r"(dst),
      "l"(m), "r"(bar), "r"(x), "r"(y), "h"(mask)
      : "memory");
}
__device__ __forceinline__ void tma_store_2d(const CUtensorMap* m, uint32_t src, int x, int y) {
  asm volatile("cp.async.bulk.tensor.2d.global.shared::cta.bulk_group [%0, {%2, %3}], [%1];" ::"l"(m), "r"(src), "r"(x),
               "r"(y)
               : "memory");
}
__device__ __forceinline__ void bulk_load(uint32_t dst, const void* src, uint32_t bytes, uint32_t bar) {
  asm volatile("cp.async.bulk.shared::cluster.global.mbarrier::complete_tx::bytes [%0], [%1], %2, [%3];" ::"r"(dst),
               "l"(src), "r"(bytes), "r"(bar)
               : "memory");
}
__device__ __forceinline__ void bulk_load_mc(uint32_t dst, const void* src, uint32_t bytes, uint32_t bar, uint16_t mask) {
  asm volatile("cp.async.bulk.shared::cluster.global.mbarrier::complete_tx::bytes.multicast::cluster [%0], [%1], %2, [%3], %4;" ::"r"(dst),
               "l"(src), "r"(bytes), "r"(bar), "h"(mask)
               : "memory");
}
__device__ __forceinline__ void pdl_launch_dependents() { asm volatile("griddepcontrol.launch_dependents;" ::: "memory"); }
__device__ __forceinline__ void pdl_wait() { asm volatile("griddepcontrol.wait;" ::: "memory"); }
__device__ __forceinline__ void wg_fence() { asm volatile("wgmma.fence.sync.aligned;" ::: "memory"); }
__device__ __forceinline__ void wg_commit() { asm volatile("wgmma.commit_group.sync.aligned;" ::: "memory"); }
template <int N>
__device__ __forceinline__ void wg_wait() {
  asm volatile("wgmma.wait_group.sync.aligned %0;" ::"n"(N) : "memory");
}
template <int M>
__device__ __forceinline__ void fence_regs(float (&r)[M]) {
#pragma unroll
  for (int i = 0; i < M; i++) asm volatile("" : "+f"(r[i])::"memory");
}
__device__ __forceinline__ uint64_t mkdesc(uint32_t addr, uint32_t lbo, uint32_t sbo, uint32_t layout) {
  return (uint64_t)((addr & 0x3FFFF) >> 4) | ((uint64_t)(lbo >> 4) << 16) | ((uint64_t)(sbo >> 4) << 32) |
         ((uint64_t)layout << 62);
}
__device__ __forceinline__ uint32_t pack_bf16(float lo, float hi) {
  uint32_t r;
  asm("cvt.rn.bf16x2.f32 %0, %1, %2;" : "=r"(r) : "f"(hi), "f"(lo));
  return r;
}
__device__ __forceinline__ float bf_lo(uint32_t v) { return __uint_as_float(v << 16); }
__device__ __forceinline__ float bf_hi(uint32_t v) { return __uint_as_float(v & 0xFFFF0000u); }
__device__ __forceinline__ float round_bf16(float x) { return bf_lo(pack_bf16(x, 0.f)); }
__device__ __forceinline__ float ex2f(float x) {
  float y;
  asm("ex2.approx.ftz.f32 %0, %1;" : "=f"(y) : "f"(x));
  return y;
}

__device__ __forceinline__ void wgmma_rs_n24_tb(float (&d)[12], uint32_t a0, uint32_t a1, uint32_t a2, uint32_t a3, uint64_t descB, int scaleD) {
  asm volatile("{\n.reg .pred p;\nsetp.ne.b32 p, %17, 0;\n"
    "wgmma.mma_async.sync.aligned.m64n24k16.f32.bf16.bf16 "
    "{%0, %1, %2, %3, %4, %5, %6, %7, %8, %9, %10, %11}, {%12, %13, %14, %15}, %16, p, 1, 1, 1;\n}\n"
    : "+f"(d[0]), "+f"(d[1]), "+f"(d[2]), "+f"(d[3]), "+f"(d[4]), "+f"(d[5]), "+f"(d[6]), "+f"(d[7]),
      "+f"(d[8]), "+f"(d[9]), "+f"(d[10]), "+f"(d[11])
    : "r"(a0), "r"(a1), "r"(a2), "r"(a3), "l"(descB), "r"(scaleD));
}
__device__ __forceinline__ void wgmma_rs_n64_z(float (&d)[32], uint32_t a0, uint32_t a1, uint32_t a2, uint32_t a3, uint64_t descB) {
  asm volatile("{\n.reg .pred p;\nsetp.ne.b32 p, %37, 0;\n"
    "wgmma.mma_async.sync.aligned.m64n64k16.f32.bf16.bf16 "
    "{%0, %1, %2, %3, %4, %5, %6, %7, %8, %9, %10, %11, %12, %13, %14, %15, %16, %17, %18, %19, %20, %21, %22, %23, %24, %25, %26, %27, %28, %29, %30, %31}, {%32, %33, %34, %35}, %36, p, 1, 1, 0;\n}\n"
    : "=f"(d[0]), "=f"(d[1]), "=f"(d[2]), "=f"(d[3]), "=f"(d[4]), "=f"(d[5]), "=f"(d[6]), "=f"(d[7]),
      "=f"(d[8]), "=f"(d[9]), "=f"(d[10]), "=f"(d[11]), "=f"(d[12]), "=f"(d[13]), "=f"(d[14]), "=f"(d[15]),
      "=f"(d[16]), "=f"(d[17]), "=f"(d[18]), "=f"(d[19]), "=f"(d[20]), "=f"(d[21]), "=f"(d[22]), "=f"(d[23]),
      "=f"(d[24]), "=f"(d[25]), "=f"(d[26]), "=f"(d[27]), "=f"(d[28]), "=f"(d[29]), "=f"(d[30]), "=f"(d[31])
    : "r"(a0), "r"(a1), "r"(a2), "r"(a3), "l"(descB), "n"(0));
}
__device__ __forceinline__ void wgmma_ss_n128_tb(float (&d)[64], uint64_t descA, uint64_t descB, int scaleD) {
  asm volatile("{\n.reg .pred p;\nsetp.ne.b32 p, %66, 0;\n"
    "wgmma.mma_async.sync.aligned.m64n128k16.f32.bf16.bf16 "
    "{%0, %1, %2, %3, %4, %5, %6, %7, %8, %9, %10, %11, %12, %13, %14, %15, %16, %17, %18, %19, %20, %21, %22, %23, %24, %25, %26, %27, %28, %29, %30, %31, %32, %33, %34, %35, %36, %37, %38, %39, %40, %41, %42, %43, %44, %45, %46, %47, %48, %49, %50, %51, %52, %53, %54, %55, %56, %57, %58, %59, %60, %61, %62, %63}, %64, %65, p, 1, 1, 0, 1;\n}\n"
    : "+f"(d[0]), "+f"(d[1]), "+f"(d[2]), "+f"(d[3]), "+f"(d[4]), "+f"(d[5]), "+f"(d[6]), "+f"(d[7]),
      "+f"(d[8]), "+f"(d[9]), "+f"(d[10]), "+f"(d[11]), "+f"(d[12]), "+f"(d[13]), "+f"(d[14]), "+f"(d[15]),
      "+f"(d[16]), "+f"(d[17]), "+f"(d[18]), "+f"(d[19]), "+f"(d[20]), "+f"(d[21]), "+f"(d[22]), "+f"(d[23]),
      "+f"(d[24]), "+f"(d[25]), "+f"(d[26]), "+f"(d[27]), "+f"(d[28]), "+f"(d[29]), "+f"(d[30]), "+f"(d[31]),
      "+f"(d[32]), "+f"(d[33]), "+f"(d[34]), "+f"(d[35]), "+f"(d[36]), "+f"(d[37]), "+f"(d[38]), "+f"(d[39]),
      "+f"(d[40]), "+f"(d[41]), "+f"(d[42]), "+f"(d[43]), "+f"(d[44]), "+f"(d[45]), "+f"(d[46]), "+f"(d[47]),
      "+f"(d[48]), "+f"(d[49]), "+f"(d[50]), "+f"(d[51]), "+f"(d[52]), "+f"(d[53]), "+f"(d[54]), "+f"(d[55]),
      "+f"(d[56]), "+f"(d[57]), "+f"(d[58]), "+f"(d[59]), "+f"(d[60]), "+f"(d[61]), "+f"(d[62]), "+f"(d[63])
    : "l"(descA), "l"(descB), "r"(scaleD));
}
__device__ __forceinline__ void wgmma_ss_n192_tb(float (&d)[96], uint64_t descA, uint64_t descB, int scaleD) {
  asm volatile("{\n.reg .pred p;\nsetp.ne.b32 p, %98, 0;\n"
    "wgmma.mma_async.sync.aligned.m64n192k16.f32.bf16.bf16 "
    "{%0, %1, %2, %3, %4, %5, %6, %7, %8, %9, %10, %11, %12, %13, %14, %15, %16, %17, %18, %19, %20, %21, %22, %23, %24, %25, %26, %27, %28, %29, %30, %31, %32, %33, %34, %35, %36, %37, %38, %39, %40, %41, %42, %43, %44, %45, %46, %47, %48, %49, %50, %51, %52, %53, %54, %55, %56, %57, %58, %59, %60, %61, %62, %63, %64, %65, %66, %67, %68, %69, %70, %71, %72, %73, %74, %75, %76, %77, %78, %79, %80, %81, %82, %83, %84, %85, %86, %87, %88, %89, %90, %91, %92, %93, %94, %95}, %96, %97, p, 1, 1, 0, 1;\n}\n"
    : "+f"(d[0]), "+f"(d[1]), "+f"(d[2]), "+f"(d[3]), "+f"(d[4]), "+f"(d[5]), "+f"(d[6]), "+f"(d[7]),
      "+f"(d[8]), "+f"(d[9]), "+f"(d[10]), "+f"(d[11]), "+f"(d[12]), "+f"(d[13]), "+f"(d[14]), "+f"(d[15]),
      "+f"(d[16]), "+f"(d[17]), "+f"(d[18]), "+f"(d[19]), "+f"(d[20]), "+f"(d[21]), "+f"(d[22]), "+f"(d[23]),
      "+f"(d[24]), "+f"(d[25]), "+f"(d[26]), "+f"(d[27]), "+f"(d[28]), "+f"(d[29]), "+f"(d[30]), "+f"(d[31]),
      "+f"(d[32]), "+f"(d[33]), "+f"(d[34]), "+f"(d[35]), "+f"(d[36]), "+f"(d[37]), "+f"(d[38]), "+f"(d[39]),
      "+f"(d[40]), "+f"(d[41]), "+f"(d[42]), "+f"(d[43]), "+f"(d[44]), "+f"(d[45]), "+f"(d[46]), "+f"(d[47]),
      "+f"(d[48]), "+f"(d[49]), "+f"(d[50]), "+f"(d[51]), "+f"(d[52]), "+f"(d[53]), "+f"(d[54]), "+f"(d[55]),
      "+f"(d[56]), "+f"(d[57]), "+f"(d[58]), "+f"(d[59]), "+f"(d[60]), "+f"(d[61]), "+f"(d[62]), "+f"(d[63]),
      "+f"(d[64]), "+f"(d[65]), "+f"(d[66]), "+f"(d[67]), "+f"(d[68]), "+f"(d[69]), "+f"(d[70]), "+f"(d[71]),
      "+f"(d[72]), "+f"(d[73]), "+f"(d[74]), "+f"(d[75]), "+f"(d[76]), "+f"(d[77]), "+f"(d[78]), "+f"(d[79]),
      "+f"(d[80]), "+f"(d[81]), "+f"(d[82]), "+f"(d[83]), "+f"(d[84]), "+f"(d[85]), "+f"(d[86]), "+f"(d[87]),
      "+f"(d[88]), "+f"(d[89]), "+f"(d[90]), "+f"(d[91]), "+f"(d[92]), "+f"(d[93]), "+f"(d[94]), "+f"(d[95])
    : "l"(descA), "l"(descB), "r"(scaleD));
}

__device__ __forceinline__ void ldsm4t(uint32_t (&b)[4], uint32_t addr) {
  asm volatile("ldmatrix.sync.aligned.m8n8.x4.trans.shared.b16 {%0,%1,%2,%3}, [%4];"
               : "=r"(b[0]), "=r"(b[1]), "=r"(b[2]), "=r"(b[3])
               : "r"(addr));
}
__device__ __forceinline__ void hmma(float (&c)[4], uint32_t a0, uint32_t a1, uint32_t a2, uint32_t a3, uint32_t b0, uint32_t b1) {
  asm("mma.sync.aligned.m16n8k16.row.col.f32.bf16.bf16.f32 {%0,%1,%2,%3}, {%4,%5,%6,%7}, {%8,%9}, {%0,%1,%2,%3};"
      : "+f"(c[0]), "+f"(c[1]), "+f"(c[2]), "+f"(c[3])
      : "r"(a0), "r"(a1), "r"(a2), "r"(a3), "r"(b0), "r"(b1));
}

__device__ __forceinline__ uint32_t movm(uint32_t a) {
  uint32_t d;
  asm volatile("movmatrix.sync.aligned.m8n8.trans.b16 %0, %1;" : "=r"(d) : "r"(a));
  return d;
}

constexpr int K1_STAGES = 4;
constexpr int K1_W_BYTES = 3 * 8192;
constexpr int K1_X_BYTES = 8 * 16384;
constexpr int K1_BAR_OFF = K1_X_BYTES + K1_STAGES * K1_W_BYTES;
constexpr int K1_SMEM = K1_BAR_OFF + 192 + 1024;
constexpr float QSCALE = 0.25f * 1.4426950408889634f;

__device__ __forceinline__ uint32_t phi2(uint32_t t2) {
  uint32_t a2, mask, r2, o2;
  asm("add.rn.bf16x2 %0, %1, %2;" : "=r"(a2) : "r"(t2), "r"(0x3F803F80u));
  const uint32_t e2 = pack_bf16(ex2f(bf_lo(t2) * 1.4426950408889634f), ex2f(bf_hi(t2) * 1.4426950408889634f));
  asm("set.gt.u32.bf16x2 %0, %1, %2;" : "=r"(mask) : "r"(t2), "r"(0u));
  r2 = (a2 & mask) | (e2 & ~mask);
  asm("add.rn.bf16x2 %0, %1, %2;" : "=r"(o2) : "r"(r2), "r"(0x35863586u));
  return o2;
}

#define K1_SLOT_KB(h) ((h) < 4 ? 2 * (h) : 2 * ((h) - 4) + 1)
struct EpiCtx {
  uint4* qf;
  uint32_t* kp;
  uint32_t* vp;
  uint32_t* s_red;
  float* red;
  int lane;
};

template <bool LINEAR, int J, int HH, int PART>
__device__ __forceinline__ void epi_slice(const float (&acc)[96], const EpiCtx& c, uint32_t (&pk)[4], float& vmax) {
  constexpr int h = J * 4 + HH;
  const float* a = &acc[HH * 8];
  const float* k = &acc[32 + HH * 8];
  const float* v = &acc[64 + HH * 8];
  if (!LINEAR) {
    if (PART == 0) {
      c.qf[h * 32 * 128] = make_uint4(pack_bf16(a[0] * QSCALE, a[1] * QSCALE), pack_bf16(a[2] * QSCALE, a[3] * QSCALE),
                                      pack_bf16(a[4] * QSCALE, a[5] * QSCALE), pack_bf16(a[6] * QSCALE, a[7] * QSCALE));
      uint32_t* kh = c.kp + h * (KV_HEAD_BYTES / 4);
      kh[0] = pack_bf16(k[0], k[1]);
      kh[64] = pack_bf16(k[2], k[3]);
      kh[32] = pack_bf16(k[4], k[5]);
      kh[96] = pack_bf16(k[6], k[7]);
      float q0 = a[0] * a[0] + a[1] * a[1] + a[4] * a[4] + a[5] * a[5];
      float q1 = a[2] * a[2] + a[3] * a[3] + a[6] * a[6] + a[7] * a[7];
      float k0 = k[0] * k[0] + k[1] * k[1] + k[4] * k[4] + k[5] * k[5];
      float k1 = k[2] * k[2] + k[3] * k[3] + k[6] * k[6] + k[7] * k[7];
#pragma unroll
      for (int o = 1; o <= 2; o <<= 1) {
        q0 += __shfl_xor_sync(0xffffffffu, q0, o);
        q1 += __shfl_xor_sync(0xffffffffu, q1, o);
        k0 += __shfl_xor_sync(0xffffffffu, k0, o);
        k1 += __shfl_xor_sync(0xffffffffu, k1, o);
      }
      const uint32_t qm = __reduce_max_sync(0xffffffffu, max(__float_as_uint(q0) & 0x7FFFFFFFu, __float_as_uint(q1) & 0x7FFFFFFFu));
      const uint32_t km = __reduce_max_sync(0xffffffffu, max(__float_as_uint(k0) & 0x7FFFFFFFu, __float_as_uint(k1) & 0x7FFFFFFFu));
      if (c.lane == 0) {
        atomicMax(&c.s_red[h * 2 + 0], qm);
        atomicMax(&c.s_red[h * 2 + 1], km);
      }
    } else {
      uint32_t* vh = c.vp + h * (KV_HEAD_BYTES / 4);
      vh[0] = pack_bf16(v[0], v[1]);
      vh[96] = pack_bf16(v[2], v[3]);
      vh[32] = pack_bf16(v[4], v[5]);
      vh[128] = pack_bf16(v[6], v[7]);
      vh[64] = 0x3F803F80u;
      vh[160] = 0x3F803F80u;
#pragma unroll
      for (int i = 0; i < 8; i++) asm("max.NaN.f32 %0, %0, %1;" : "+f"(vmax) : "f"(fabsf(v[i])));
    }
  } else {
    if (PART == 0) {
      c.qf[h * 32 * 128] = make_uint4(phi2(pack_bf16(a[0], a[1])), phi2(pack_bf16(a[2], a[3])), phi2(pack_bf16(a[4], a[5])),
                                      phi2(pack_bf16(a[6], a[7])));
      pk[0] = movm(phi2(pack_bf16(k[0], k[1])));
      pk[2] = movm(phi2(pack_bf16(k[2], k[3])));
      pk[1] = movm(phi2(pack_bf16(k[4], k[5])));
      pk[3] = movm(phi2(pack_bf16(k[6], k[7])));
    } else {
      const uint32_t b0 = movm(pack_bf16(v[0], v[1]));
      const uint32_t b1 = movm(pack_bf16(v[2], v[3]));
      const uint32_t b2 = movm(pack_bf16(v[4], v[5]));
      const uint32_t b3 = movm(pack_bf16(v[6], v[7]));
      float c0[4] = {0, 0, 0, 0}, c1[4] = {0, 0, 0, 0}, c2[4] = {0, 0, 0, 0};
      hmma(c0, pk[0], pk[1], pk[2], pk[3], b0, b1);
      hmma(c1, pk[0], pk[1], pk[2], pk[3], b2, b3);
      hmma(c2, pk[0], pk[1], pk[2], pk[3], 0x3F803F80u, 0x3F803F80u);
      float* slot = c.red + K1_SLOT_KB(h) * 4096;
#pragma unroll
      for (int i = 0; i < 4; i++) {
        slot[i * 32] = c0[i];
        slot[(4 + i) * 32] = c1[i];
        slot[(8 + i) * 32] = c2[i];
      }
    }
  }
}

template <bool LINEAR>
__device__ __forceinline__ void qkv_consumer(uint32_t sbase, uint8_t* smem_gen, uint32_t* s_red, int cp, int rt) {
  const uint32_t bar_full = sbase + K1_BAR_OFF;
  const uint32_t bar_empty = bar_full + 8 * K1_STAGES;
  const int warp = threadIdx.x >> 5;
  const int wg = warp >> 2;
  const int lane = threadIdx.x & 31;
  float acc0[96], acc1[96];
#pragma unroll 1
  for (int kb = 0; kb < 8; kb++) {
    const int s = kb % K1_STAGES;
    mbar_wait(bar_full + 8 * s, (kb / K1_STAGES) & 1);
    if (threadIdx.x == 0) PROF_T(0, 2 + (kb >> 1));
    const uint64_t dA = mkdesc(sbase + kb * 16384 + wg * 8192, 16, 1024, 1);
    const uint64_t dB = mkdesc(sbase + K1_X_BYTES + s * K1_W_BYTES, 8192, 1024, 1);
    wg_fence();
#pragma unroll
    for (int k = 0; k < 4; k++) wgmma_ss_n192_tb(acc0, dA + k * 2, dB + k * 128, (kb | k) != 0);
    wg_commit();
    if (kb > 0) {
      wg_wait<1>();
      if ((threadIdx.x & 127) == 0) {
        const int sp = (kb - 1) % K1_STAGES;
        mbar_arrive_cluster(bar_empty + 8 * sp, 0);
        mbar_arrive_cluster(bar_empty + 8 * sp, 1);
      }
    }
  }
  wg_wait<0>();
  fence_regs(acc0);
  if ((threadIdx.x & 127) == 0) {
    mbar_arrive_cluster(bar_empty + 8 * (7 % K1_STAGES), 0);
    mbar_arrive_cluster(bar_empty + 8 * (7 % K1_STAGES), 1);
  }
  if (threadIdx.x == 0) PROF_T(0, 6);

  EpiCtx c;
  {
    const int row0 = rt * 128 + wg * 64 + (warp & 3) * 16;
    c.qf = g_qfrag + ((size_t)((LINEAR ? NH : 0) + cp * 8) * 32 + (rt * 2 + wg)) * 128 + (threadIdx.x & 127);
    uint32_t* img = reinterpret_cast<uint32_t*>(reinterpret_cast<uint8_t*>(g_kv) + (size_t)(cp * 8) * KV_HEAD_BYTES);
    c.kp = img + (row0 >> 3) * 64 + lane;
    c.vp = img + KV_K_BYTES / 4 + (row0 >> 3) * 96 + lane;
    c.s_red = s_red;
    c.red = reinterpret_cast<float*>(smem_gen + wg * 8192) + (warp & 3) * 384 + lane;
    c.lane = lane;
  }
  uint32_t pk[4];
  float vmax = 0.f;
#define K1_T1_STEP(KB)                                                                           \
  {                                                                                              \
    constexpr int g = 8 + KB;                                                                    \
    constexpr int s = g % K1_STAGES;                                                             \
    mbar_wait(bar_full + 8 * s, (g / K1_STAGES) & 1);                                            \
    const uint64_t dA = mkdesc(sbase + KB * 16384 + wg * 8192, 16, 1024, 1);                     \
    const uint64_t dB = mkdesc(sbase + K1_X_BYTES + s * K1_W_BYTES, 8192, 1024, 1);              \
    wg_fence();                                                                                  \
    _Pragma("unroll") for (int k = 0; k < 4; k++) wgmma_ss_n192_tb(acc1, dA + k * 2, dB + k * 128, (KB | k) != 0); \
    wg_commit();                                                                                 \
    epi_slice<LINEAR, 0, KB / 2, KB & 1>(acc0, c, pk, vmax);                                     \
    wg_wait<0>();                                                                                \
    if (KB + K1_STAGES < 8 && (threadIdx.x & 127) == 0) {                                        \
      mbar_arrive_cluster(bar_empty + 8 * s, 0);                                                 \
      mbar_arrive_cluster(bar_empty + 8 * s, 1);                                                 \
    }                                                                                            \
  }
  K1_T1_STEP(0) K1_T1_STEP(1) K1_T1_STEP(2) K1_T1_STEP(3) K1_T1_STEP(4) K1_T1_STEP(5) K1_T1_STEP(6) K1_T1_STEP(7)
#undef K1_T1_STEP
  fence_regs(acc1);
  if (threadIdx.x == 0) PROF_T(0, 10);
  epi_slice<LINEAR, 1, 0, 0>(acc1, c, pk, vmax);
  epi_slice<LINEAR, 1, 0, 1>(acc1, c, pk, vmax);
  epi_slice<LINEAR, 1, 1, 0>(acc1, c, pk, vmax);
  epi_slice<LINEAR, 1, 1, 1>(acc1, c, pk, vmax);
  epi_slice<LINEAR, 1, 2, 0>(acc1, c, pk, vmax);
  epi_slice<LINEAR, 1, 2, 1>(acc1, c, pk, vmax);
  epi_slice<LINEAR, 1, 3, 0>(acc1, c, pk, vmax);
  epi_slice<LINEAR, 1, 3, 1>(acc1, c, pk, vmax);
  if (!LINEAR) {
    const uint32_t vm = __reduce_max_sync(0xffffffffu, __float_as_uint(vmax) & 0x7FFFFFFFu);
    if (lane == 0) atomicMax(&s_red[16], vm);
    asm volatile("bar.sync 1, 256;" ::: "memory");
    if (threadIdx.x < 8) {
      *reinterpret_cast<float4*>(&g_nrm[((cp * 8 + threadIdx.x) * 16 + rt) * 4]) =
          make_float4(__uint_as_float(s_red[threadIdx.x * 2]), __uint_as_float(s_red[threadIdx.x * 2 + 1]), __uint_as_float(s_red[16]), 0.f);
    }
  } else {
    asm volatile("bar.sync 1, 256;" ::: "memory");
    float* dst = g_kvpart + ((size_t)rt * NH + cp * 8) * 384;
#pragma unroll
    for (int i = 0; i < 12; i++) {
      const int o = threadIdx.x + i * 256;
      const int h = o / 384, e = o - h * 384;
      const float* src = reinterpret_cast<const float*>(smem_gen) + K1_SLOT_KB(h) * 4096 + e;
      float sum = 0.f;
#pragma unroll
      for (int w = 0; w < 8; w++) sum += src[(w >> 2) * 2048 + (w & 3) * 384];
      dst[o] = sum;
    }
  }
}

__global__ void __launch_bounds__(384, 1)
qkv_gemm_kernel(const __grid_constant__ CUtensorMap mxA, const __grid_constant__ CUtensorMap mxB,
                const __grid_constant__ CUtensorMap mwA, const __grid_constant__ CUtensorMap mwB) {
  extern __shared__ uint8_t smem_raw[];
  const uint32_t sbase = (smem_u32(smem_raw) + 1023) & ~1023u;
  uint8_t* smem_gen = smem_raw + (sbase - smem_u32(smem_raw));
  const uint32_t bar_full = sbase + K1_BAR_OFF;
  const uint32_t bar_empty = bar_full + 8 * K1_STAGES;
  uint32_t* s_red = reinterpret_cast<uint32_t*>(smem_gen + K1_BAR_OFF + 64);

  const int rank = blockIdx.x & 1;
  const int pair = blockIdx.x >> 1;
  const int branch = pair >> 5;
  const int rp = (pair & 31) >> 2;
  const int cp = pair & 3;
  const int rt = rp * 2 + rank;
  const int warp = threadIdx.x >> 5;
  if (threadIdx.x == 0) { PROF_G(0, 30); PROF_T(0, 0); }
  const CUtensorMap* mx = branch ? &mxA : &mxB;
  const CUtensorMap* mw = branch ? &mwA : &mwB;

  if (threadIdx.x == 256) {
    asm volatile("prefetch.tensormap [%0];" ::"l"(mx) : "memory");
    asm volatile("prefetch.tensormap [%0];" ::"l"(mw) : "memory");
    for (int i = 0; i < K1_STAGES; i++) {
      mbar_init(bar_full + 8 * i, 1);
      mbar_init(bar_empty + 8 * i, 4);
    }
    fence_barrier_init();
    fence_proxy_async();
    for (int kb = 0; kb < K1_STAGES; kb++) mbar_expect_tx(bar_full + 8 * kb, 16384 + K1_W_BYTES);
    tma_load_2d(sbase, mx, 0, rt * 128, bar_full);
  }
  pdl_launch_dependents();
  if (threadIdx.x < 32) s_red[threadIdx.x] = 0;
  __syncthreads();
  cluster_sync_relaxed();
  if (threadIdx.x == 0) PROF_T(0, 1);

  if (warp >= 8) {
    asm volatile("setmaxnreg.dec.sync.aligned.u32 40;");
    if (threadIdx.x == 256) {
      for (int g = 0; g < 16; g++) {
        const int s = g % K1_STAGES;
        const int kb = g & 7;
        if (g >= K1_STAGES) {
          mbar_wait(bar_empty + 8 * s, ((g / K1_STAGES) - 1) & 1);
          mbar_expect_tx(bar_full + 8 * s, (g < 8 ? 16384 : 0) + K1_W_BYTES);
        }
        if (g > 0 && g < 8) tma_load_2d(sbase + kb * 16384, mx, kb * 64, rt * 128, bar_full + 8 * s);
        const int h0 = cp * 8 + (g >> 3) * 4;
        const uint32_t st = sbase + K1_X_BYTES + s * K1_W_BYTES + rank * 4096;
#pragma unroll
        for (int p = 0; p < 3; p++)
          tma_load_2d_mc(st + p * 8192, mw, p * 512 + h0 * 16, kb * 64 + rank * 32, bar_full + 8 * s, (uint16_t)3);
      }
    }
    __syncwarp();
    cluster_sync_relaxed();
  } else {
    asm volatile("setmaxnreg.inc.sync.aligned.u32 232;");
    if (branch == 0) qkv_consumer<false>(sbase, smem_gen, s_red, cp, rt);
    else qkv_consumer<true>(sbase, smem_gen, s_red, cp, rt);
    if (threadIdx.x == 0) PROF_T(0, 11);
    __syncwarp();
    cluster_sync_relaxed();
    if (threadIdx.x == 0) { PROF_T(0, 12); PROF_G(0, 31); }
  }
}

constexpr int K2_SMEM = KV_HEAD_BYTES + 1024 + 256;

#define ATT_NPOLY 18
#define ATT_CH 8
#define ATT_D 1
#define PRO_MODE 1
#define STAGGER 0
#define CONST_SMID 0
#define ATT_STRUCT 1
#define ATT_PIN 0
#define ATT_GM 1
#define ATT_DEG 2
struct ExpC {
  uint32_t k3c00, kmask, seven, c3;
};
__device__ __forceinline__ uint32_t hfma2(uint32_t a, uint32_t b, uint32_t c) {
  uint32_t r;
  asm("fma.rn.f16x2 %0, %1, %2, %3;" : "=r"(r) : "r"(a), "r"(b), "r"(c));
  return r;
}
__device__ __forceinline__ uint32_t exp2_poly_pair(float t0, float t1, const ExpC& c) {
  uint32_t u;
  asm("prmt.b32 %0, %1, %2, 0x5410;" : "=r"(u) : "r"(__float_as_uint(t0)), "r"(__float_as_uint(t1)));
  uint32_t m;
  asm("lop3.b32 %0, %1, 0x03FF03FF, %2, 0xEA;" : "=r"(m) : "r"(u), "r"(c.k3c00));
  uint32_t p = hfma2(m, c.c3, 0xa385a385u);
  p = hfma2(p, m, 0x4ad64ad7u);
  uint32_t mu;
  asm("lop3.b32 %0, %1, 0xFC00FC00, %2, 0xEA;" : "=r"(mu) : "r"(u), "r"(c.kmask));
  uint32_t r;
  asm("{.reg .b32 t; shf.r.wrap.b32 t, %1, %2, 3; add.u32 %0, t, %3;}" : "=r"(r) : "r"(mu), "r"(c.seven), "r"(p));
  return r;
}
__device__ __forceinline__ float gadd(float x, float M, uint32_t g) {
  float r = x;
  asm("{.reg .pred p; setp.ne.b32 p, %2, -1; @p add.f32 %0, %0, %1;}" : "+f"(r) : "f"(M), "r"(g));
  return r;
}
__device__ __forceinline__ float gex2(float x, uint32_t g) {
  float r = x;
  asm("{.reg .pred p; setp.ne.b32 p, %1, -1; @p ex2.approx.ftz.f32 %0, %0;}" : "+f"(r) : "r"(g));
  return r;
}
template <int NPOLY, int NPAIR, int CH, int D, bool G0 = false>
__device__ __forceinline__ void exp_tile(const float (&s)[2 * NPAIR], uint32_t (&p)[NPAIR], const ExpC& c, uint32_t g0 = 0) {
#pragma unroll
  for (int i = 0; i < NPAIR; i++) {
    const bool isPoly = ((i + 1) * NPOLY / 32) != (i * NPOLY / 32);
    const int ch = i / CH;
    const bool gated = ch >= D || G0;
    int gi = (ch - D) * CH + CH - 1;
    if (ch >= D) {
      while (gi > (ch - D) * CH && !(((gi + 1) * NPOLY / 32) != (gi * NPOLY / 32))) gi--;
    }
    const uint32_t g = ch >= D ? p[gi] : g0;
    if (!isPoly) {
      if (gated && ATT_GM) p[i] = pack_bf16(gex2(s[2 * i], g), gex2(s[2 * i + 1], g));
      else p[i] = pack_bf16(ex2f(s[2 * i]), ex2f(s[2 * i + 1]));
    } else {
      if (gated) p[i] = exp2_poly_pair(gadd(s[2 * i], 12329.f, g), gadd(s[2 * i + 1], 12329.f, g), c);
      else p[i] = exp2_poly_pair(s[2 * i] + 12329.f, s[2 * i + 1] + 12329.f, c);
    }
  }
}

__device__ __forceinline__ void store_o(__nv_bfloat16* o, int row0, int head, int lane, const uint32_t (&r)[4]) {
  const int g = lane >> 2, t = lane & 3;
  uint32_t* p0 = reinterpret_cast<uint32_t*>(o + (size_t)(row0 + g) * DM + head * 16) + t;
  uint32_t* p1 = reinterpret_cast<uint32_t*>(o + (size_t)(row0 + g + 8) * DM + head * 16) + t;
  p0[0] = r[0];
  p1[0] = r[1];
  p0[4] = r[2];
  p1[4] = r[3];
}

__device__ __forceinline__ void kv_fetch_piece(uint32_t sbase, uint32_t bar, int piece) {
  const uint8_t* img = reinterpret_cast<const uint8_t*>(g_kv) + (size_t)(blockIdx.x >> 2) * KV_HEAD_BYTES;
  const int g = piece >> 1, isv = piece & 1;
  const int e0 = g == 0 ? 0 : (isv ? 256 : 320) + (g - 1) * 512;
  const int e1 = g == 3 ? 2048 : (isv ? 256 : 320) + g * 512;
  const int bytes = (e1 - e0) * (isv ? 48 : 32);
  const int off = isv ? KV_K_BYTES + e0 * 48 : e0 * 32;
  mbar_expect_tx(bar + 8 * g, bytes);
  bulk_load(sbase + off, img + off, bytes, bar + 8 * g);
}

__device__ __forceinline__ void safe_exp(const float (&s)[32], uint32_t (&p)[16], float (&o)[12], float& m0, float& m1) {
  float x0 = s[0], x1 = s[2];
#pragma unroll
  for (int i = 0; i < 8; i++) {
    x0 = fmaxf(x0, fmaxf(s[4 * i], s[4 * i + 1]));
    x1 = fmaxf(x1, fmaxf(s[4 * i + 2], s[4 * i + 3]));
  }
  x0 = fmaxf(x0, __shfl_xor_sync(0xffffffffu, x0, 1));
  x1 = fmaxf(x1, __shfl_xor_sync(0xffffffffu, x1, 1));
  x0 = fmaxf(x0, __shfl_xor_sync(0xffffffffu, x0, 2));
  x1 = fmaxf(x1, __shfl_xor_sync(0xffffffffu, x1, 2));
  const float n0 = fmaxf(m0, x0), n1 = fmaxf(m1, x1);
  const float c0 = ex2f(m0 - n0), c1 = ex2f(m1 - n1);
  m0 = n0;
  m1 = n1;
#pragma unroll
  for (int i = 0; i < 3; i++) {
    o[4 * i] *= c0;
    o[4 * i + 1] *= c0;
    o[4 * i + 2] *= c1;
    o[4 * i + 3] *= c1;
  }
#pragma unroll
  for (int i = 0; i < 8; i++) {
    p[2 * i] = pack_bf16(ex2f(s[4 * i] - n0), ex2f(s[4 * i + 1] - n0));
    p[2 * i + 1] = pack_bf16(ex2f(s[4 * i + 2] - n1), ex2f(s[4 * i + 3] - n1));
  }
}

__device__ __forceinline__ void attn_step(float (&sx)[32], float (&sy)[32], float (&o)[12], const uint4& qf, uint64_t dK, uint64_t dV,
                                          const ExpC& ec) {
  uint32_t pa[16], pb[16];
  wg_fence();
  wgmma_rs_n64_z(sy, qf.x, qf.y, qf.z, qf.w, dK + 128);
  wg_commit();
  exp_tile<ATT_NPOLY, 16, ATT_CH, ATT_D>(sx, pa, ec);
  wg_fence();
  wgmma_rs_n24_tb(o, pa[12], pa[13], pa[14], pa[15], dV + 3 * 48, 1);
  wg_commit();
  wg_wait<1>();
  fence_regs(sy);
  exp_tile<ATT_NPOLY, 16, ATT_CH, ATT_D>(sy, pb, ec);
  wg_fence();
#pragma unroll
  for (int k = 0; k < 3; k++) wgmma_rs_n24_tb(o, pa[4 * k], pa[4 * k + 1], pa[4 * k + 2], pa[4 * k + 3], dV + k * 48, 1);
#pragma unroll
  for (int k = 0; k < 4; k++) wgmma_rs_n24_tb(o, pb[4 * k], pb[4 * k + 1], pb[4 * k + 2], pb[4 * k + 3], dV + (4 + k) * 48, 1);
  wgmma_rs_n64_z(sy, qf.x, qf.y, qf.z, qf.w, dK + 256);
  wg_commit();
  wg_wait<0>();
  fence_regs(sy);
}

template <bool SAFE>
__device__ __forceinline__ void attn_tile(uint64_t dK, uint64_t dV, uint32_t bar, const uint4 qf, const ExpC& ec, uint32_t (&outp)[4]) {
  float o[12];
#pragma unroll
  for (int i = 0; i < 12; i++) asm volatile("mov.f32 %0, 0f00000000;" : "=f"(o[i]));
  mbar_wait(bar, 0);
  if (!SAFE) {
    float s0[32], s1[32];
    wg_fence();
    wgmma_rs_n64_z(s0, qf.x, qf.y, qf.z, qf.w, dK);
    wg_commit();
    wg_wait<0>();
    fence_regs(s0);
#pragma unroll 1
    for (int p = 0; p < 8; p++) {
      if (p & 1) mbar_wait(bar + 8 * min((p + 1) >> 1, 3), 0);
      attn_step(s0, s1, o, qf, dK, dV, ec);
      attn_step(s1, s0, o, qf, dK + 256, dV + 384, ec);
      dK += 512;
      dV += 768;
    }
  } else {
    float m0 = -INFINITY, m1 = -INFINITY;
#pragma unroll 1
    for (int j = 0; j < 32; j++) {
      if (j == 4) { mbar_wait(bar + 8, 0); mbar_wait(bar + 16, 0); mbar_wait(bar + 24, 0); }
      float s[32];
      uint32_t p[16];
      wg_fence();
      wgmma_rs_n64_z(s, qf.x, qf.y, qf.z, qf.w, dK);
      wg_commit();
      wg_wait<0>();
      fence_regs(s);
      safe_exp(s, p, o, m0, m1);
      wg_fence();
#pragma unroll
      for (int k = 0; k < 4; k++) wgmma_rs_n24_tb(o, p[4 * k], p[4 * k + 1], p[4 * k + 2], p[4 * k + 3], dV + k * 48, 1);
      wg_commit();
      wg_wait<0>();
      fence_regs(o);
      dK += 128;
      dV += 192;
    }
  }
  fence_regs(o);
  const float r0 = 1.0f / o[8], r1 = 1.0f / o[10];
  outp[0] = pack_bf16(o[0] * r0, o[1] * r0);
  outp[1] = pack_bf16(o[2] * r1, o[3] * r1);
  outp[2] = pack_bf16(o[4] * r0, o[5] * r0);
  outp[3] = pack_bf16(o[6] * r1, o[7] * r1);
}

__device__ __forceinline__ void linear_attn_cta(uint8_t* smem_raw, uint32_t sbase, const CUtensorMap* mo16, int cta) {
  const int warp = threadIdx.x >> 5, lane = threadIdx.x & 31;
  float* red = reinterpret_cast<float*>(smem_raw + (sbase - smem_u32(smem_raw)) + 131072);
  {
    const float* src = g_kvpart + (size_t)cta * 8 * 384;
    float sum[6];
#pragma unroll
    for (int i = 0; i < 6; i++) sum[i] = 0.f;
#pragma unroll
    for (int r = 0; r < 16; r++) {
#pragma unroll
      for (int i = 0; i < 6; i++) sum[i] += src[(size_t)r * NH * 384 + threadIdx.x + i * 512];
    }
#pragma unroll
    for (int i = 0; i < 6; i++) red[threadIdx.x + i * 512] = round_bf16(sum[i]);
  }
  __syncthreads();
  uint32_t bf[8][6];
  {
    const int g = lane >> 2, t = lane & 3;
#pragma unroll
    for (int h = 0; h < 8; h++) {
#pragma unroll
      for (int f = 0; f < 6; f++) {
        const int blk = f >> 1, half = f & 1;
        const int e = (blk == 2) ? 0 : g;
        const int d = 2 * t + 8 * half;
        const int base = h * 384 + (blk * 4 + half * 2 + (e & 1)) * 32 + (e >> 1);
        bf[h][f] = pack_bf16(red[base + (d & 7) * 4], red[base + ((d + 1) & 7) * 4]);
      }
    }
  }
  const uint32_t stg = sbase + warp * 8192;
#pragma unroll 1
  for (int rb = 0; rb < 8; rb++) {
    const int blk16 = rb * 16 + warp;
    const uint4* qp = g_qfrag + ((size_t)(NH + cta * 8) * 32 + (blk16 >> 2)) * 128 + (blk16 & 3) * 32 + lane;
    uint4 q[8];
#pragma unroll
    for (int h = 0; h < 8; h++) q[h] = qp[h * 32 * 128];
    const uint32_t buf = stg + (rb & 1) * 4096;
    if (rb >= 2) {
      if (lane == 0) asm volatile("cp.async.bulk.wait_group.read 1;" ::: "memory");
      __syncwarp();
    }
#pragma unroll
    for (int h = 0; h < 8; h++) {
      float n0[4] = {0, 0, 0, 0}, n1[4] = {0, 0, 0, 0}, dn[4] = {0, 0, 0, 0};
      hmma(n0, q[h].x, q[h].y, q[h].z, q[h].w, bf[h][0], bf[h][1]);
      hmma(n1, q[h].x, q[h].y, q[h].z, q[h].w, bf[h][2], bf[h][3]);
      hmma(dn, q[h].x, q[h].y, q[h].z, q[h].w, bf[h][4], bf[h][5]);
      const float d0 = round_bf16(round_bf16(dn[0]) + 1e-6f), d1 = round_bf16(round_bf16(dn[2]) + 1e-6f);
      const uint32_t r0 = pack_bf16(__fdividef(round_bf16(n0[0]), d0), __fdividef(round_bf16(n0[1]), d0));
      const uint32_t r1 = pack_bf16(__fdividef(round_bf16(n0[2]), d1), __fdividef(round_bf16(n0[3]), d1));
      const uint32_t r2 = pack_bf16(__fdividef(round_bf16(n1[0]), d0), __fdividef(round_bf16(n1[1]), d0));
      const uint32_t r3 = pack_bf16(__fdividef(round_bf16(n1[2]), d1), __fdividef(round_bf16(n1[3]), d1));
      const int row = lane & 15;
      const int chunk = (h & 3) * 2 + (lane >> 4);
      const uint32_t addr = buf + (h >> 2) * 2048 + row * 128 + ((chunk ^ (row & 7)) << 4);
      asm volatile("stmatrix.sync.aligned.m8n8.x4.shared.b16 [%0], {%1,%2,%3,%4};" ::"r"(addr), "r"(r0), "r"(r1), "r"(r2), "r"(r3)
                   : "memory");
    }
    fence_proxy_async();
    __syncwarp();
    if (lane == 0) {
      tma_store_2d(mo16, buf, cta * 128, blk16 * 16);
      tma_store_2d(mo16, buf + 2048, cta * 128 + 64, blk16 * 16);
      asm volatile("cp.async.bulk.commit_group;" ::: "memory");
    }
  }
  if (lane == 0) asm volatile("cp.async.bulk.wait_group 0;" ::: "memory");
}

__global__ void __launch_bounds__(512, 1) attn_kernel(const __grid_constant__ CUtensorMap mo16) {
  extern __shared__ uint8_t smem_raw[];
  const uint32_t sbase = (smem_u32(smem_raw) + 1023) & ~1023u;
  const uint32_t bar = sbase + KV_HEAD_BYTES;
  if (threadIdx.x == 0) { PROF_G(1, 30); PROF_T(1, 0); }
  if (threadIdx.x == 0) {
    for (int i = 0; i < 4; i++) mbar_init(bar + 8 * i, 2);
    asm volatile("st.shared.v4.u32 [%0], {%1, %2, %3, %4};" ::"r"(bar + 64), "r"(0x3C003C00u), "r"(0x00070000u), "r"(7u),
                 "r"(ATT_DEG == 3 ? 0x2cfd2cfdu : 0x35623562u)
                 : "memory");
    fence_barrier_init();
    fence_proxy_async();
  }
  __syncthreads();
  pdl_launch_dependents();
  pdl_wait();
  if (threadIdx.x == 0) { PROF_T(1, 7); PROF_G(1, 29); }
  if (blockIdx.x >= 128) {
    linear_attn_cta(smem_raw, sbase, &mo16, blockIdx.x - 128);
    if (threadIdx.x == 0) { PROF_T(1, 5); PROF_G(1, 31); }
    return;
  }
  const int head = blockIdx.x >> 2, qb = blockIdx.x & 3;
  const int lane = threadIdx.x & 31;
  const int wg = threadIdx.x >> 7, warp = (threadIdx.x >> 5) & 3;
  if (threadIdx.x == 0) {
#pragma unroll
    for (int piece = 0; piece < 8; piece++) kv_fetch_piece(sbase, bar, piece);
  }
  uint4 qnext = g_qfrag[(head * 32 + qb * 8 + wg * 2) * 128 + (threadIdx.x & 127)];
  float4 n = make_float4(0.f, 0.f, 0.f, 0.f);
  if (lane < 16) n = *reinterpret_cast<const float4*>(&g_nrm[(head * 16 + lane) * 4]);
  bool safe_path;
  {
    uint32_t qm = ((lane >> 2) == qb) ? __float_as_uint(n.x) : 0u;
    qm = __reduce_max_sync(0xffffffffu, qm);
    const uint32_t km = __reduce_max_sync(0xffffffffu, __float_as_uint(n.y));
    const uint32_t vm = __reduce_max_sync(0xffffffffu, __float_as_uint(n.z));
    const float b2 = __uint_as_float(qm) * (QSCALE * QSCALE) * __uint_as_float(km) * 1.02f;
    const float vmax = __uint_as_float(vm);
    const bool ok = (b2 <= 21.5f * 21.5f) && (vmax <= 1.0e24f) && (vmax >= 1.0e-18f || vmax == 0.f);
    safe_path = !ok;
  }
  ExpC ec;
  asm volatile("ld.volatile.shared.v4.u32 {%0, %1, %2, %3}, [%4];" : "=r"(ec.k3c00), "=r"(ec.kmask), "=r"(ec.seven), "=r"(ec.c3) : "r"(bar + 64));
  const uint64_t dK = mkdesc(sbase, 128, 256, 0);
  const uint64_t dV = mkdesc(sbase + KV_K_BYTES, 384, 128, 0);
#pragma unroll 1
  for (int t = 0; t < 2; t++) {
    const int tile64 = qb * 8 + wg * 2 + t;
    const uint4 qf = qnext;
    if (t == 0) qnext = g_qfrag[(head * 32 + tile64 + 1) * 128 + (threadIdx.x & 127)];
    uint32_t r[4];
    if (threadIdx.x == 0) PROF_T(1, 1 + t);
    if (!safe_path) attn_tile<false>(dK, dV, bar, qf, ec, r);
    else attn_tile<true>(dK, dV, bar, qf, ec, r);
    store_o(g_o + (size_t)S_LEN * DM, tile64 * 64 + warp * 16, head, lane, r);
  }
  if (threadIdx.x == 0) { PROF_T(1, 5); PROF_G(1, 31); }
}

constexpr int K3_STAGES = 5;
constexpr int K3_W_BYTES = 8 * 16384;
constexpr int K3_BAR_OFF = K3_W_BYTES + K3_STAGES * 16384;
constexpr int K3_SMEM = K3_BAR_OFF + 256 + 1024;

__global__ void __launch_bounds__(288, 1)
out_gemm_kernel(const __grid_constant__ CUtensorMap mo, const __grid_constant__ CUtensorMap mwA,
                const __grid_constant__ CUtensorMap mwB, const __grid_constant__ CUtensorMap mout) {
  extern __shared__ uint8_t smem_raw[];
  const uint32_t sbase = (smem_u32(smem_raw) + 1023) & ~1023u;
  const uint32_t bar_full = sbase + K3_BAR_OFF;
  const uint32_t bar_empty = bar_full + 8 * K3_STAGES;
  const uint32_t bar_w = bar_empty + 8 * K3_STAGES;
  const int branch = blockIdx.x >> 6;
  const int rt = (blockIdx.x & 63) >> 2;
  const int ct = blockIdx.x & 3;
  const int warp = threadIdx.x >> 5;
  if (threadIdx.x == 0) { PROF_G(2, 30); PROF_T(2, 0); }
  if (threadIdx.x == 256) {
    const CUtensorMap* mw = branch ? &mwB : &mwA;
    asm volatile("prefetch.tensormap [%0];" ::"l"(mw) : "memory");
    asm volatile("prefetch.tensormap [%0];" ::"l"(&mo) : "memory");
    asm volatile("prefetch.tensormap [%0];" ::"l"(&mout) : "memory");
    for (int i = 0; i < K3_STAGES; i++) {
      mbar_init(bar_full + 8 * i, 1);
      mbar_init(bar_empty + 8 * i, 2);
    }
    for (int i = 0; i < 8; i++) mbar_init(bar_w + 8 * i, 1);
    fence_barrier_init();
    fence_proxy_async();
    for (int kb = 0; kb < 8; kb++) {
      mbar_expect_tx(bar_w + 8 * kb, 16384);
      tma_load_2d(sbase + kb * 16384, mw, ct * 128, kb * 64, bar_w + 8 * kb);
      tma_load_2d(sbase + kb * 16384 + 8192, mw, ct * 128 + 64, kb * 64, bar_w + 8 * kb);
    }
  }
  __syncthreads();
  if (warp == 8) {
    if ((threadIdx.x & 31) == 0) {
      pdl_wait();
      PROF_T(2, 1);
      for (int kb = 0; kb < 8; kb++) {
        const int s = kb % K3_STAGES;
        if (kb >= K3_STAGES) mbar_wait(bar_empty + 8 * s, ((kb / K3_STAGES) - 1) & 1);
        mbar_expect_tx(bar_full + 8 * s, 16384);
        tma_load_2d(sbase + K3_W_BYTES + s * 16384, &mo, kb * 64, branch * S_LEN + rt * 128, bar_full + 8 * s);
      }
    }
  } else {
    const int wg = warp >> 2;
    float acc[64];
    for (int kb = 0; kb < 8; kb++) {
      const int s = kb % K3_STAGES;
      mbar_wait(bar_w + 8 * kb, 0);
      mbar_wait(bar_full + 8 * s, (kb / K3_STAGES) & 1);
      if (threadIdx.x == 0) PROF_T(2, 2 + kb);
      const uint64_t dA = mkdesc(sbase + K3_W_BYTES + s * 16384 + wg * 8192, 16, 1024, 1);
      const uint64_t dB = mkdesc(sbase + kb * 16384, 8192, 1024, 1);
      wg_fence();
#pragma unroll
      for (int k = 0; k < 4; k++) wgmma_ss_n128_tb(acc, dA + k * 2, dB + k * 128, (kb | k) != 0);
      wg_commit();
      if (kb > 0) {
        wg_wait<1>();
        if ((threadIdx.x & 127) == 0) mbar_arrive(bar_empty + 8 * ((kb - 1) % K3_STAGES));
      }
    }
    wg_wait<0>();
    fence_regs(acc);
    if (threadIdx.x == 0) PROF_T(2, 10);
    const uint32_t stg = sbase + K3_W_BYTES + wg * 8192;
    asm volatile("bar.sync 1, 256;" ::: "memory");
    const int lane = threadIdx.x & 31;
    const int rloc = (warp & 3) * 16 + (lane & 15);
#pragma unroll
    for (int c16 = 0; c16 < 8; c16++) {
      const float* a = &acc[c16 * 8];
      const uint32_t r0 = pack_bf16(a[0], a[1]), r1 = pack_bf16(a[2], a[3]), r2 = pack_bf16(a[4], a[5]), r3 = pack_bf16(a[6], a[7]);
      const int chunk = (c16 & 3) * 2 + (lane >> 4);
      const uint32_t addr = stg + (c16 >> 2) * 16384 + rloc * 128 + ((chunk ^ (rloc & 7)) << 4);
      asm volatile("stmatrix.sync.aligned.m8n8.x4.shared.b16 [%0], {%1,%2,%3,%4};" ::"r"(addr), "r"(r0), "r"(r1), "r"(r2), "r"(r3)
                   : "memory");
    }
    fence_proxy_async();
    asm volatile("bar.sync %0, 128;" ::"r"(2 + wg) : "memory");
    if ((threadIdx.x & 127) == 0) {
      tma_store_2d(&mout, stg, branch * DM + ct * 128, rt * 128 + wg * 64);
      tma_store_2d(&mout, stg + 16384, branch * DM + ct * 128 + 64, rt * 128 + wg * 64);
      asm volatile("cp.async.bulk.commit_group;" ::: "memory");
      asm volatile("cp.async.bulk.wait_group.read 0;" ::: "memory");
      if (threadIdx.x == 0) { PROF_T(2, 12); PROF_G(2, 31); }
    }
  }
}

typedef CUresult (*EncodeFn)(CUtensorMap*, CUtensorMapDataType, cuuint32_t, void*, const cuuint64_t*, const cuuint64_t*,
                             const cuuint32_t*, const cuuint32_t*, CUtensorMapInterleave, CUtensorMapSwizzle,
                             CUtensorMapL2promotion, CUtensorMapFloatOOBfill);

void make_map(EncodeFn enc, CUtensorMap* m, const void* ptr, uint64_t inner, uint64_t outer, uint32_t box_inner, uint32_t box_outer) {
  cuuint64_t dims[2] = {inner, outer};
  cuuint64_t strides[1] = {inner * 2};
  cuuint32_t box[2] = {box_inner, box_outer};
  cuuint32_t es[2] = {1, 1};
  enc(m, CU_TENSOR_MAP_DATA_TYPE_BFLOAT16, 2, const_cast<void*>(ptr), dims, strides, box, es, CU_TENSOR_MAP_INTERLEAVE_NONE,
      CU_TENSOR_MAP_SWIZZLE_128B, CU_TENSOR_MAP_L2_PROMOTION_L2_256B, CU_TENSOR_MAP_FLOAT_OOB_FILL_NONE);
}

struct HostState {
  bool init;
  const void* key[7];
  CUtensorMap mxA, mxB, mwA, mwB, mo, mo16, mwoA, mwoB, mout;
};
HostState g_hs;

}

extern "C" void kernel_launch(void* const* d_in, const int* in_sizes, int n_in, void* d_out, int out_size) {
  (void)in_sizes; (void)n_in; (void)out_size;
  HostState& hs = g_hs;
  bool same = hs.init && hs.key[6] == d_out;
  for (int i = 0; i < 6 && same; i++) same = hs.key[i] == d_in[i];
  if (!same) {
    void* fn = nullptr;
    cudaDriverEntryPointQueryResult qr;
    cudaGetDriverEntryPoint("cuTensorMapEncodeTiled", &fn, cudaEnableDefault, &qr);
    EncodeFn enc = (EncodeFn)fn;
    void* go = nullptr;
    cudaGetSymbolAddress(&go, g_o);
    make_map(enc, &hs.mxA, d_in[0], 512, 2048, 64, 128);
    make_map(enc, &hs.mwA, d_in[1], 1536, 512, 64, 32);
    make_map(enc, &hs.mwoA, d_in[2], 512, 512, 64, 64);
    make_map(enc, &hs.mxB, d_in[3], 512, 2048, 64, 128);
    make_map(enc, &hs.mwB, d_in[4], 1536, 512, 64, 32);
    make_map(enc, &hs.mwoB, d_in[5], 512, 512, 64, 64);
    make_map(enc, &hs.mo, go, 512, 4096, 64, 128);
    make_map(enc, &hs.mo16, go, 512, 4096, 64, 16);
    make_map(enc, &hs.mout, d_out, 1024, 2048, 64, 64);
    cudaFuncSetAttribute(qkv_gemm_kernel, cudaFuncAttributeMaxDynamicSharedMemorySize, K1_SMEM);
    cudaFuncSetAttribute(attn_kernel, cudaFuncAttributeMaxDynamicSharedMemorySize, K2_SMEM);
    cudaFuncSetAttribute(out_gemm_kernel, cudaFuncAttributeMaxDynamicSharedMemorySize, K3_SMEM);
    for (int i = 0; i < 6; i++) hs.key[i] = d_in[i];
    hs.key[6] = d_out;
    hs.init = true;
  }
  cudaStream_t st = cudaStreamPerThread;
  {
    cudaLaunchConfig_t cfg = {};
    cfg.gridDim = dim3(128);
    cfg.blockDim = dim3(384);
    cfg.dynamicSmemBytes = K1_SMEM;
    cfg.stream = st;
    cudaLaunchAttribute at[1];
    at[0].id = cudaLaunchAttributeClusterDimension;
    at[0].val.clusterDim.x = 2;
    at[0].val.clusterDim.y = 1;
    at[0].val.clusterDim.z = 1;
    cfg.attrs = at;
    cfg.numAttrs = 1;
    cudaLaunchKernelEx(&cfg, qkv_gemm_kernel, hs.mxA, hs.mxB, hs.mwA, hs.mwB);
  }
  {
    cudaLaunchConfig_t cfg = {};
    cfg.gridDim = dim3(132);
    cfg.blockDim = dim3(512);
    cfg.dynamicSmemBytes = K2_SMEM;
    cfg.stream = st;
    cudaLaunchAttribute at[1];
    at[0].id = cudaLaunchAttributeProgrammaticStreamSerialization;
    at[0].val.programmaticStreamSerializationAllowed = 1;
    cfg.attrs = at;
    cfg.numAttrs = 1;
    cudaLaunchKernelEx(&cfg, attn_kernel, hs.mo16);
    cfg.gridDim = dim3(128);
    cfg.blockDim = dim3(288);
    cfg.dynamicSmemBytes = K3_SMEM;
    cudaLaunchKernelEx(&cfg, out_gemm_kernel, hs.mo, hs.mwoA, hs.mwoB, hs.mout);
  }
}
```

```cpp
#include <cuda_runtime.h>
#include <cuda_bf16.h>
#include <cuda.h>
#include <stdint.h>

namespace {

constexpr int S_LEN = 2048;
constexpr int DM = 512;
constexpr int NH = 32;

constexpr int KV_K_BYTES = 65536;
constexpr int KV_HEAD_BYTES = KV_K_BYTES + 98304;
__device__ uint4 g_qfrag[2 * NH * 32 * 128];
__device__ uint4 g_kv[NH * KV_HEAD_BYTES / 16];
__device__ float g_kvpart[16 * NH * 384];
__device__ float g_nrm[NH * 16 * 4];
__device__ __nv_bfloat16 g_o[2 * S_LEN * DM];

#define g_prof_set(k, i, v)
#define g_prof_dummy(i) true
#define PROF_T(k, i) do {} while (0)
#define PROF_G(k, i) do {} while (0)
__device__ __forceinline__ uint32_t smem_u32(const void* p) { return (uint32_t)__cvta_generic_to_shared(p); }
__device__ __forceinline__ void mbar_init(uint32_t bar, int cnt) {
  asm volatile("mbarrier.init.shared::cta.b64 [%0], %1;" ::"r"(bar), "r"(cnt) : "memory");
}
__device__ __forceinline__ void mbar_expect_tx(uint32_t bar, uint32_t bytes) {
  asm volatile("mbarrier.arrive.expect_tx.shared::cta.b64 _, [%0], %1;" ::"r"(bar), "r"(bytes) : "memory");
}
__device__ __forceinline__ void mbar_arrive(uint32_t bar) {
  asm volatile("mbarrier.arrive.shared::cta.b64 _, [%0];" ::"r"(bar) : "memory");
}
__device__ __forceinline__ void mbar_arrive_cluster(uint32_t bar, uint32_t cta) {
  asm volatile(
      "{\n.reg .b32 ra;\nmapa.shared::cluster.u32 ra, %0, %1;\n"
      "mbarrier.arrive.shared::cluster.b64 _, [ra];\n}" ::"r"(bar), "r"(cta) : "memory");
}
__device__ __forceinline__ void mbar_wait(uint32_t bar, uint32_t parity) {
  asm volatile(
      "{\n.reg .pred p;\n.reg .u32 n;\n"
      "mov.u32 n, 0;\n"
      "WAIT_LOOP:\n"
      "mbarrier.try_wait.parity.shared::cta.b64 p, [%0], %1, 0x400000;\n"
      "@p bra WAIT_DONE;\n"
      "add.u32 n, n, 1;\n"
      "setp.lt.u32 p, n, 4000000;\n"
      "@p bra WAIT_LOOP;\n"
      "trap;\n"
      "WAIT_DONE:\n}" ::"r"(bar), "r"(parity) : "memory");
}
__device__ __forceinline__ void fence_barrier_init() {
  asm volatile("fence.mbarrier_init.release.cluster;" ::: "memory");
}
__device__ __forceinline__ void fence_proxy_async() { asm volatile("fence.proxy.async.shared::cta;" ::: "memory"); }
__device__ __forceinline__ void cluster_sync_relaxed() {
  asm volatile("barrier.cluster.arrive.relaxed.aligned;\nbarrier.cluster.wait.aligned;" ::: "memory");
}
__device__ __forceinline__ void tma_load_2d(uint32_t dst, const CUtensorMap* m, int x, int y, uint32_t bar) {
  asm volatile(
      "cp.async.bulk.tensor.2d.shared::cluster.global.mbarrier::complete_tx::bytes [%0], [%1, {%3, %4}], [%2];" ::"r"(dst),
      "l"(m), "r"(bar), "r"(x), "r"(y)
      : "memory");
}
__device__ __forceinline__ void tma_load_2d_mc(uint32_t dst, const CUtensorMap* m, int x, int y, uint32_t bar, uint16_t mask) {
  asm volatile(
      "cp.async.bulk.tensor.2d.shared::cluster.global.mbarrier::complete_tx::bytes.multicast::cluster [%0], [%1, {%3, %4}], "
      "[%2], %5;" ::"r"(dst),
      "l"(m), "r"(bar), "r"(x), "r"(y), "h"(mask)
      : "memory");
}
__device__ __forceinline__ void tma_store_2d(const CUtensorMap* m, uint32_t src, int x, int y) {
  asm volatile("cp.async.bulk.tensor.2d.global.shared::cta.bulk_group [%0, {%2, %3}], [%1];" ::"l"(m), "r"(src), "r"(x),
               "r"(y)
               : "memory");
}
__device__ __forceinline__ void bulk_load(uint32_t dst, const void* src, uint32_t bytes, uint32_t bar) {
  asm volatile("cp.async.bulk.shared::cluster.global.mbarrier::complete_tx::bytes [%0], [%1], %2, [%3];" ::"r"(dst),
               "l"(src), "r"(bytes), "r"(bar)
               : "memory");
}
__device__ __forceinline__ void bulk_load_mc(uint32_t dst, const void* src, uint32_t bytes, uint32_t bar, uint16_t mask) {
  asm volatile("cp.async.bulk.shared::cluster.global.mbarrier::complete_tx::bytes.multicast::cluster [%0], [%1], %2, [%3], %4;" ::"r"(dst),
               "l"(src), "r"(bytes), "r"(bar), "h"(mask)
               : "memory");
}
__device__ __forceinline__ void pdl_launch_dependents() { asm volatile("griddepcontrol.launch_dependents;" ::: "memory"); }
__device__ __forceinline__ void pdl_wait() { asm volatile("griddepcontrol.wait;" ::: "memory"); }
__device__ __forceinline__ void wg_fence() { asm volatile("wgmma.fence.sync.aligned;" ::: "memory"); }
__device__ __forceinline__ void wg_commit() { asm volatile("wgmma.commit_group.sync.aligned;" ::: "memory"); }
template <int N>
__device__ __forceinline__ void wg_wait() {
  asm volatile("wgmma.wait_group.sync.aligned %0;" ::"n"(N) : "memory");
}
template <int M>
__device__ __forceinline__ void fence_regs(float (&r)[M]) {
#pragma unroll
  for (int i = 0; i < M; i++) asm volatile("" : "+f"(r[i])::"memory");
}
__device__ __forceinline__ uint64_t mkdesc(uint32_t addr, uint32_t lbo, uint32_t sbo, uint32_t layout) {
  return (uint64_t)((addr & 0x3FFFF) >> 4) | ((uint64_t)(lbo >> 4) << 16) | ((uint64_t)(sbo >> 4) << 32) |
         ((uint64_t)layout << 62);
}
__device__ __forceinline__ uint32_t pack_bf16(float lo, float hi) {
  uint32_t r;
  asm("cvt.rn.bf16x2.f32 %0, %1, %2;" : "=r"(r) : "f"(hi), "f"(lo));
  return r;
}
__device__ __forceinline__ float bf_lo(uint32_t v) { return __uint_as_float(v << 16); }
__device__ __forceinline__ float bf_hi(uint32_t v) { return __uint_as_float(v & 0xFFFF0000u); }
__device__ __forceinline__ float round_bf16(float x) { return bf_lo(pack_bf16(x, 0.f)); }
__device__ __forceinline__ float ex2f(float x) {
  float y;
  asm("ex2.approx.ftz.f32 %0, %1;" : "=f"(y) : "f"(x));
  return y;
}

__device__ __forceinline__ void wgmma_rs_n24_tb(float (&d)[12], uint32_t a0, uint32_t a1, uint32_t a2, uint32_t a3, uint64_t descB, int scaleD) {
  asm volatile("{\n.reg .pred p;\nsetp.ne.b32 p, %17, 0;\n"
    "wgmma.mma_async.sync.aligned.m64n24k16.f32.bf16.bf16 "
    "{%0, %1, %2, %3, %4, %5, %6, %7, %8, %9, %10, %11}, {%12, %13, %14, %15}, %16, p, 1, 1, 1;\n}\n"
    : "+f"(d[0]), "+f"(d[1]), "+f"(d[2]), "+f"(d[3]), "+f"(d[4]), "+f"(d[5]), "+f"(d[6]), "+f"(d[7]),
      "+f"(d[8]), "+f"(d[9]), "+f"(d[10]), "+f"(d[11])
    : "r"(a0), "r"(a1), "r"(a2), "r"(a3), "l"(descB), "r"(scaleD));
}
__device__ __forceinline__ void wgmma_rs_n64_z(float (&d)[32], uint32_t a0, uint32_t a1, uint32_t a2, uint32_t a3, uint64_t descB) {
  asm volatile("{\n.reg .pred p;\nsetp.ne.b32 p, %37, 0;\n"
    "wgmma.mma_async.sync.aligned.m64n64k16.f32.bf16.bf16 "
    "{%0, %1, %2, %3, %4, %5, %6, %7, %8, %9, %10, %11, %12, %13, %14, %15, %16, %17, %18, %19, %20, %21, %22, %23, %24, %25, %26, %27, %28, %29, %30, %31}, {%32, %33, %34, %35}, %36, p, 1, 1, 0;\n}\n"
    : "=f"(d[0]), "=f"(d[1]), "=f"(d[2]), "=f"(d[3]), "=f"(d[4]), "=f"(d[5]), "=f"(d[6]), "=f"(d[7]),
      "=f"(d[8]), "=f"(d[9]), "=f"(d[10]), "=f"(d[11]), "=f"(d[12]), "=f"(d[13]), "=f"(d[14]), "=f"(d[15]),
      "=f"(d[16]), "=f"(d[17]), "=f"(d[18]), "=f"(d[19]), "=f"(d[20]), "=f"(d[21]), "=f"(d[22]), "=f"(d[23]),
      "=f"(d[24]), "=f"(d[25]), "=f"(d[26]), "=f"(d[27]), "=f"(d[28]), "=f"(d[29]), "=f"(d[30]), "=f"(d[31])
    : "r"(a0), "r"(a1), "r"(a2), "r"(a3), "l"(descB), "n"(0));
}
__device__ __forceinline__ void wgmma_ss_n128_tb(float (&d)[64], uint64_t descA, uint64_t descB, int scaleD) {
  asm volatile("{\n.reg .pred p;\nsetp.ne.b32 p, %66, 0;\n"
    "wgmma.mma_async.sync.aligned.m64n128k16.f32.bf16.bf16 "
    "{%0, %1, %2, %3, %4, %5, %6, %7, %8, %9, %10, %11, %12, %13, %14, %15, %16, %17, %18, %19, %20, %21, %22, %23, %24, %25, %26, %27, %28, %29, %30, %31, %32, %33, %34, %35, %36, %37, %38, %39, %40, %41, %42, %43, %44, %45, %46, %47, %48, %49, %50, %51, %52, %53, %54, %55, %56, %57, %58, %59, %60, %61, %62, %63}, %64, %65, p, 1, 1, 0, 1;\n}\n"
    : "+f"(d[0]), "+f"(d[1]), "+f"(d[2]), "+f"(d[3]), "+f"(d[4]), "+f"(d[5]), "+f"(d[6]), "+f"(d[7]),
      "+f"(d[8]), "+f"(d[9]), "+f"(d[10]), "+f"(d[11]), "+f"(d[12]), "+f"(d[13]), "+f"(d[14]), "+f"(d[15]),
      "+f"(d[16]), "+f"(d[17]), "+f"(d[18]), "+f"(d[19]), "+f"(d[20]), "+f"(d[21]), "+f"(d[22]), "+f"(d[23]),
      "+f"(d[24]), "+f"(d[25]), "+f"(d[26]), "+f"(d[27]), "+f"(d[28]), "+f"(d[29]), "+f"(d[30]), "+f"(d[31]),
      "+f"(d[32]), "+f"(d[33]), "+f"(d[34]), "+f"(d[35]), "+f"(d[36]), "+f"(d[37]), "+f"(d[38]), "+f"(d[39]),
      "+f"(d[40]), "+f"(d[41]), "+f"(d[42]), "+f"(d[43]), "+f"(d[44]), "+f"(d[45]), "+f"(d[46]), "+f"(d[47]),
      "+f"(d[48]), "+f"(d[49]), "+f"(d[50]), "+f"(d[51]), "+f"(d[52]), "+f"(d[53]), "+f"(d[54]), "+f"(d[55]),
      "+f"(d[56]), "+f"(d[57]), "+f"(d[58]), "+f"(d[59]), "+f"(d[60]), "+f"(d[61]), "+f"(d[62]), "+f"(d[63])
    : "l"(descA), "l"(descB), "r"(scaleD));
}
__device__ __forceinline__ void wgmma_ss_n192_tb(float (&d)[96], uint64_t descA, uint64_t descB, int scaleD) {
  asm volatile("{\n.reg .pred p;\nsetp.ne.b32 p, %98, 0;\n"
    "wgmma.mma_async.sync.aligned.m64n192k16.f32.bf16.bf16 "
    "{%0, %1, %2, %3, %4, %5, %6, %7, %8, %9, %10, %11, %12, %13, %14, %15, %16, %17, %18, %19, %20, %21, %22, %23, %24, %25, %26, %27, %28, %29, %30, %31, %32, %33, %34, %35, %36, %37, %38, %39, %40, %41, %42, %43, %44, %45, %46, %47, %48, %49, %50, %51, %52, %53, %54, %55, %56, %57, %58, %59, %60, %61, %62, %63, %64, %65, %66, %67, %68, %69, %70, %71, %72, %73, %74, %75, %76, %77, %78, %79, %80, %81, %82, %83, %84, %85, %86, %87, %88, %89, %90, %91, %92, %93, %94, %95}, %96, %97, p, 1, 1, 0, 1;\n}\n"
    : "+f"(d[0]), "+f"(d[1]), "+f"(d[2]), "+f"(d[3]), "+f"(d[4]), "+f"(d[5]), "+f"(d[6]), "+f"(d[7]),
      "+f"(d[8]), "+f"(d[9]), "+f"(d[10]), "+f"(d[11]), "+f"(d[12]), "+f"(d[13]), "+f"(d[14]), "+f"(d[15]),
      "+f"(d[16]), "+f"(d[17]), "+f"(d[18]), "+f"(d[19]), "+f"(d[20]), "+f"(d[21]), "+f"(d[22]), "+f"(d[23]),
      "+f"(d[24]), "+f"(d[25]), "+f"(d[26]), "+f"(d[27]), "+f"(d[28]), "+f"(d[29]), "+f"(d[30]), "+f"(d[31]),
      "+f"(d[32]), "+f"(d[33]), "+f"(d[34]), "+f"(d[35]), "+f"(d[36]), "+f"(d[37]), "+f"(d[38]), "+f"(d[39]),
      "+f"(d[40]), "+f"(d[41]), "+f"(d[42]), "+f"(d[43]), "+f"(d[44]), "+f"(d[45]), "+f"(d[46]), "+f"(d[47]),
      "+f"(d[48]), "+f"(d[49]), "+f"(d[50]), "+f"(d[51]), "+f"(d[52]), "+f"(d[53]), "+f"(d[54]), "+f"(d[55]),
      "+f"(d[56]), "+f"(d[57]), "+f"(d[58]), "+f"(d[59]), "+f"(d[60]), "+f"(d[61]), "+f"(d[62]), "+f"(d[63]),
      "+f"(d[64]), "+f"(d[65]), "+f"(d[66]), "+f"(d[67]), "+f"(d[68]), "+f"(d[69]), "+f"(d[70]), "+f"(d[71]),
      "+f"(d[72]), "+f"(d[73]), "+f"(d[74]), "+f"(d[75]), "+f"(d[76]), "+f"(d[77]), "+f"(d[78]), "+f"(d[79]),
      "+f"(d[80]), "+f"(d[81]), "+f"(d[82]), "+f"(d[83]), "+f"(d[84]), "+f"(d[85]), "+f"(d[86]), "+f"(d[87]),
      "+f"(d[88]), "+f"(d[89]), "+f"(d[90]), "+f"(d[91]), "+f"(d[92]), "+f"(d[93]), "+f"(d[94]), "+f"(d[95])
    : "l"(descA), "l"(descB), "r"(scaleD));
}

__device__ __forceinline__ void ldsm4t(uint32_t (&b)[4], uint32_t addr) {
  asm volatile("ldmatrix.sync.aligned.m8n8.x4.trans.shared.b16 {%0,%1,%2,%3}, [%4];"
               : "=r"(b[0]), "=r"(b[1]), "=r"(b[2]), "=r"(b[3])
               : "r"(addr));
}
__device__ __forceinline__ void hmma(float (&c)[4], uint32_t a0, uint32_t a1, uint32_t a2, uint32_t a3, uint32_t b0, uint32_t b1) {
  asm("mma.sync.aligned.m16n8k16.row.col.f32.bf16.bf16.f32 {%0,%1,%2,%3}, {%4,%5,%6,%7}, {%8,%9}, {%0,%1,%2,%3};"
      : "+f"(c[0]), "+f"(c[1]), "+f"(c[2]), "+f"(c[3])
      : "r"(a0), "r"(a1), "r"(a2), "r"(a3), "r"(b0), "r"(b1));
}

__device__ __forceinline__ uint32_t movm(uint32_t a) {
  uint32_t d;
  asm volatile("movmatrix.sync.aligned.m8n8.trans.b16 %0, %1;" : "=r"(d) : "r"(a));
  return d;
}

constexpr int K1_STAGES = 4;
constexpr int K1_W_BYTES = 3 * 8192;
constexpr int K1_X_BYTES = 8 * 16384;
constexpr int K1_BAR_OFF = K1_X_BYTES + K1_STAGES * K1_W_BYTES;
constexpr int K1_SMEM = K1_BAR_OFF + 192 + 1024;
constexpr float QSCALE = 0.25f * 1.4426950408889634f;

__device__ __forceinline__ uint32_t phi2(uint32_t t2) {
  uint32_t a2, mask, r2, o2;
  asm("add.rn.bf16x2 %0, %1, %2;" : "=r"(a2) : "r"(t2), "r"(0x3F803F80u));
  const uint32_t e2 = pack_bf16(ex2f(bf_lo(t2) * 1.4426950408889634f), ex2f(bf_hi(t2) * 1.4426950408889634f));
  asm("set.gt.u32.bf16x2 %0, %1, %2;" : "=r"(mask) : "r"(t2), "r"(0u));
  r2 = (a2 & mask) | (e2 & ~mask);
  asm("add.rn.bf16x2 %0, %1, %2;" : "=r"(o2) : "r"(r2), "r"(0x35863586u));
  return o2;
}

#define K1_SLOT_KB(h) ((h) < 4 ? 2 * (h) : 2 * ((h) - 4) + 1)
struct EpiCtx {
  uint4* qf;
  uint32_t* kp;
  uint32_t* vp;
  uint32_t* s_red;
  float* red;
  int lane;
};

template <bool LINEAR, int HH, int PART>
__device__ __forceinline__ void epi_slice(const float (&acc)[96], const EpiCtx& c, uint32_t (&pk)[4], float& vmax, bool live) {
  const float* a = &acc[HH * 8];
  const float* k = &acc[32 + HH * 8];
  const float* v = &acc[64 + HH * 8];
  if (!LINEAR) {
    if (PART == 0) {
      uint32_t* kh = c.kp + HH * (KV_HEAD_BYTES / 4);
      if (live) {
        c.qf[HH * 32 * 128] = make_uint4(pack_bf16(a[0] * QSCALE, a[1] * QSCALE), pack_bf16(a[2] * QSCALE, a[3] * QSCALE),
                                         pack_bf16(a[4] * QSCALE, a[5] * QSCALE), pack_bf16(a[6] * QSCALE, a[7] * QSCALE));
        kh[0] = pack_bf16(k[0], k[1]);
        kh[64] = pack_bf16(k[2], k[3]);
        kh[32] = pack_bf16(k[4], k[5]);
        kh[96] = pack_bf16(k[6], k[7]);
      }
      float q0 = a[0] * a[0] + a[1] * a[1] + a[4] * a[4] + a[5] * a[5];
      float q1 = a[2] * a[2] + a[3] * a[3] + a[6] * a[6] + a[7] * a[7];
      float k0 = k[0] * k[0] + k[1] * k[1] + k[4] * k[4] + k[5] * k[5];
      float k1 = k[2] * k[2] + k[3] * k[3] + k[6] * k[6] + k[7] * k[7];
#pragma unroll
      for (int o = 1; o <= 2; o <<= 1) {
        q0 += __shfl_xor_sync(0xffffffffu, q0, o);
        q1 += __shfl_xor_sync(0xffffffffu, q1, o);
        k0 += __shfl_xor_sync(0xffffffffu, k0, o);
        k1 += __shfl_xor_sync(0xffffffffu, k1, o);
      }
      const uint32_t qm = __reduce_max_sync(0xffffffffu, max(__float_as_uint(q0) & 0x7FFFFFFFu, __float_as_uint(q1) & 0x7FFFFFFFu));
      const uint32_t km = __reduce_max_sync(0xffffffffu, max(__float_as_uint(k0) & 0x7FFFFFFFu, __float_as_uint(k1) & 0x7FFFFFFFu));
      if (c.lane == 0 && live) {
        atomicMax(&c.s_red[HH * 2 + 0], qm);
        atomicMax(&c.s_red[HH * 2 + 1], km);
      }
    } else {
      uint32_t* vh = c.vp + HH * (KV_HEAD_BYTES / 4);
      if (live) {
        vh[0] = pack_bf16(v[0], v[1]);
        vh[96] = pack_bf16(v[2], v[3]);
        vh[32] = pack_bf16(v[4], v[5]);
        vh[128] = pack_bf16(v[6], v[7]);
        vh[64] = 0x3F803F80u;
        vh[160] = 0x3F803F80u;
      }
#pragma unroll
      for (int i = 0; i < 8; i++) asm("max.NaN.f32 %0, %0, %1;" : "+f"(vmax) : "f"(fabsf(v[i])));
    }
  } else {
    if (PART == 0) {
      const uint4 pq = make_uint4(phi2(pack_bf16(a[0], a[1])), phi2(pack_bf16(a[2], a[3])), phi2(pack_bf16(a[4], a[5])),
                                  phi2(pack_bf16(a[6], a[7])));
      if (live) c.qf[HH * 32 * 128] = pq;
      pk[0] = movm(phi2(pack_bf16(k[0], k[1])));
      pk[2] = movm(phi2(pack_bf16(k[2], k[3])));
      pk[1] = movm(phi2(pack_bf16(k[4], k[5])));
      pk[3] = movm(phi2(pack_bf16(k[6], k[7])));
    } else {
      const uint32_t b0 = movm(pack_bf16(v[0], v[1]));
      const uint32_t b1 = movm(pack_bf16(v[2], v[3]));
      const uint32_t b2 = movm(pack_bf16(v[4], v[5]));
      const uint32_t b3 = movm(pack_bf16(v[6], v[7]));
      float c0[4] = {0, 0, 0, 0}, c1[4] = {0, 0, 0, 0}, c2[4] = {0, 0, 0, 0};
      hmma(c0, pk[0], pk[1], pk[2], pk[3], b0, b1);
      hmma(c1, pk[0], pk[1], pk[2], pk[3], b2, b3);
      hmma(c2, pk[0], pk[1], pk[2], pk[3], 0x3F803F80u, 0x3F803F80u);
      float* slot = c.red + HH * 2 * 4096;
      if (live) {
#pragma unroll
        for (int i = 0; i < 4; i++) {
          slot[i * 32] = c0[i];
          slot[(4 + i) * 32] = c1[i];
          slot[(8 + i) * 32] = c2[i];
        }
      }
    }
  }
}

template <bool LINEAR>
__device__ __forceinline__ void qkv_consumer(uint32_t sbase, uint8_t* smem_gen, uint32_t* s_red, int cp, int rt) {
  const uint32_t bar_full = sbase + K1_BAR_OFF;
  const uint32_t bar_empty = bar_full + 8 * K1_STAGES;
  const int warp = threadIdx.x >> 5;
  const int wg = warp >> 2;
  const int lane = threadIdx.x & 31;
  float accN[96], accP[96];
  EpiCtx c;
  {
    const int row0 = rt * 128 + wg * 64 + (warp & 3) * 16;
    c.qf = g_qfrag + ((size_t)((LINEAR ? NH : 0) + cp * 8) * 32 + (rt * 2 + wg)) * 128 + (threadIdx.x & 127);
    uint32_t* img = reinterpret_cast<uint32_t*>(reinterpret_cast<uint8_t*>(g_kv) + (size_t)(cp * 8) * KV_HEAD_BYTES);
    c.kp = img + (row0 >> 3) * 64 + lane;
    c.vp = img + KV_K_BYTES / 4 + (row0 >> 3) * 96 + lane;
    c.s_red = s_red;
    c.red = reinterpret_cast<float*>(smem_gen + wg * 8192) + (warp & 3) * 384 + lane;
    c.lane = lane;
  }
  uint32_t pk[4] = {0, 0, 0, 0};
  float vmax = 0.f;
#pragma unroll
  for (int i = 0; i < 96; i++) asm volatile("mov.f32 %0, 0f00000000;" : "=f"(accN[i]));
  int npass;
  asm volatile("mov.u32 %0, 2;" : "=r"(npass));
#pragma unroll 1
  for (int pass = 0; pass < npass; pass++) {
    const bool live = pass != 0;
    if (live) {
#pragma unroll 1
      for (int kb = 0; kb < 8; kb++) {
        const int s = kb % K1_STAGES;
        mbar_wait(bar_full + 8 * s, (kb / K1_STAGES) & 1);
        if (threadIdx.x == 0) PROF_T(0, 2 + (kb >> 1));
        const uint64_t dA = mkdesc(sbase + kb * 16384 + wg * 8192, 16, 1024, 1);
        const uint64_t dB = mkdesc(sbase + K1_X_BYTES + s * K1_W_BYTES, 8192, 1024, 1);
        wg_fence();
#pragma unroll
        for (int k = 0; k < 4; k++) wgmma_ss_n192_tb(accP, dA + k * 2, dB + k * 128, (kb | k) != 0);
        wg_commit();
        if (kb > 0) {
          wg_wait<1>();
          if ((threadIdx.x & 127) == 0) {
            const int sp = (kb - 1) % K1_STAGES;
            mbar_arrive_cluster(bar_empty + 8 * sp, 0);
            mbar_arrive_cluster(bar_empty + 8 * sp, 1);
          }
        }
      }
      wg_wait<0>();
      fence_regs(accP);
      if ((threadIdx.x & 127) == 0) {
        mbar_arrive_cluster(bar_empty + 8 * (7 % K1_STAGES), 0);
        mbar_arrive_cluster(bar_empty + 8 * (7 % K1_STAGES), 1);
      }
      if (threadIdx.x == 0) PROF_T(0, 6);
#define K1_T1_STEP(KB)                                                                           \
  {                                                                                              \
    constexpr int g = 8 + KB;                                                                    \
    constexpr int s = g % K1_STAGES;                                                             \
    mbar_wait(bar_full + 8 * s, (g / K1_STAGES) & 1);                                            \
    const uint64_t dA = mkdesc(sbase + KB * 16384 + wg * 8192, 16, 1024, 1);                     \
    const uint64_t dB = mkdesc(sbase + K1_X_BYTES + s * K1_W_BYTES, 8192, 1024, 1);              \
    wg_fence();                                                                                  \
    _Pragma("unroll") for (int k = 0; k < 4; k++) wgmma_ss_n192_tb(accN, dA + k * 2, dB + k * 128, (KB | k) != 0); \
    wg_commit();                                                                                 \
    epi_slice<LINEAR, KB / 2, KB & 1>(accP, c, pk, vmax, true);                                  \
    wg_wait<0>();                                                                                \
    if (KB + K1_STAGES < 8 && (threadIdx.x & 127) == 0) {                                        \
      mbar_arrive_cluster(bar_empty + 8 * s, 0);                                                 \
      mbar_arrive_cluster(bar_empty + 8 * s, 1);                                                 \
    }                                                                                            \
  }
      K1_T1_STEP(0) K1_T1_STEP(1) K1_T1_STEP(2) K1_T1_STEP(3) K1_T1_STEP(4) K1_T1_STEP(5) K1_T1_STEP(6) K1_T1_STEP(7)
#undef K1_T1_STEP
      fence_regs(accN);
      if (threadIdx.x == 0) PROF_T(0, 10);
      c.qf += 4 * 32 * 128;
      c.kp += 4 * (KV_HEAD_BYTES / 4);
      c.vp += 4 * (KV_HEAD_BYTES / 4);
      c.s_red += 8;
      c.red += 4096;
    }
    float vm1 = 0.f;
    epi_slice<LINEAR, 0, 0>(accN, c, pk, vm1, live);
    epi_slice<LINEAR, 0, 1>(accN, c, pk, vm1, live);
    epi_slice<LINEAR, 1, 0>(accN, c, pk, vm1, live);
    epi_slice<LINEAR, 1, 1>(accN, c, pk, vm1, live);
    epi_slice<LINEAR, 2, 0>(accN, c, pk, vm1, live);
    epi_slice<LINEAR, 2, 1>(accN, c, pk, vm1, live);
    epi_slice<LINEAR, 3, 0>(accN, c, pk, vm1, live);
    epi_slice<LINEAR, 3, 1>(accN, c, pk, vm1, live);
    if (live) asm("max.NaN.f32 %0, %0, %1;" : "+f"(vmax) : "f"(vm1));
  }
  if (!LINEAR) {
    const uint32_t vm = __reduce_max_sync(0xffffffffu, __float_as_uint(vmax) & 0x7FFFFFFFu);
    if (lane == 0) atomicMax(&s_red[16], vm);
    asm volatile("bar.sync 1, 256;" ::: "memory");
    if (threadIdx.x < 8) {
      *reinterpret_cast<float4*>(&g_nrm[((cp * 8 + threadIdx.x) * 16 + rt) * 4]) =
          make_float4(__uint_as_float(s_red[threadIdx.x * 2]), __uint_as_float(s_red[threadIdx.x * 2 + 1]), __uint_as_float(s_red[16]), 0.f);
    }
  } else {
    asm volatile("bar.sync 1, 256;" ::: "memory");
    float* dst = g_kvpart + ((size_t)rt * NH + cp * 8) * 384;
#pragma unroll
    for (int i = 0; i < 12; i++) {
      const int o = threadIdx.x + i * 256;
      const int h = o / 384, e = o - h * 384;
      const float* src = reinterpret_cast<const float*>(smem_gen) + K1_SLOT_KB(h) * 4096 + e;
      float sum = 0.f;
#pragma unroll
      for (int w = 0; w < 8; w++) sum += src[(w >> 2) * 2048 + (w & 3) * 384];
      dst[o] = sum;
    }
  }
}

__global__ void __launch_bounds__(384, 1)
qkv_gemm_kernel(const __grid_constant__ CUtensorMap mxA, const __grid_constant__ CUtensorMap mxB,
                const __grid_constant__ CUtensorMap mwA, const __grid_constant__ CUtensorMap mwB) {
  extern __shared__ uint8_t smem_raw[];
  const uint32_t sbase = (smem_u32(smem_raw) + 1023) & ~1023u;
  uint8_t* smem_gen = smem_raw + (sbase - smem_u32(smem_raw));
  const uint32_t bar_full = sbase + K1_BAR_OFF;
  const uint32_t bar_empty = bar_full + 8 * K1_STAGES;
  uint32_t* s_red = reinterpret_cast<uint32_t*>(smem_gen + K1_BAR_OFF + 64);

  const int rank = blockIdx.x & 1;
  const int pair = blockIdx.x >> 1;
  const int branch = pair >> 5;
  const int rp = (pair & 31) >> 2;
  const int cp = pair & 3;
  const int rt = rp * 2 + rank;
  const int warp = threadIdx.x >> 5;
  if (threadIdx.x == 0) { PROF_G(0, 30); PROF_T(0, 0); }
  const CUtensorMap* mx = branch ? &mxA : &mxB;
  const CUtensorMap* mw = branch ? &mwA : &mwB;

  if (threadIdx.x == 256) {
    asm volatile("prefetch.tensormap [%0];" ::"l"(mx) : "memory");
    asm volatile("prefetch.tensormap [%0];" ::"l"(mw) : "memory");
    for (int i = 0; i < K1_STAGES; i++) {
      mbar_init(bar_full + 8 * i, 1);
      mbar_init(bar_empty + 8 * i, 4);
    }
    fence_barrier_init();
    fence_proxy_async();
    for (int kb = 0; kb < K1_STAGES; kb++) mbar_expect_tx(bar_full + 8 * kb, 16384 + K1_W_BYTES);
    tma_load_2d(sbase, mx, 0, rt * 128, bar_full);
  }
  pdl_launch_dependents();
  if (threadIdx.x < 32) s_red[threadIdx.x] = 0;
  __syncthreads();
  cluster_sync_relaxed();
  if (threadIdx.x == 0) PROF_T(0, 1);

  if (warp >= 8) {
    asm volatile("setmaxnreg.dec.sync.aligned.u32 40;");
    if (threadIdx.x == 256) {
      for (int g = 0; g < 16; g++) {
        const int s = g % K1_STAGES;
        const int kb = g & 7;
        if (g >= K1_STAGES) {
          mbar_wait(bar_empty + 8 * s, ((g / K1_STAGES) - 1) & 1);
          mbar_expect_tx(bar_full + 8 * s, (g < 8 ? 16384 : 0) + K1_W_BYTES);
        }
        if (g > 0 && g < 8) tma_load_2d(sbase + kb * 16384, mx, kb * 64, rt * 128, bar_full + 8 * s);
        const int h0 = cp * 8 + (g >> 3) * 4;
        const uint32_t st = sbase + K1_X_BYTES + s * K1_W_BYTES + rank * 4096;
#pragma unroll
        for (int p = 0; p < 3; p++)
          tma_load_2d_mc(st + p * 8192, mw, p * 512 + h0 * 16, kb * 64 + rank * 32, bar_full + 8 * s, (uint16_t)3);
      }
    }
    __syncwarp();
    cluster_sync_relaxed();
  } else {
    asm volatile("setmaxnreg.inc.sync.aligned.u32 232;");
    if (branch == 0) qkv_consumer<false>(sbase, smem_gen, s_red, cp, rt);
    else qkv_consumer<true>(sbase, smem_gen, s_red, cp, rt);
    if (threadIdx.x == 0) PROF_T(0, 11);
    __syncwarp();
    cluster_sync_relaxed();
    if (threadIdx.x == 0) { PROF_T(0, 12); PROF_G(0, 31); }
  }
}

constexpr int K2_SMEM = KV_HEAD_BYTES + 1024 + 256;

#define ATT_NPOLY 18
#define ATT_CH 8
#define ATT_D 1
#define PRO_MODE 1
#define STAGGER 0
#define CONST_SMID 0
#define ATT_STRUCT 1
#define ATT_PIN 0
#define ATT_GM 1
#define ATT_DEG 2
struct ExpC {
  uint32_t k3c00, kmask, seven, c3;
};
__device__ __forceinline__ uint32_t hfma2(uint32_t a, uint32_t b, uint32_t c) {
  uint32_t r;
  asm("fma.rn.f16x2 %0, %1, %2, %3;" : "=r"(r) : "r"(a), "r"(b), "r"(c));
  return r;
}
__device__ __forceinline__ uint32_t exp2_poly_pair(float t0, float t1, const ExpC& c) {
  uint32_t u;
  asm("prmt.b32 %0, %1, %2, 0x5410;" : "=r"(u) : "r"(__float_as_uint(t0)), "r"(__float_as_uint(t1)));
  uint32_t m;
  asm("lop3.b32 %0, %1, 0x03FF03FF, %2, 0xEA;" : "=r"(m) : "r"(u), "r"(c.k3c00));
  uint32_t p = hfma2(m, c.c3, 0xa385a385u);
  p = hfma2(p, m, 0x4ad64ad7u);
  uint32_t mu;
  asm("lop3.b32 %0, %1, 0xFC00FC00, %2, 0xEA;" : "=r"(mu) : "r"(u), "r"(c.kmask));
  uint32_t r;
  asm("{.reg .b32 t; shf.r.wrap.b32 t, %1, %2, 3; add.u32 %0, t, %3;}" : "=r"(r) : "r"(mu), "r"(c.seven), "r"(p));
  return r;
}
__device__ __forceinline__ float gadd(float x, float M, uint32_t g) {
  float r = x;
  asm("{.reg .pred p; setp.ne.b32 p, %2, -1; @p add.f32 %0, %0, %1;}" : "+f"(r) : "f"(M), "r"(g));
  return r;
}
__device__ __forceinline__ float gex2(float x, uint32_t g) {
  float r = x;
  asm("{.reg .pred p; setp.ne.b32 p, %1, -1; @p ex2.approx.ftz.f32 %0, %0;}" : "+f"(r) : "r"(g));
  return r;
}
template <int NPOLY, int NPAIR, int CH, int D, bool G0 = false>
__device__ __forceinline__ void exp_tile(const float (&s)[2 * NPAIR], uint32_t (&p)[NPAIR], const ExpC& c, uint32_t g0 = 0) {
#pragma unroll
  for (int i = 0; i < NPAIR; i++) {
    const bool isPoly = ((i + 1) * NPOLY / 32) != (i * NPOLY / 32);
    const int ch = i / CH;
    const bool gated = ch >= D || G0;
    int gi = (ch - D) * CH + CH - 1;
    if (ch >= D) {
      while (gi > (ch - D) * CH && !(((gi + 1) * NPOLY / 32) != (gi * NPOLY / 32))) gi--;
    }
    const uint32_t g = ch >= D ? p[gi] : g0;
    if (!isPoly) {
      if (gated && ATT_GM) p[i] = pack_bf16(gex2(s[2 * i], g), gex2(s[2 * i + 1], g));
      else p[i] = pack_bf16(ex2f(s[2 * i]), ex2f(s[2 * i + 1]));
    } else {
      if (gated) p[i] = exp2_poly_pair(gadd(s[2 * i], 12329.f, g), gadd(s[2 * i + 1], 12329.f, g), c);
      else p[i] = exp2_poly_pair(s[2 * i] + 12329.f, s[2 * i + 1] + 12329.f, c);
    }
  }
}

__device__ __forceinline__ void store_o(__nv_bfloat16* o, int row0, int head, int lane, const uint32_t (&r)[4]) {
  const int g = lane >> 2, t = lane & 3;
  uint32_t* p0 = reinterpret_cast<uint32_t*>(o + (size_t)(row0 + g) * DM + head * 16) + t;
  uint32_t* p1 = reinterpret_cast<uint32_t*>(o + (size_t)(row0 + g + 8) * DM + head * 16) + t;
  p0[0] = r[0];
  p1[0] = r[1];
  p0[4] = r[2];
  p1[4] = r[3];
}

__device__ __forceinline__ void kv_fetch_piece(uint32_t sbase, uint32_t bar, int piece) {
  const uint8_t* img = reinterpret_cast<const uint8_t*>(g_kv) + (size_t)(blockIdx.x >> 2) * KV_HEAD_BYTES;
  const int g = piece >> 1, isv = piece & 1;
  const int e0 = g == 0 ? 0 : (isv ? 256 : 320) + (g - 1) * 512;
  const int e1 = g == 3 ? 2048 : (isv ? 256 : 320) + g * 512;
  const int bytes = (e1 - e0) * (isv ? 48 : 32);
  const int off = isv ? KV_K_BYTES + e0 * 48 : e0 * 32;
  mbar_expect_tx(bar + 8 * g, bytes);
  bulk_load(sbase + off, img + off, bytes, bar + 8 * g);
}

__device__ __forceinline__ void safe_exp(const float (&s)[32], uint32_t (&p)[16], float (&o)[12], float& m0, float& m1) {
  float x0 = s[0], x1 = s[2];
#pragma unroll
  for (int i = 0; i < 8; i++) {
    x0 = fmaxf(x0, fmaxf(s[4 * i], s[4 * i + 1]));
    x1 = fmaxf(x1, fmaxf(s[4 * i + 2], s[4 * i + 3]));
  }
  x0 = fmaxf(x0, __shfl_xor_sync(0xffffffffu, x0, 1));
  x1 = fmaxf(x1, __shfl_xor_sync(0xffffffffu, x1, 1));
  x0 = fmaxf(x0, __shfl_xor_sync(0xffffffffu, x0, 2));
  x1 = fmaxf(x1, __shfl_xor_sync(0xffffffffu, x1, 2));
  const float n0 = fmaxf(m0, x0), n1 = fmaxf(m1, x1);
  const float c0 = ex2f(m0 - n0), c1 = ex2f(m1 - n1);
  m0 = n0;
  m1 = n1;
#pragma unroll
  for (int i = 0; i < 3; i++) {
    o[4 * i] *= c0;
    o[4 * i + 1] *= c0;
    o[4 * i + 2] *= c1;
    o[4 * i + 3] *= c1;
  }
#pragma unroll
  for (int i = 0; i < 8; i++) {
    p[2 * i] = pack_bf16(ex2f(s[4 * i] - n0), ex2f(s[4 * i + 1] - n0));
    p[2 * i + 1] = pack_bf16(ex2f(s[4 * i + 2] - n1), ex2f(s[4 * i + 3] - n1));
  }
}

__device__ __forceinline__ void attn_step(float (&sx)[32], float (&sy)[32], float (&o)[12], const uint4& qf, uint64_t dK, uint64_t dV,
                                          const ExpC& ec) {
  uint32_t pa[16], pb[16];
  wg_fence();
  wgmma_rs_n64_z(sy, qf.x, qf.y, qf.z, qf.w, dK + 128);
  wg_commit();
  exp_tile<ATT_NPOLY, 16, ATT_CH, ATT_D>(sx, pa, ec);
  wg_fence();
  wgmma_rs_n24_tb(o, pa[12], pa[13], pa[14], pa[15], dV + 3 * 48, 1);
  wg_commit();
  wg_wait<1>();
  fence_regs(sy);
  exp_tile<ATT_NPOLY, 16, ATT_CH, ATT_D>(sy, pb, ec);
  wg_fence();
#pragma unroll
  for (int k = 0; k < 3; k++) wgmma_rs_n24_tb(o, pa[4 * k], pa[4 * k + 1], pa[4 * k + 2], pa[4 * k + 3], dV + k * 48, 1);
#pragma unroll
  for (int k = 0; k < 4; k++) wgmma_rs_n24_tb(o, pb[4 * k], pb[4 * k + 1], pb[4 * k + 2], pb[4 * k + 3], dV + (4 + k) * 48, 1);
  wgmma_rs_n64_z(sy, qf.x, qf.y, qf.z, qf.w, dK + 256);
  wg_commit();
  wg_wait<0>();
  fence_regs(sy);
}

template <bool SAFE>
__device__ __forceinline__ void attn_tile(uint64_t dK, uint64_t dV, uint32_t bar, const uint4 qf, const ExpC& ec, uint32_t (&outp)[4]) {
  float o[12];
#pragma unroll
  for (int i = 0; i < 12; i++) asm volatile("mov.f32 %0, 0f00000000;" : "=f"(o[i]));
  mbar_wait(bar, 0);
  if (!SAFE) {
    float s0[32], s1[32];
    wg_fence();
    wgmma_rs_n64_z(s0, qf.x, qf.y, qf.z, qf.w, dK);
    wg_commit();
    wg_wait<0>();
    fence_regs(s0);
#pragma unroll 1
    for (int p = 0; p < 8; p++) {
      if (p & 1) mbar_wait(bar + 8 * min((p + 1) >> 1, 3), 0);
      attn_step(s0, s1, o, qf, dK, dV, ec);
      attn_step(s1, s0, o, qf, dK + 256, dV + 384, ec);
      dK += 512;
      dV += 768;
    }
  } else {
    float m0 = -INFINITY, m1 = -INFINITY;
#pragma unroll 1
    for (int j = 0; j < 32; j++) {
      if (j == 4) { mbar_wait(bar + 8, 0); mbar_wait(bar + 16, 0); mbar_wait(bar + 24, 0); }
      float s[32];
      uint32_t p[16];
      wg_fence();
      wgmma_rs_n64_z(s, qf.x, qf.y, qf.z, qf.w, dK);
      wg_commit();
      wg_wait<0>();
      fence_regs(s);
      safe_exp(s, p, o, m0, m1);
      wg_fence();
#pragma unroll
      for (int k = 0; k < 4; k++) wgmma_rs_n24_tb(o, p[4 * k], p[4 * k + 1], p[4 * k + 2], p[4 * k + 3], dV + k * 48, 1);
      wg_commit();
      wg_wait<0>();
      fence_regs(o);
      dK += 128;
      dV += 192;
    }
  }
  fence_regs(o);
  const float r0 = 1.0f / o[8], r1 = 1.0f / o[10];
  outp[0] = pack_bf16(o[0] * r0, o[1] * r0);
  outp[1] = pack_bf16(o[2] * r1, o[3] * r1);
  outp[2] = pack_bf16(o[4] * r0, o[5] * r0);
  outp[3] = pack_bf16(o[6] * r1, o[7] * r1);
}

__device__ __forceinline__ void linear_attn_cta(uint8_t* smem_raw, uint32_t sbase, const CUtensorMap* mo16, int cta) {
  const int warp = threadIdx.x >> 5, lane = threadIdx.x & 31;
  float* red = reinterpret_cast<float*>(smem_raw + (sbase - smem_u32(smem_raw)) + 131072);
  {
    const float* src = g_kvpart + (size_t)cta * 8 * 384;
    float sum[6];
#pragma unroll
    for (int i = 0; i < 6; i++) sum[i] = 0.f;
#pragma unroll
    for (int r = 0; r < 16; r++) {
#pragma unroll
      for (int i = 0; i < 6; i++) sum[i] += src[(size_t)r * NH * 384 + threadIdx.x + i * 512];
    }
#pragma unroll
    for (int i = 0; i < 6; i++) red[threadIdx.x + i * 512] = round_bf16(sum[i]);
  }
  __syncthreads();
  uint32_t bf[8][6];
  {
    const int g = lane >> 2, t = lane & 3;
#pragma unroll
    for (int h = 0; h < 8; h++) {
#pragma unroll
      for (int f = 0; f < 6; f++) {
        const int blk = f >> 1, half = f & 1;
        const int e = (blk == 2) ? 0 : g;
        const int d = 2 * t + 8 * half;
        const int base = h * 384 + (blk * 4 + half * 2 + (e & 1)) * 32 + (e >> 1);
        bf[h][f] = pack_bf16(red[base + (d & 7) * 4], red[base + ((d + 1) & 7) * 4]);
      }
    }
  }
  const uint32_t stg = sbase + warp * 8192;
#pragma unroll 1
  for (int rb = 0; rb < 8; rb++) {
    const int blk16 = rb * 16 + warp;
    const uint4* qp = g_qfrag + ((size_t)(NH + cta * 8) * 32 + (blk16 >> 2)) * 128 + (blk16 & 3) * 32 + lane;
    uint4 q[8];
#pragma unroll
    for (int h = 0; h < 8; h++) q[h] = qp[h * 32 * 128];
    const uint32_t buf = stg + (rb & 1) * 4096;
    if (rb >= 2) {
      if (lane == 0) asm volatile("cp.async.bulk.wait_group.read 1;" ::: "memory");
      __syncwarp();
    }
#pragma unroll
    for (int h = 0; h < 8; h++) {
      float n0[4] = {0, 0, 0, 0}, n1[4] = {0, 0, 0, 0}, dn[4] = {0, 0, 0, 0};
      hmma(n0, q[h].x, q[h].y, q[h].z, q[h].w, bf[h][0], bf[h][1]);
      hmma(n1, q[h].x, q[h].y, q[h].z, q[h].w, bf[h][2], bf[h][3]);
      hmma(dn, q[h].x, q[h].y, q[h].z, q[h].w, bf[h][4], bf[h][5]);
      const float d0 = round_bf16(round_bf16(dn[0]) + 1e-6f), d1 = round_bf16(round_bf16(dn[2]) + 1e-6f);
      const uint32_t r0 = pack_bf16(__fdividef(round_bf16(n0[0]), d0), __fdividef(round_bf16(n0[1]), d0));
      const uint32_t r1 = pack_bf16(__fdividef(round_bf16(n0[2]), d1), __fdividef(round_bf16(n0[3]), d1));
      const uint32_t r2 = pack_bf16(__fdividef(round_bf16(n1[0]), d0), __fdividef(round_bf16(n1[1]), d0));
      const uint32_t r3 = pack_bf16(__fdividef(round_bf16(n1[2]), d1), __fdividef(round_bf16(n1[3]), d1));
      const int row = lane & 15;
      const int chunk = (h & 3) * 2 + (lane >> 4);
      const uint32_t addr = buf + (h >> 2) * 2048 + row * 128 + ((chunk ^ (row & 7)) << 4);
      asm volatile("stmatrix.sync.aligned.m8n8.x4.shared.b16 [%0], {%1,%2,%3,%4};" ::"r"(addr), "r"(r0), "r"(r1), "r"(r2), "r"(r3)
                   : "memory");
    }
    fence_proxy_async();
    __syncwarp();
    if (lane == 0) {
      tma_store_2d(mo16, buf, cta * 128, blk16 * 16);
      tma_store_2d(mo16, buf + 2048, cta * 128 + 64, blk16 * 16);
      asm volatile("cp.async.bulk.commit_group;" ::: "memory");
    }
  }
  if (lane == 0) asm volatile("cp.async.bulk.wait_group 0;" ::: "memory");
}

__global__ void __launch_bounds__(512, 1)
attn_kernel(const __grid_constant__ CUtensorMap mo16, const uint8_t* __restrict__ woA, const uint8_t* __restrict__ woB) {
  extern __shared__ uint8_t smem_raw[];
  const uint32_t sbase = (smem_u32(smem_raw) + 1023) & ~1023u;
  const uint32_t bar = sbase + KV_HEAD_BYTES;
  if (threadIdx.x == 0) { PROF_G(1, 30); PROF_T(1, 0); }
  if (threadIdx.x == 0) {
    for (int i = 0; i < 4; i++) mbar_init(bar + 8 * i, 2);
    asm volatile("st.shared.v4.u32 [%0], {%1, %2, %3, %4};" ::"r"(bar + 64), "r"(0x3C003C00u), "r"(0x00070000u), "r"(7u),
                 "r"(ATT_DEG == 3 ? 0x2cfd2cfdu : 0x35623562u)
                 : "memory");
    fence_barrier_init();
    fence_proxy_async();
  }
  __syncthreads();
  pdl_launch_dependents();
  if (blockIdx.x >= 128 && threadIdx.x < 16) {
    const int i = (blockIdx.x - 128) * 16 + threadIdx.x;
    const uint8_t* p = (i < 32 ? woA : woB) + (size_t)(i & 31) * 16384;
    asm volatile("cp.async.bulk.prefetch.L2.global [%0], %1;" ::"l"(p), "r"(16384) : "memory");
  }
  pdl_wait();
  if (threadIdx.x == 0) { PROF_T(1, 7); PROF_G(1, 29); }
  if (blockIdx.x >= 128) {
    linear_attn_cta(smem_raw, sbase, &mo16, blockIdx.x - 128);
    if (threadIdx.x == 0) { PROF_T(1, 5); PROF_G(1, 31); }
    return;
  }
  const int head = blockIdx.x >> 2, qb = blockIdx.x & 3;
  const int lane = threadIdx.x & 31;
  const int wg = threadIdx.x >> 7, warp = (threadIdx.x >> 5) & 3;
  if (threadIdx.x == 0) {
#pragma unroll
    for (int piece = 0; piece < 8; piece++) kv_fetch_piece(sbase, bar, piece);
  }
  uint4 qnext = g_qfrag[(head * 32 + qb * 8 + wg * 2) * 128 + (threadIdx.x & 127)];
  float4 n = make_float4(0.f, 0.f, 0.f, 0.f);
  if (lane < 16) n = *reinterpret_cast<const float4*>(&g_nrm[(head * 16 + lane) * 4]);
  bool safe_path;
  {
    uint32_t qm = ((lane >> 2) == qb) ? __float_as_uint(n.x) : 0u;
    qm = __reduce_max_sync(0xffffffffu, qm);
    const uint32_t km = __reduce_max_sync(0xffffffffu, __float_as_uint(n.y));
    const uint32_t vm = __reduce_max_sync(0xffffffffu, __float_as_uint(n.z));
    const float b2 = __uint_as_float(qm) * (QSCALE * QSCALE) * __uint_as_float(km) * 1.02f;
    const float vmax = __uint_as_float(vm);
    const bool ok = (b2 <= 21.5f * 21.5f) && (vmax <= 1.0e24f) && (vmax >= 1.0e-18f || vmax == 0.f);
    safe_path = !ok;
  }
  ExpC ec;
  asm volatile("ld.volatile.shared.v4.u32 {%0, %1, %2, %3}, [%4];" : "=r"(ec.k3c00), "=r"(ec.kmask), "=r"(ec.seven), "=r"(ec.c3) : "r"(bar + 64));
  const uint64_t dK = mkdesc(sbase, 128, 256, 0);
  const uint64_t dV = mkdesc(sbase + KV_K_BYTES, 384, 128, 0);
#pragma unroll 1
  for (int t = 0; t < 2; t++) {
    const int tile64 = qb * 8 + wg * 2 + t;
    const uint4 qf = qnext;
    if (t == 0) qnext = g_qfrag[(head * 32 + tile64 + 1) * 128 + (threadIdx.x & 127)];
    uint32_t r[4];
    if (threadIdx.x == 0) PROF_T(1, 1 + t);
    if (!safe_path) attn_tile<false>(dK, dV, bar, qf, ec, r);
    else attn_tile<true>(dK, dV, bar, qf, ec, r);
    store_o(g_o + (size_t)S_LEN * DM, tile64 * 64 + warp * 16, head, lane, r);
  }
  if (threadIdx.x == 0) { PROF_T(1, 5); PROF_G(1, 31); }
}

#define K3_WPRE 2
constexpr int K3_STAGES = 5;
constexpr int K3_W_BYTES = 8 * 16384;
constexpr int K3_BAR_OFF = K3_W_BYTES + K3_STAGES * 16384;
constexpr int K3_SMEM = K3_BAR_OFF + 256 + 1024;

__global__ void __launch_bounds__(288, 1)
out_gemm_kernel(const __grid_constant__ CUtensorMap mo, const __grid_constant__ CUtensorMap mwA,
                const __grid_constant__ CUtensorMap mwB, const __grid_constant__ CUtensorMap mout) {
  extern __shared__ uint8_t smem_raw[];
  const uint32_t sbase = (smem_u32(smem_raw) + 1023) & ~1023u;
  const uint32_t bar_full = sbase + K3_BAR_OFF;
  const uint32_t bar_empty = bar_full + 8 * K3_STAGES;
  const uint32_t bar_w = bar_empty + 8 * K3_STAGES;
  const int branch = blockIdx.x >> 6;
  const int rt = (blockIdx.x & 63) >> 2;
  const int ct = blockIdx.x & 3;
  const int warp = threadIdx.x >> 5;
  if (threadIdx.x == 0) { PROF_G(2, 30); PROF_T(2, 0); }
  if (threadIdx.x == 256) {
    const CUtensorMap* mw = branch ? &mwB : &mwA;
    asm volatile("prefetch.tensormap [%0];" ::"l"(mw) : "memory");
    asm volatile("prefetch.tensormap [%0];" ::"l"(&mo) : "memory");
    asm volatile("prefetch.tensormap [%0];" ::"l"(&mout) : "memory");
    for (int i = 0; i < K3_STAGES; i++) {
      mbar_init(bar_full + 8 * i, 1);
      mbar_init(bar_empty + 8 * i, 2);
    }
    for (int i = 0; i < 8; i++) mbar_init(bar_w + 8 * i, 1);
    fence_barrier_init();
    fence_proxy_async();
    for (int kb = 0; kb < K3_WPRE; kb++) {
      mbar_expect_tx(bar_w + 8 * kb, 16384);
      tma_load_2d(sbase + kb * 16384, mw, ct * 128, kb * 64, bar_w + 8 * kb);
      tma_load_2d(sbase + kb * 16384 + 8192, mw, ct * 128 + 64, kb * 64, bar_w + 8 * kb);
    }
  }
  __syncthreads();
  if (warp == 8) {
    if ((threadIdx.x & 31) == 0) {
      const CUtensorMap* mw = branch ? &mwB : &mwA;
      pdl_wait();
      PROF_T(2, 1);
      for (int kb = 0; kb < 8; kb++) {
        const int s = kb % K3_STAGES;
        if (kb >= K3_STAGES) mbar_wait(bar_empty + 8 * s, ((kb / K3_STAGES) - 1) & 1);
        mbar_expect_tx(bar_full + 8 * s, 16384);
        tma_load_2d(sbase + K3_W_BYTES + s * 16384, &mo, kb * 64, branch * S_LEN + rt * 128, bar_full + 8 * s);
        const int kw = kb + K3_WPRE;
        if (kw < 8) {
          mbar_expect_tx(bar_w + 8 * kw, 16384);
          tma_load_2d(sbase + kw * 16384, mw, ct * 128, kw * 64, bar_w + 8 * kw);
          tma_load_2d(sbase + kw * 16384 + 8192, mw, ct * 128 + 64, kw * 64, bar_w + 8 * kw);
        }
      }
    }
  } else {
    const int wg = warp >> 2;
    float acc[64];
    for (int kb = 0; kb < 8; kb++) {
      const int s = kb % K3_STAGES;
      mbar_wait(bar_w + 8 * kb, 0);
      mbar_wait(bar_full + 8 * s, (kb / K3_STAGES) & 1);
      if (threadIdx.x == 0) PROF_T(2, 2 + kb);
      const uint64_t dA = mkdesc(sbase + K3_W_BYTES + s * 16384 + wg * 8192, 16, 1024, 1);
      const uint64_t dB = mkdesc(sbase + kb * 16384, 8192, 1024, 1);
      wg_fence();
#pragma unroll
      for (int k = 0; k < 4; k++) wgmma_ss_n128_tb(acc, dA + k * 2, dB + k * 128, (kb | k) != 0);
      wg_commit();
      if (kb > 0) {
        wg_wait<1>();
        if ((threadIdx.x & 127) == 0) mbar_arrive(bar_empty + 8 * ((kb - 1) % K3_STAGES));
      }
    }
    wg_wait<0>();
    fence_regs(acc);
    if (threadIdx.x == 0) PROF_T(2, 10);
    const uint32_t stg = sbase + K3_W_BYTES + wg * 8192;
    const int lane = threadIdx.x & 31;
    const int rloc = (warp & 3) * 16 + (lane & 15);
#pragma unroll
    for (int c16 = 0; c16 < 8; c16++) {
      const float* a = &acc[c16 * 8];
      const uint32_t r0 = pack_bf16(a[0], a[1]), r1 = pack_bf16(a[2], a[3]), r2 = pack_bf16(a[4], a[5]), r3 = pack_bf16(a[6], a[7]);
      const int chunk = (c16 & 3) * 2 + (lane >> 4);
      const uint32_t addr = stg + (c16 >> 2) * 16384 + rloc * 128 + ((chunk ^ (rloc & 7)) << 4);
      asm volatile("stmatrix.sync.aligned.m8n8.x4.shared.b16 [%0], {%1,%2,%3,%4};" ::"r"(addr), "r"(r0), "r"(r1), "r"(r2), "r"(r3)
                   : "memory");
    }
    fence_proxy_async();
    asm volatile("bar.sync %0, 128;" ::"r"(2 + wg) : "memory");
    if ((threadIdx.x & 127) == 0) {
      tma_store_2d(&mout, stg, branch * DM + ct * 128, rt * 128 + wg * 64);
      tma_store_2d(&mout, stg + 16384, branch * DM + ct * 128 + 64, rt * 128 + wg * 64);
      asm volatile("cp.async.bulk.commit_group;" ::: "memory");
      asm volatile("cp.async.bulk.wait_group.read 0;" ::: "memory");
      if (threadIdx.x == 0) { PROF_T(2, 12); PROF_G(2, 31); }
    }
  }
}

typedef CUresult (*EncodeFn)(CUtensorMap*, CUtensorMapDataType, cuuint32_t, void*, const cuuint64_t*, const cuuint64_t*,
                             const cuuint32_t*, const cuuint32_t*, CUtensorMapInterleave, CUtensorMapSwizzle,
                             CUtensorMapL2promotion, CUtensorMapFloatOOBfill);

void make_map(EncodeFn enc, CUtensorMap* m, const void* ptr, uint64_t inner, uint64_t outer, uint32_t box_inner, uint32_t box_outer) {
  cuuint64_t dims[2] = {inner, outer};
  cuuint64_t strides[1] = {inner * 2};
  cuuint32_t box[2] = {box_inner, box_outer};
  cuuint32_t es[2] = {1, 1};
  enc(m, CU_TENSOR_MAP_DATA_TYPE_BFLOAT16, 2, const_cast<void*>(ptr), dims, strides, box, es, CU_TENSOR_MAP_INTERLEAVE_NONE,
      CU_TENSOR_MAP_SWIZZLE_128B, CU_TENSOR_MAP_L2_PROMOTION_L2_256B, CU_TENSOR_MAP_FLOAT_OOB_FILL_NONE);
}

struct HostState {
  bool init;
  const void* key[7];
  CUtensorMap mxA, mxB, mwA, mwB, mo, mo16, mwoA, mwoB, mout;
};
HostState g_hs;

}

extern "C" void kernel_launch(void* const* d_in, const int* in_sizes, int n_in, void* d_out, int out_size) {
  (void)in_sizes; (void)n_in; (void)out_size;
  HostState& hs = g_hs;
  bool same = hs.init && hs.key[6] == d_out;
  for (int i = 0; i < 6 && same; i++) same = hs.key[i] == d_in[i];
  if (!same) {
    void* fn = nullptr;
    cudaDriverEntryPointQueryResult qr;
    cudaGetDriverEntryPoint("cuTensorMapEncodeTiled", &fn, cudaEnableDefault, &qr);
    EncodeFn enc = (EncodeFn)fn;
    void* go = nullptr;
    cudaGetSymbolAddress(&go, g_o);
    make_map(enc, &hs.mxA, d_in[0], 512, 2048, 64, 128);
    make_map(enc, &hs.mwA, d_in[1], 1536, 512, 64, 32);
    make_map(enc, &hs.mwoA, d_in[2], 512, 512, 64, 64);
    make_map(enc, &hs.mxB, d_in[3], 512, 2048, 64, 128);
    make_map(enc, &hs.mwB, d_in[4], 1536, 512, 64, 32);
    make_map(enc, &hs.mwoB, d_in[5], 512, 512, 64, 64);
    make_map(enc, &hs.mo, go, 512, 4096, 64, 128);
    make_map(enc, &hs.mo16, go, 512, 4096, 64, 16);
    make_map(enc, &hs.mout, d_out, 1024, 2048, 64, 64);
    cudaFuncSetAttribute(qkv_gemm_kernel, cudaFuncAttributeMaxDynamicSharedMemorySize, K1_SMEM);
    cudaFuncSetAttribute(attn_kernel, cudaFuncAttributeMaxDynamicSharedMemorySize, K2_SMEM);
    cudaFuncSetAttribute(out_gemm_kernel, cudaFuncAttributeMaxDynamicSharedMemorySize, K3_SMEM);
    for (int i = 0; i < 6; i++) hs.key[i] = d_in[i];
    hs.key[6] = d_out;
    hs.init = true;
  }
  cudaStream_t st = cudaStreamPerThread;
  {
    cudaLaunchConfig_t cfg = {};
    cfg.gridDim = dim3(128);
    cfg.blockDim = dim3(384);
    cfg.dynamicSmemBytes = K1_SMEM;
    cfg.stream = st;
    cudaLaunchAttribute at[1];
    at[0].id = cudaLaunchAttributeClusterDimension;
    at[0].val.clusterDim.x = 2;
    at[0].val.clusterDim.y = 1;
    at[0].val.clusterDim.z = 1;
    cfg.attrs = at;
    cfg.numAttrs = 1;
    cudaLaunchKernelEx(&cfg, qkv_gemm_kernel, hs.mxA, hs.mxB, hs.mwA, hs.mwB);
  }
  {
    cudaLaunchConfig_t cfg = {};
    cfg.gridDim = dim3(132);
    cfg.blockDim = dim3(512);
    cfg.dynamicSmemBytes = K2_SMEM;
    cfg.stream = st;
    cudaLaunchAttribute at[1];
    at[0].id = cudaLaunchAttributeProgrammaticStreamSerialization;
    at[0].val.programmaticStreamSerializationAllowed = 1;
    cfg.attrs = at;
    cfg.numAttrs = 1;
    cudaLaunchKernelEx(&cfg, attn_kernel, hs.mo16, (const uint8_t*)d_in[2], (const uint8_t*)d_in[5]);
    cfg.gridDim = dim3(128);
    cfg.blockDim = dim3(288);
    cfg.dynamicSmemBytes = K3_SMEM;
    cudaLaunchKernelEx(&cfg, out_gemm_kernel, hs.mo, hs.mwoA, hs.mwoB, hs.mout);
  }
}
```

```cpp
#include <cuda_runtime.h>
#include <cuda_bf16.h>
#include <cuda.h>
#include <stdint.h>

namespace {

constexpr int S_LEN = 2048;
constexpr int DM = 512;
constexpr int NH = 32;

constexpr int KV_K_BYTES = 65536;
constexpr int KV_HEAD_BYTES = KV_K_BYTES + 98304;
__device__ uint4 g_qfrag[2 * NH * 32 * 128];
__device__ uint4 g_kv[NH * KV_HEAD_BYTES / 16];
__device__ float g_kvpart[16 * NH * 384];
__device__ float g_nrm[NH * 16 * 4];
__device__ __nv_bfloat16 g_o[2 * S_LEN * DM];

#define g_prof_set(k, i, v)
#define g_prof_dummy(i) true
#define PROF_T(k, i) do {} while (0)
#define PROF_G(k, i) do {} while (0)
__device__ __forceinline__ uint32_t smem_u32(const void* p) { return (uint32_t)__cvta_generic_to_shared(p); }
__device__ __forceinline__ void mbar_init(uint32_t bar, int cnt) {
  asm volatile("mbarrier.init.shared::cta.b64 [%0], %1;" ::"r"(bar), "r"(cnt) : "memory");
}
__device__ __forceinline__ void mbar_expect_tx(uint32_t bar, uint32_t bytes) {
  asm volatile("mbarrier.arrive.expect_tx.shared::cta.b64 _, [%0], %1;" ::"r"(bar), "r"(bytes) : "memory");
}
__device__ __forceinline__ void mbar_arrive(uint32_t bar) {
  asm volatile("mbarrier.arrive.shared::cta.b64 _, [%0];" ::"r"(bar) : "memory");
}
__device__ __forceinline__ void mbar_arrive_cluster(uint32_t bar, uint32_t cta) {
  asm volatile(
      "{\n.reg .b32 ra;\nmapa.shared::cluster.u32 ra, %0, %1;\n"
      "mbarrier.arrive.shared::cluster.b64 _, [ra];\n}" ::"r"(bar), "r"(cta) : "memory");
}
__device__ __forceinline__ void mbar_wait(uint32_t bar, uint32_t parity) {
  asm volatile(
      "{\n.reg .pred p;\n.reg .u32 n;\n"
      "mov.u32 n, 0;\n"
      "WAIT_LOOP:\n"
      "mbarrier.try_wait.parity.shared::cta.b64 p, [%0], %1, 0x400000;\n"
      "@p bra WAIT_DONE;\n"
      "add.u32 n, n, 1;\n"
      "setp.lt.u32 p, n, 4000000;\n"
      "@p bra WAIT_LOOP;\n"
      "trap;\n"
      "WAIT_DONE:\n}" ::"r"(bar), "r"(parity) : "memory");
}
__device__ __forceinline__ void fence_barrier_init() {
  asm volatile("fence.mbarrier_init.release.cluster;" ::: "memory");
}
__device__ __forceinline__ void fence_proxy_async() { asm volatile("fence.proxy.async.shared::cta;" ::: "memory"); }
__device__ __forceinline__ void cluster_sync_relaxed() {
  asm volatile("barrier.cluster.arrive.relaxed.aligned;\nbarrier.cluster.wait.aligned;" ::: "memory");
}
__device__ __forceinline__ void tma_load_2d(uint32_t dst, const CUtensorMap* m, int x, int y, uint32_t bar) {
  asm volatile(
      "cp.async.bulk.tensor.2d.shared::cluster.global.mbarrier::complete_tx::bytes [%0], [%1, {%3, %4}], [%2];" ::"r"(dst),
      "l"(m), "r"(bar), "r"(x), "r"(y)
      : "memory");
}
__device__ __forceinline__ void tma_load_2d_mc(uint32_t dst, const CUtensorMap* m, int x, int y, uint32_t bar, uint16_t mask) {
  asm volatile(
      "cp.async.bulk.tensor.2d.shared::cluster.global.mbarrier::complete_tx::bytes.multicast::cluster [%0], [%1, {%3, %4}], "
      "[%2], %5;" ::"r"(dst),
      "l"(m), "r"(bar), "r"(x), "r"(y), "h"(mask)
      : "memory");
}
__device__ __forceinline__ void tma_store_2d(const CUtensorMap* m, uint32_t src, int x, int y) {
  asm volatile("cp.async.bulk.tensor.2d.global.shared::cta.bulk_group [%0, {%2, %3}], [%1];" ::"l"(m), "r"(src), "r"(x),
               "r"(y)
               : "memory");
}
__device__ __forceinline__ void bulk_load(uint32_t dst, const void* src, uint32_t bytes, uint32_t bar) {
  asm volatile("cp.async.bulk.shared::cluster.global.mbarrier::complete_tx::bytes [%0], [%1], %2, [%3];" ::"r"(dst),
               "l"(src), "r"(bytes), "r"(bar)
               : "memory");
}
__device__ __forceinline__ void bulk_load_mc(uint32_t dst, const void* src, uint32_t bytes, uint32_t bar, uint16_t mask) {
  asm volatile("cp.async.bulk.shared::cluster.global.mbarrier::complete_tx::bytes.multicast::cluster [%0], [%1], %2, [%3], %4;" ::"r"(dst),
               "l"(src), "r"(bytes), "r"(bar), "h"(mask)
               : "memory");
}
__device__ __forceinline__ void pdl_launch_dependents() { asm volatile("griddepcontrol.launch_dependents;" ::: "memory"); }
__device__ __forceinline__ void pdl_wait() { asm volatile("griddepcontrol.wait;" ::: "memory"); }
__device__ __forceinline__ void wg_fence() { asm volatile("wgmma.fence.sync.aligned;" ::: "memory"); }
__device__ __forceinline__ void wg_commit() { asm volatile("wgmma.commit_group.sync.aligned;" ::: "memory"); }
template <int N>
__device__ __forceinline__ void wg_wait() {
  asm volatile("wgmma.wait_group.sync.aligned %0;" ::"n"(N) : "memory");
}
template <int M>
__device__ __forceinline__ void fence_regs(float (&r)[M]) {
#pragma unroll
  for (int i = 0; i < M; i++) asm volatile("" : "+f"(r[i])::"memory");
}
__device__ __forceinline__ uint64_t mkdesc(uint32_t addr, uint32_t lbo, uint32_t sbo, uint32_t layout) {
  return (uint64_t)((addr & 0x3FFFF) >> 4) | ((uint64_t)(lbo >> 4) << 16) | ((uint64_t)(sbo >> 4) << 32) |
         ((uint64_t)layout << 62);
}
__device__ __forceinline__ uint32_t pack_bf16(float lo, float hi) {
  uint32_t r;
  asm("cvt.rn.bf16x2.f32 %0, %1, %2;" : "=r"(r) : "f"(hi), "f"(lo));
  return r;
}
__device__ __forceinline__ float bf_lo(uint32_t v) { return __uint_as_float(v << 16); }
__device__ __forceinline__ float bf_hi(uint32_t v) { return __uint_as_float(v & 0xFFFF0000u); }
__device__ __forceinline__ float round_bf16(float x) { return bf_lo(pack_bf16(x, 0.f)); }
__device__ __forceinline__ float ex2f(float x) {
  float y;
  asm("ex2.approx.ftz.f32 %0, %1;" : "=f"(y) : "f"(x));
  return y;
}

__device__ __forceinline__ void wgmma_rs_n24_tb(float (&d)[12], uint32_t a0, uint32_t a1, uint32_t a2, uint32_t a3, uint64_t descB, int scaleD) {
  asm volatile("{\n.reg .pred p;\nsetp.ne.b32 p, %17, 0;\n"
    "wgmma.mma_async.sync.aligned.m64n24k16.f32.bf16.bf16 "
    "{%0, %1, %2, %3, %4, %5, %6, %7, %8, %9, %10, %11}, {%12, %13, %14, %15}, %16, p, 1, 1, 1;\n}\n"
    : "+f"(d[0]), "+f"(d[1]), "+f"(d[2]), "+f"(d[3]), "+f"(d[4]), "+f"(d[5]), "+f"(d[6]), "+f"(d[7]),
      "+f"(d[8]), "+f"(d[9]), "+f"(d[10]), "+f"(d[11])
    : "r"(a0), "r"(a1), "r"(a2), "r"(a3), "l"(descB), "r"(scaleD));
}
__device__ __forceinline__ void wgmma_rs_n64_z(float (&d)[32], uint32_t a0, uint32_t a1, uint32_t a2, uint32_t a3, uint64_t descB) {
  asm volatile("{\n.reg .pred p;\nsetp.ne.b32 p, %37, 0;\n"
    "wgmma.mma_async.sync.aligned.m64n64k16.f32.bf16.bf16 "
    "{%0, %1, %2, %3, %4, %5, %6, %7, %8, %9, %10, %11, %12, %13, %14, %15, %16, %17, %18, %19, %20, %21, %22, %23, %24, %25, %26, %27, %28, %29, %30, %31}, {%32, %33, %34, %35}, %36, p, 1, 1, 0;\n}\n"
    : "=f"(d[0]), "=f"(d[1]), "=f"(d[2]), "=f"(d[3]), "=f"(d[4]), "=f"(d[5]), "=f"(d[6]), "=f"(d[7]),
      "=f"(d[8]), "=f"(d[9]), "=f"(d[10]), "=f"(d[11]), "=f"(d[12]), "=f"(d[13]), "=f"(d[14]), "=f"(d[15]),
      "=f"(d[16]), "=f"(d[17]), "=f"(d[18]), "=f"(d[19]), "=f"(d[20]), "=f"(d[21]), "=f"(d[22]), "=f"(d[23]),
      "=f"(d[24]), "=f"(d[25]), "=f"(d[26]), "=f"(d[27]), "=f"(d[28]), "=f"(d[29]), "=f"(d[30]), "=f"(d[31])
    : "r"(a0), "r"(a1), "r"(a2), "r"(a3), "l"(descB), "n"(0));
}
__device__ __forceinline__ void wgmma_ss_n128_tb(float (&d)[64], uint64_t descA, uint64_t descB, int scaleD) {
  asm volatile("{\n.reg .pred p;\nsetp.ne.b32 p, %66, 0;\n"
    "wgmma.mma_async.sync.aligned.m64n128k16.f32.bf16.bf16 "
    "{%0, %1, %2, %3, %4, %5, %6, %7, %8, %9, %10, %11, %12, %13, %14, %15, %16, %17, %18, %19, %20, %21, %22, %23, %24, %25, %26, %27, %28, %29, %30, %31, %32, %33, %34, %35, %36, %37, %38, %39, %40, %41, %42, %43, %44, %45, %46, %47, %48, %49, %50, %51, %52, %53, %54, %55, %56, %57, %58, %59, %60, %61, %62, %63}, %64, %65, p, 1, 1, 0, 1;\n}\n"
    : "+f"(d[0]), "+f"(d[1]), "+f"(d[2]), "+f"(d[3]), "+f"(d[4]), "+f"(d[5]), "+f"(d[6]), "+f"(d[7]),
      "+f"(d[8]), "+f"(d[9]), "+f"(d[10]), "+f"(d[11]), "+f"(d[12]), "+f"(d[13]), "+f"(d[14]), "+f"(d[15]),
      "+f"(d[16]), "+f"(d[17]), "+f"(d[18]), "+f"(d[19]), "+f"(d[20]), "+f"(d[21]), "+f"(d[22]), "+f"(d[23]),
      "+f"(d[24]), "+f"(d[25]), "+f"(d[26]), "+f"(d[27]), "+f"(d[28]), "+f"(d[29]), "+f"(d[30]), "+f"(d[31]),
      "+f"(d[32]), "+f"(d[33]), "+f"(d[34]), "+f"(d[35]), "+f"(d[36]), "+f"(d[37]), "+f"(d[38]), "+f"(d[39]),
      "+f"(d[40]), "+f"(d[41]), "+f"(d[42]), "+f"(d[43]), "+f"(d[44]), "+f"(d[45]), "+f"(d[46]), "+f"(d[47]),
      "+f"(d[48]), "+f"(d[49]), "+f"(d[50]), "+f"(d[51]), "+f"(d[52]), "+f"(d[53]), "+f"(d[54]), "+f"(d[55]),
      "+f"(d[56]), "+f"(d[57]), "+f"(d[58]), "+f"(d[59]), "+f"(d[60]), "+f"(d[61]), "+f"(d[62]), "+f"(d[63])
    : "l"(descA), "l"(descB), "r"(scaleD));
}
__device__ __forceinline__ void wgmma_ss_n192_tb(float (&d)[96], uint64_t descA, uint64_t descB, int scaleD) {
  asm volatile("{\n.reg .pred p;\nsetp.ne.b32 p, %98, 0;\n"
    "wgmma.mma_async.sync.aligned.m64n192k16.f32.bf16.bf16 "
    "{%0, %1, %2, %3, %4, %5, %6, %7, %8, %9, %10, %11, %12, %13, %14, %15, %16, %17, %18, %19, %20, %21, %22, %23, %24, %25, %26, %27, %28, %29, %30, %31, %32, %33, %34, %35, %36, %37, %38, %39, %40, %41, %42, %43, %44, %45, %46, %47, %48, %49, %50, %51, %52, %53, %54, %55, %56, %57, %58, %59, %60, %61, %62, %63, %64, %65, %66, %67, %68, %69, %70, %71, %72, %73, %74, %75, %76, %77, %78, %79, %80, %81, %82, %83, %84, %85, %86, %87, %88, %89, %90, %91, %92, %93, %94, %95}, %96, %97, p, 1, 1, 0, 1;\n}\n"
    : "+f"(d[0]), "+f"(d[1]), "+f"(d[2]), "+f"(d[3]), "+f"(d[4]), "+f"(d[5]), "+f"(d[6]), "+f"(d[7]),
      "+f"(d[8]), "+f"(d[9]), "+f"(d[10]), "+f"(d[11]), "+f"(d[12]), "+f"(d[13]), "+f"(d[14]), "+f"(d[15]),
      "+f"(d[16]), "+f"(d[17]), "+f"(d[18]), "+f"(d[19]), "+f"(d[20]), "+f"(d[21]), "+f"(d[22]), "+f"(d[23]),
      "+f"(d[24]), "+f"(d[25]), "+f"(d[26]), "+f"(d[27]), "+f"(d[28]), "+f"(d[29]), "+f"(d[30]), "+f"(d[31]),
      "+f"(d[32]), "+f"(d[33]), "+f"(d[34]), "+f"(d[35]), "+f"(d[36]), "+f"(d[37]), "+f"(d[38]), "+f"(d[39]),
      "+f"(d[40]), "+f"(d[41]), "+f"(d[42]), "+f"(d[43]), "+f"(d[44]), "+f"(d[45]), "+f"(d[46]), "+f"(d[47]),
      "+f"(d[48]), "+f"(d[49]), "+f"(d[50]), "+f"(d[51]), "+f"(d[52]), "+f"(d[53]), "+f"(d[54]), "+f"(d[55]),
      "+f"(d[56]), "+f"(d[57]), "+f"(d[58]), "+f"(d[59]), "+f"(d[60]), "+f"(d[61]), "+f"(d[62]), "+f"(d[63]),
      "+f"(d[64]), "+f"(d[65]), "+f"(d[66]), "+f"(d[67]), "+f"(d[68]), "+f"(d[69]), "+f"(d[70]), "+f"(d[71]),
      "+f"(d[72]), "+f"(d[73]), "+f"(d[74]), "+f"(d[75]), "+f"(d[76]), "+f"(d[77]), "+f"(d[78]), "+f"(d[79]),
      "+f"(d[80]), "+f"(d[81]), "+f"(d[82]), "+f"(d[83]), "+f"(d[84]), "+f"(d[85]), "+f"(d[86]), "+f"(d[87]),
      "+f"(d[88]), "+f"(d[89]), "+f"(d[90]), "+f"(d[91]), "+f"(d[92]), "+f"(d[93]), "+f"(d[94]), "+f"(d[95])
    : "l"(descA), "l"(descB), "r"(scaleD));
}

__device__ __forceinline__ void ldsm4t(uint32_t (&b)[4], uint32_t addr) {
  asm volatile("ldmatrix.sync.aligned.m8n8.x4.trans.shared.b16 {%0,%1,%2,%3}, [%4];"
               : "=r"(b[0]), "=r"(b[1]), "=r"(b[2]), "=r"(b[3])
               : "r"(addr));
}
__device__ __forceinline__ void hmma(float (&c)[4], uint32_t a0, uint32_t a1, uint32_t a2, uint32_t a3, uint32_t b0, uint32_t b1) {
  asm("mma.sync.aligned.m16n8k16.row.col.f32.bf16.bf16.f32 {%0,%1,%2,%3}, {%4,%5,%6,%7}, {%8,%9}, {%0,%1,%2,%3};"
      : "+f"(c[0]), "+f"(c[1]), "+f"(c[2]), "+f"(c[3])
      : "r"(a0), "r"(a1), "r"(a2), "r"(a3), "r"(b0), "r"(b1));
}

__device__ __forceinline__ uint32_t movm(uint32_t a) {
  uint32_t d;
  asm volatile("movmatrix.sync.aligned.m8n8.trans.b16 %0, %1;" : "=r"(d) : "r"(a));
  return d;
}

#define K1_WARM 0
constexpr int K1_STAGES = 4;
constexpr int K1_W_BYTES = 3 * 8192;
constexpr int K1_X_BYTES = 8 * 16384;
constexpr int K1_BAR_OFF = K1_X_BYTES + K1_STAGES * K1_W_BYTES;
constexpr int K1_SMEM = K1_BAR_OFF + 192 + 1024;
constexpr float QSCALE = 0.25f * 1.4426950408889634f;

__device__ __forceinline__ uint32_t phi2(uint32_t t2) {
  uint32_t a2, mask, r2, o2;
  asm("add.rn.bf16x2 %0, %1, %2;" : "=r"(a2) : "r"(t2), "r"(0x3F803F80u));
  const uint32_t e2 = pack_bf16(ex2f(bf_lo(t2) * 1.4426950408889634f), ex2f(bf_hi(t2) * 1.4426950408889634f));
  asm("set.gt.u32.bf16x2 %0, %1, %2;" : "=r"(mask) : "r"(t2), "r"(0u));
  r2 = (a2 & mask) | (e2 & ~mask);
  asm("add.rn.bf16x2 %0, %1, %2;" : "=r"(o2) : "r"(r2), "r"(0x35863586u));
  return o2;
}

#define K1_SLOT_KB(h) ((h) < 4 ? 2 * (h) : 2 * ((h) - 4) + 1)
struct EpiCtx {
  uint4* qf;
  uint32_t* kp;
  uint32_t* vp;
  uint32_t* s_red;
  float* red;
  int lane;
};

template <bool LINEAR, int HH, int PART>
__device__ __forceinline__ void epi_slice(const float (&acc)[96], const EpiCtx& c, uint32_t (&pk)[4], float& vmax, bool live) {
  const float* a = &acc[HH * 8];
  const float* k = &acc[32 + HH * 8];
  const float* v = &acc[64 + HH * 8];
  if (!LINEAR) {
    if (PART == 0) {
      uint32_t* kh = c.kp + HH * (KV_HEAD_BYTES / 4);
      if (live) {
        c.qf[HH * 32 * 128] = make_uint4(pack_bf16(a[0] * QSCALE, a[1] * QSCALE), pack_bf16(a[2] * QSCALE, a[3] * QSCALE),
                                         pack_bf16(a[4] * QSCALE, a[5] * QSCALE), pack_bf16(a[6] * QSCALE, a[7] * QSCALE));
        kh[0] = pack_bf16(k[0], k[1]);
        kh[64] = pack_bf16(k[2], k[3]);
        kh[32] = pack_bf16(k[4], k[5]);
        kh[96] = pack_bf16(k[6], k[7]);
      }
      float q0 = a[0] * a[0] + a[1] * a[1] + a[4] * a[4] + a[5] * a[5];
      float q1 = a[2] * a[2] + a[3] * a[3] + a[6] * a[6] + a[7] * a[7];
      float k0 = k[0] * k[0] + k[1] * k[1] + k[4] * k[4] + k[5] * k[5];
      float k1 = k[2] * k[2] + k[3] * k[3] + k[6] * k[6] + k[7] * k[7];
#pragma unroll
      for (int o = 1; o <= 2; o <<= 1) {
        q0 += __shfl_xor_sync(0xffffffffu, q0, o);
        q1 += __shfl_xor_sync(0xffffffffu, q1, o);
        k0 += __shfl_xor_sync(0xffffffffu, k0, o);
        k1 += __shfl_xor_sync(0xffffffffu, k1, o);
      }
      const uint32_t qm = __reduce_max_sync(0xffffffffu, max(__float_as_uint(q0) & 0x7FFFFFFFu, __float_as_uint(q1) & 0x7FFFFFFFu));
      const uint32_t km = __reduce_max_sync(0xffffffffu, max(__float_as_uint(k0) & 0x7FFFFFFFu, __float_as_uint(k1) & 0x7FFFFFFFu));
      if (c.lane == 0 && live) {
        atomicMax(&c.s_red[HH * 2 + 0], qm);
        atomicMax(&c.s_red[HH * 2 + 1], km);
      }
    } else {
      uint32_t* vh = c.vp + HH * (KV_HEAD_BYTES / 4);
      if (live) {
        vh[0] = pack_bf16(v[0], v[1]);
        vh[96] = pack_bf16(v[2], v[3]);
        vh[32] = pack_bf16(v[4], v[5]);
        vh[128] = pack_bf16(v[6], v[7]);
        vh[64] = 0x3F803F80u;
        vh[160] = 0x3F803F80u;
      }
#pragma unroll
      for (int i = 0; i < 8; i++) asm("max.NaN.f32 %0, %0, %1;" : "+f"(vmax) : "f"(fabsf(v[i])));
    }
  } else {
    if (PART == 0) {
      const uint4 pq = make_uint4(phi2(pack_bf16(a[0], a[1])), phi2(pack_bf16(a[2], a[3])), phi2(pack_bf16(a[4], a[5])),
                                  phi2(pack_bf16(a[6], a[7])));
      if (live) c.qf[HH * 32 * 128] = pq;
      pk[0] = movm(phi2(pack_bf16(k[0], k[1])));
      pk[2] = movm(phi2(pack_bf16(k[2], k[3])));
      pk[1] = movm(phi2(pack_bf16(k[4], k[5])));
      pk[3] = movm(phi2(pack_bf16(k[6], k[7])));
    } else {
      const uint32_t b0 = movm(pack_bf16(v[0], v[1]));
      const uint32_t b1 = movm(pack_bf16(v[2], v[3]));
      const uint32_t b2 = movm(pack_bf16(v[4], v[5]));
      const uint32_t b3 = movm(pack_bf16(v[6], v[7]));
      float c0[4] = {0, 0, 0, 0}, c1[4] = {0, 0, 0, 0}, c2[4] = {0, 0, 0, 0};
      hmma(c0, pk[0], pk[1], pk[2], pk[3], b0, b1);
      hmma(c1, pk[0], pk[1], pk[2], pk[3], b2, b3);
      hmma(c2, pk[0], pk[1], pk[2], pk[3], 0x3F803F80u, 0x3F803F80u);
      float* slot = c.red + HH * 2 * 4096;
      if (live) {
#pragma unroll
        for (int i = 0; i < 4; i++) {
          slot[i * 32] = c0[i];
          slot[(4 + i) * 32] = c1[i];
          slot[(8 + i) * 32] = c2[i];
        }
      }
    }
  }
}

template <bool LINEAR>
__device__ __forceinline__ void qkv_consumer(uint32_t sbase, uint8_t* smem_gen, uint32_t* s_red, int cp, int rt) {
  const uint32_t bar_full = sbase + K1_BAR_OFF;
  const uint32_t bar_empty = bar_full + 8 * K1_STAGES;
  const int warp = threadIdx.x >> 5;
  const int wg = warp >> 2;
  const int lane = threadIdx.x & 31;
  float accN[96], accP[96];
  EpiCtx c;
  {
    const int row0 = rt * 128 + wg * 64 + (warp & 3) * 16;
    c.qf = g_qfrag + ((size_t)((LINEAR ? NH : 0) + cp * 8) * 32 + (rt * 2 + wg)) * 128 + (threadIdx.x & 127);
    uint32_t* img = reinterpret_cast<uint32_t*>(reinterpret_cast<uint8_t*>(g_kv) + (size_t)(cp * 8) * KV_HEAD_BYTES);
    c.kp = img + (row0 >> 3) * 64 + lane;
    c.vp = img + KV_K_BYTES / 4 + (row0 >> 3) * 96 + lane;
    c.s_red = s_red;
    c.red = reinterpret_cast<float*>(smem_gen + wg * 8192) + (warp & 3) * 384 + lane;
    c.lane = lane;
  }
  uint32_t pk[4] = {0, 0, 0, 0};
  float vmax = 0.f;
#pragma unroll
  for (int i = 0; i < 96; i++) asm volatile("mov.f32 %0, 0f00000000;" : "=f"(accN[i]));
  int npass;
  asm volatile("mov.u32 %0, 2;" : "=r"(npass));
#pragma unroll 1
  for (int pass = K1_WARM ? 0 : 1; pass < npass; pass++) {
    const bool live = K1_WARM ? pass != 0 : true;
    if (live) {
#pragma unroll 1
      for (int kb = 0; kb < 8; kb++) {
        const int s = kb % K1_STAGES;
        mbar_wait(bar_full + 8 * s, (kb / K1_STAGES) & 1);
        if (threadIdx.x == 0) PROF_T(0, 2 + (kb >> 1));
        const uint64_t dA = mkdesc(sbase + kb * 16384 + wg * 8192, 16, 1024, 1);
        const uint64_t dB = mkdesc(sbase + K1_X_BYTES + s * K1_W_BYTES, 8192, 1024, 1);
        wg_fence();
#pragma unroll
        for (int k = 0; k < 4; k++) wgmma_ss_n192_tb(accP, dA + k * 2, dB + k * 128, (kb | k) != 0);
        wg_commit();
        if (kb > 0) {
          wg_wait<1>();
          if ((threadIdx.x & 127) == 0) {
            const int sp = (kb - 1) % K1_STAGES;
            mbar_arrive_cluster(bar_empty + 8 * sp, 0);
            mbar_arrive_cluster(bar_empty + 8 * sp, 1);
          }
        }
      }
      wg_wait<0>();
      fence_regs(accP);
      if ((threadIdx.x & 127) == 0) {
        mbar_arrive_cluster(bar_empty + 8 * (7 % K1_STAGES), 0);
        mbar_arrive_cluster(bar_empty + 8 * (7 % K1_STAGES), 1);
      }
      if (threadIdx.x == 0) PROF_T(0, 6);
#define K1_T1_STEP(KB)                                                                           \
  {                                                                                              \
    constexpr int g = 8 + KB;                                                                    \
    constexpr int s = g % K1_STAGES;                                                             \
    mbar_wait(bar_full + 8 * s, (g / K1_STAGES) & 1);                                            \
    const uint64_t dA = mkdesc(sbase + KB * 16384 + wg * 8192, 16, 1024, 1);                     \
    const uint64_t dB = mkdesc(sbase + K1_X_BYTES + s * K1_W_BYTES, 8192, 1024, 1);              \
    wg_fence();                                                                                  \
    _Pragma("unroll") for (int k = 0; k < 4; k++) wgmma_ss_n192_tb(accN, dA + k * 2, dB + k * 128, (KB | k) != 0); \
    wg_commit();                                                                                 \
    epi_slice<LINEAR, KB / 2, KB & 1>(accP, c, pk, vmax, true);                                  \
    wg_wait<0>();                                                                                \
    if (KB + K1_STAGES < 8 && (threadIdx.x & 127) == 0) {                                        \
      mbar_arrive_cluster(bar_empty + 8 * s, 0);                                                 \
      mbar_arrive_cluster(bar_empty + 8 * s, 1);                                                 \
    }                                                                                            \
  }
      K1_T1_STEP(0) K1_T1_STEP(1) K1_T1_STEP(2) K1_T1_STEP(3) K1_T1_STEP(4) K1_T1_STEP(5) K1_T1_STEP(6) K1_T1_STEP(7)
#undef K1_T1_STEP
      fence_regs(accN);
      if (threadIdx.x == 0) PROF_T(0, 10);
      c.qf += 4 * 32 * 128;
      c.kp += 4 * (KV_HEAD_BYTES / 4);
      c.vp += 4 * (KV_HEAD_BYTES / 4);
      c.s_red += 8;
      c.red += 4096;
    }
    float vm1 = 0.f;
    epi_slice<LINEAR, 0, 0>(accN, c, pk, vm1, live);
    epi_slice<LINEAR, 0, 1>(accN, c, pk, vm1, live);
    epi_slice<LINEAR, 1, 0>(accN, c, pk, vm1, live);
    epi_slice<LINEAR, 1, 1>(accN, c, pk, vm1, live);
    epi_slice<LINEAR, 2, 0>(accN, c, pk, vm1, live);
    epi_slice<LINEAR, 2, 1>(accN, c, pk, vm1, live);
    epi_slice<LINEAR, 3, 0>(accN, c, pk, vm1, live);
    epi_slice<LINEAR, 3, 1>(accN, c, pk, vm1, live);
    if (live) asm("max.NaN.f32 %0, %0, %1;" : "+f"(vmax) : "f"(vm1));
  }
  if (!LINEAR) {
    const uint32_t vm = __reduce_max_sync(0xffffffffu, __float_as_uint(vmax) & 0x7FFFFFFFu);
    if (lane == 0) atomicMax(&s_red[16], vm);
    asm volatile("bar.sync 1, 256;" ::: "memory");
    if (threadIdx.x < 8) {
      *reinterpret_cast<float4*>(&g_nrm[((cp * 8 + threadIdx.x) * 16 + rt) * 4]) =
          make_float4(__uint_as_float(s_red[threadIdx.x * 2]), __uint_as_float(s_red[threadIdx.x * 2 + 1]), __uint_as_float(s_red[16]), 0.f);
    }
  } else {
    asm volatile("bar.sync 1, 256;" ::: "memory");
    float* dst = g_kvpart + ((size_t)rt * NH + cp * 8) * 384;
#pragma unroll
    for (int i = 0; i < 12; i++) {
      const int o = threadIdx.x + i * 256;
      const int h = o / 384, e = o - h * 384;
      const float* src = reinterpret_cast<const float*>(smem_gen) + K1_SLOT_KB(h) * 4096 + e;
      float sum = 0.f;
#pragma unroll
      for (int w = 0; w < 8; w++) sum += src[(w >> 2) * 2048 + (w & 3) * 384];
      dst[o] = sum;
    }
  }
}

__global__ void __launch_bounds__(384, 1)
qkv_gemm_kernel(const __grid_constant__ CUtensorMap mxA, const __grid_constant__ CUtensorMap mxB,
                const __grid_constant__ CUtensorMap mwA, const __grid_constant__ CUtensorMap mwB) {
  extern __shared__ uint8_t smem_raw[];
  const uint32_t sbase = (smem_u32(smem_raw) + 1023) & ~1023u;
  uint8_t* smem_gen = smem_raw + (sbase - smem_u32(smem_raw));
  const uint32_t bar_full = sbase + K1_BAR_OFF;
  const uint32_t bar_empty = bar_full + 8 * K1_STAGES;
  uint32_t* s_red = reinterpret_cast<uint32_t*>(smem_gen + K1_BAR_OFF + 64);

  const int rank = blockIdx.x & 1;
  const int pair = blockIdx.x >> 1;
  const int branch = pair >> 5;
  const int rp = (pair & 31) >> 2;
  const int cp = pair & 3;
  const int rt = rp * 2 + rank;
  const int warp = threadIdx.x >> 5;
  if (threadIdx.x == 0) { PROF_G(0, 30); PROF_T(0, 0); }
  const CUtensorMap* mx = branch ? &mxA : &mxB;
  const CUtensorMap* mw = branch ? &mwA : &mwB;

  if (threadIdx.x == 256) {
    asm volatile("prefetch.tensormap [%0];" ::"l"(mx) : "memory");
    asm volatile("prefetch.tensormap [%0];" ::"l"(mw) : "memory");
    for (int i = 0; i < K1_STAGES; i++) {
      mbar_init(bar_full + 8 * i, 1);
      mbar_init(bar_empty + 8 * i, 4);
    }
    fence_barrier_init();
    fence_proxy_async();
    for (int kb = 0; kb < K1_STAGES; kb++) mbar_expect_tx(bar_full + 8 * kb, 16384 + K1_W_BYTES);
    tma_load_2d(sbase, mx, 0, rt * 128, bar_full);
  }
  pdl_launch_dependents();
  if (threadIdx.x < 32) s_red[threadIdx.x] = 0;
  __syncthreads();
  cluster_sync_relaxed();
  if (threadIdx.x == 0) PROF_T(0, 1);

  if (warp >= 8) {
    asm volatile("setmaxnreg.dec.sync.aligned.u32 40;");
    if (threadIdx.x == 256) {
      for (int g = 0; g < 16; g++) {
        const int s = g % K1_STAGES;
        const int kb = g & 7;
        if (g >= K1_STAGES) {
          mbar_wait(bar_empty + 8 * s, ((g / K1_STAGES) - 1) & 1);
          mbar_expect_tx(bar_full + 8 * s, (g < 8 ? 16384 : 0) + K1_W_BYTES);
        }
        if (g > 0 && g < 8) tma_load_2d(sbase + kb * 16384, mx, kb * 64, rt * 128, bar_full + 8 * s);
        const int h0 = cp * 8 + (g >> 3) * 4;
        const uint32_t st = sbase + K1_X_BYTES + s * K1_W_BYTES + rank * 4096;
#pragma unroll
        for (int p = 0; p < 3; p++)
          tma_load_2d_mc(st + p * 8192, mw, p * 512 + h0 * 16, kb * 64 + rank * 32, bar_full + 8 * s, (uint16_t)3);
      }
    }
    __syncwarp();
    cluster_sync_relaxed();
  } else {
    asm volatile("setmaxnreg.inc.sync.aligned.u32 232;");
    if (branch == 0) qkv_consumer<false>(sbase, smem_gen, s_red, cp, rt);
    else qkv_consumer<true>(sbase, smem_gen, s_red, cp, rt);
    if (threadIdx.x == 0) PROF_T(0, 11);
    __syncwarp();
    cluster_sync_relaxed();
    if (threadIdx.x == 0) { PROF_T(0, 12); PROF_G(0, 31); }
  }
}

constexpr int K2_SMEM = KV_HEAD_BYTES + 1024 + 256;

#define ATT_NPOLY 18
#define ATT_CH 8
#define ATT_D 1
#define PRO_MODE 1
#define STAGGER 0
#define K2_WARM 1
#define CONST_SMID 0
#define ATT_STRUCT 1
#define ATT_PIN 0
#define ATT_GM 1
#define ATT_DEG 2
struct ExpC {
  uint32_t k3c00, kmask, seven, c3;
};
__device__ __forceinline__ uint32_t hfma2(uint32_t a, uint32_t b, uint32_t c) {
  uint32_t r;
  asm("fma.rn.f16x2 %0, %1, %2, %3;" : "=r"(r) : "r"(a), "r"(b), "r"(c));
  return r;
}
__device__ __forceinline__ uint32_t exp2_poly_pair(float t0, float t1, const ExpC& c) {
  uint32_t u;
  asm("prmt.b32 %0, %1, %2, 0x5410;" : "=r"(u) : "r"(__float_as_uint(t0)), "r"(__float_as_uint(t1)));
  uint32_t m;
  asm("lop3.b32 %0, %1, 0x03FF03FF, %2, 0xEA;" : "=r"(m) : "r"(u), "r"(c.k3c00));
  uint32_t p = hfma2(m, c.c3, 0xa385a385u);
  p = hfma2(p, m, 0x4ad64ad7u);
  uint32_t mu;
  asm("lop3.b32 %0, %1, 0xFC00FC00, %2, 0xEA;" : "=r"(mu) : "r"(u), "r"(c.kmask));
  uint32_t r;
  asm("{.reg .b32 t; shf.r.wrap.b32 t, %1, %2, 3; add.u32 %0, t, %3;}" : "=r"(r) : "r"(mu), "r"(c.seven), "r"(p));
  return r;
}
__device__ __forceinline__ float gadd(float x, float M, uint32_t g) {
  float r = x;
  asm("{.reg .pred p; setp.ne.b32 p, %2, -1; @p add.f32 %0, %0, %1;}" : "+f"(r) : "f"(M), "r"(g));
  return r;
}
__device__ __forceinline__ float gex2(float x, uint32_t g) {
  float r = x;
  asm("{.reg .pred p; setp.ne.b32 p, %1, -1; @p ex2.approx.ftz.f32 %0, %0;}" : "+f"(r) : "r"(g));
  return r;
}
template <int NPOLY, int NPAIR, int CH, int D, bool G0 = false>
__device__ __forceinline__ void exp_tile(const float (&s)[2 * NPAIR], uint32_t (&p)[NPAIR], const ExpC& c, uint32_t g0 = 0) {
#pragma unroll
  for (int i = 0; i < NPAIR; i++) {
    const bool isPoly = ((i + 1) * NPOLY / 32) != (i * NPOLY / 32);
    const int ch = i / CH;
    const bool gated = ch >= D || G0;
    int gi = (ch - D) * CH + CH - 1;
    if (ch >= D) {
      while (gi > (ch - D) * CH && !(((gi + 1) * NPOLY / 32) != (gi * NPOLY / 32))) gi--;
    }
    const uint32_t g = ch >= D ? p[gi] : g0;
    if (!isPoly) {
      if (gated && ATT_GM) p[i] = pack_bf16(gex2(s[2 * i], g), gex2(s[2 * i + 1], g));
      else p[i] = pack_bf16(ex2f(s[2 * i]), ex2f(s[2 * i + 1]));
    } else {
      if (gated) p[i] = exp2_poly_pair(gadd(s[2 * i], 12329.f, g), gadd(s[2 * i + 1], 12329.f, g), c);
      else p[i] = exp2_poly_pair(s[2 * i] + 12329.f, s[2 * i + 1] + 12329.f, c);
    }
  }
}

__device__ __forceinline__ void store_o(__nv_bfloat16* o, int row0, int head, int lane, const uint32_t (&r)[4]) {
  const int g = lane >> 2, t = lane & 3;
  uint32_t* p0 = reinterpret_cast<uint32_t*>(o + (size_t)(row0 + g) * DM + head * 16) + t;
  uint32_t* p1 = reinterpret_cast<uint32_t*>(o + (size_t)(row0 + g + 8) * DM + head * 16) + t;
  p0[0] = r[0];
  p1[0] = r[1];
  p0[4] = r[2];
  p1[4] = r[3];
}

__device__ __forceinline__ void kv_fetch_piece(uint32_t sbase, uint32_t bar, int piece) {
  const uint8_t* img = reinterpret_cast<const uint8_t*>(g_kv) + (size_t)(blockIdx.x >> 2) * KV_HEAD_BYTES;
  const int g = piece >> 1, isv = piece & 1;
  const int e0 = g == 0 ? 0 : (isv ? 256 : 320) + (g - 1) * 512;
  const int e1 = g == 3 ? 2048 : (isv ? 256 : 320) + g * 512;
  const int bytes = (e1 - e0) * (isv ? 48 : 32);
  const int off = isv ? KV_K_BYTES + e0 * 48 : e0 * 32;
  mbar_expect_tx(bar + 8 * g, bytes);
  bulk_load(sbase + off, img + off, bytes, bar + 8 * g);
}

__device__ __forceinline__ void safe_exp(const float (&s)[32], uint32_t (&p)[16], float (&o)[12], float& m0, float& m1) {
  float x0 = s[0], x1 = s[2];
#pragma unroll
  for (int i = 0; i < 8; i++) {
    x0 = fmaxf(x0, fmaxf(s[4 * i], s[4 * i + 1]));
    x1 = fmaxf(x1, fmaxf(s[4 * i + 2], s[4 * i + 3]));
  }
  x0 = fmaxf(x0, __shfl_xor_sync(0xffffffffu, x0, 1));
  x1 = fmaxf(x1, __shfl_xor_sync(0xffffffffu, x1, 1));
  x0 = fmaxf(x0, __shfl_xor_sync(0xffffffffu, x0, 2));
  x1 = fmaxf(x1, __shfl_xor_sync(0xffffffffu, x1, 2));
  const float n0 = fmaxf(m0, x0), n1 = fmaxf(m1, x1);
  const float c0 = ex2f(m0 - n0), c1 = ex2f(m1 - n1);
  m0 = n0;
  m1 = n1;
#pragma unroll
  for (int i = 0; i < 3; i++) {
    o[4 * i] *= c0;
    o[4 * i + 1] *= c0;
    o[4 * i + 2] *= c1;
    o[4 * i + 3] *= c1;
  }
#pragma unroll
  for (int i = 0; i < 8; i++) {
    p[2 * i] = pack_bf16(ex2f(s[4 * i] - n0), ex2f(s[4 * i + 1] - n0));
    p[2 * i + 1] = pack_bf16(ex2f(s[4 * i + 2] - n1), ex2f(s[4 * i + 3] - n1));
  }
}

__device__ __forceinline__ void attn_step(float (&sx)[32], float (&sy)[32], float (&o)[12], const uint4& qf, uint64_t dK, uint64_t dV,
                                          const ExpC& ec) {
  uint32_t pa[16], pb[16];
  wg_fence();
  wgmma_rs_n64_z(sy, qf.x, qf.y, qf.z, qf.w, dK + 128);
  wg_commit();
  exp_tile<ATT_NPOLY, 16, ATT_CH, ATT_D>(sx, pa, ec);
  wg_fence();
  wgmma_rs_n24_tb(o, pa[12], pa[13], pa[14], pa[15], dV + 3 * 48, 1);
  wg_commit();
  wg_wait<1>();
  fence_regs(sy);
  exp_tile<ATT_NPOLY, 16, ATT_CH, ATT_D>(sy, pb, ec);
  wg_fence();
#pragma unroll
  for (int k = 0; k < 3; k++) wgmma_rs_n24_tb(o, pa[4 * k], pa[4 * k + 1], pa[4 * k + 2], pa[4 * k + 3], dV + k * 48, 1);
#pragma unroll
  for (int k = 0; k < 4; k++) wgmma_rs_n24_tb(o, pb[4 * k], pb[4 * k + 1], pb[4 * k + 2], pb[4 * k + 3], dV + (4 + k) * 48, 1);
  wgmma_rs_n64_z(sy, qf.x, qf.y, qf.z, qf.w, dK + 256);
  wg_commit();
  wg_wait<0>();
  fence_regs(sy);
}

template <bool SAFE>
__device__ __forceinline__ void attn_tile(uint64_t dK, uint64_t dV, uint32_t bar, const uint4 qf, const ExpC& ec, uint32_t (&outp)[4],
                                          bool warm) {
  float o[12];
#pragma unroll
  for (int i = 0; i < 12; i++) asm volatile("mov.f32 %0, 0f00000000;" : "=f"(o[i]));
  if (!warm) mbar_wait(bar, 0);
  if (!SAFE) {
    float s0[32], s1[32];
    wg_fence();
    wgmma_rs_n64_z(s0, qf.x, qf.y, qf.z, qf.w, dK);
    wg_commit();
    wg_wait<0>();
    fence_regs(s0);
#pragma unroll 1
    for (int p = warm ? 7 : 0; p < 8; p++) {
      if ((p & 1) && !warm) mbar_wait(bar + 8 * min((p + 1) >> 1, 3), 0);
      attn_step(s0, s1, o, qf, dK, dV, ec);
      attn_step(s1, s0, o, qf, dK + 256, dV + 384, ec);
      dK += 512;
      dV += 768;
    }
  } else {
    float m0 = -INFINITY, m1 = -INFINITY;
#pragma unroll 1
    for (int j = 0; j < 32; j++) {
      if (j == 4) { mbar_wait(bar + 8, 0); mbar_wait(bar + 16, 0); mbar_wait(bar + 24, 0); }
      float s[32];
      uint32_t p[16];
      wg_fence();
      wgmma_rs_n64_z(s, qf.x, qf.y, qf.z, qf.w, dK);
      wg_commit();
      wg_wait<0>();
      fence_regs(s);
      safe_exp(s, p, o, m0, m1);
      wg_fence();
#pragma unroll
      for (int k = 0; k < 4; k++) wgmma_rs_n24_tb(o, p[4 * k], p[4 * k + 1], p[4 * k + 2], p[4 * k + 3], dV + k * 48, 1);
      wg_commit();
      wg_wait<0>();
      fence_regs(o);
      dK += 128;
      dV += 192;
    }
  }
  fence_regs(o);
  const float r0 = 1.0f / o[8], r1 = 1.0f / o[10];
  outp[0] = pack_bf16(o[0] * r0, o[1] * r0);
  outp[1] = pack_bf16(o[2] * r1, o[3] * r1);
  outp[2] = pack_bf16(o[4] * r0, o[5] * r0);
  outp[3] = pack_bf16(o[6] * r1, o[7] * r1);
}

__device__ __forceinline__ void linear_attn_cta(uint8_t* smem_raw, uint32_t sbase, const CUtensorMap* mo16, int cta) {
  const int warp = threadIdx.x >> 5, lane = threadIdx.x & 31;
  float* red = reinterpret_cast<float*>(smem_raw + (sbase - smem_u32(smem_raw)) + 131072);
  {
    const float* src = g_kvpart + (size_t)cta * 8 * 384;
    float sum[6];
#pragma unroll
    for (int i = 0; i < 6; i++) sum[i] = 0.f;
#pragma unroll
    for (int r = 0; r < 16; r++) {
#pragma unroll
      for (int i = 0; i < 6; i++) sum[i] += src[(size_t)r * NH * 384 + threadIdx.x + i * 512];
    }
#pragma unroll
    for (int i = 0; i < 6; i++) red[threadIdx.x + i * 512] = round_bf16(sum[i]);
  }
  __syncthreads();
  uint32_t bf[8][6];
  {
    const int g = lane >> 2, t = lane & 3;
#pragma unroll
    for (int h = 0; h < 8; h++) {
#pragma unroll
      for (int f = 0; f < 6; f++) {
        const int blk = f >> 1, half = f & 1;
        const int e = (blk == 2) ? 0 : g;
        const int d = 2 * t + 8 * half;
        const int base = h * 384 + (blk * 4 + half * 2 + (e & 1)) * 32 + (e >> 1);
        bf[h][f] = pack_bf16(red[base + (d & 7) * 4], red[base + ((d + 1) & 7) * 4]);
      }
    }
  }
  const uint32_t stg = sbase + warp * 8192;
#pragma unroll 1
  for (int rb = 0; rb < 8; rb++) {
    const int blk16 = rb * 16 + warp;
    const uint4* qp = g_qfrag + ((size_t)(NH + cta * 8) * 32 + (blk16 >> 2)) * 128 + (blk16 & 3) * 32 + lane;
    uint4 q[8];
#pragma unroll
    for (int h = 0; h < 8; h++) q[h] = qp[h * 32 * 128];
    const uint32_t buf = stg + (rb & 1) * 4096;
    if (rb >= 2) {
      if (lane == 0) asm volatile("cp.async.bulk.wait_group.read 1;" ::: "memory");
      __syncwarp();
    }
#pragma unroll
    for (int h = 0; h < 8; h++) {
      float n0[4] = {0, 0, 0, 0}, n1[4] = {0, 0, 0, 0}, dn[4] = {0, 0, 0, 0};
      hmma(n0, q[h].x, q[h].y, q[h].z, q[h].w, bf[h][0], bf[h][1]);
      hmma(n1, q[h].x, q[h].y, q[h].z, q[h].w, bf[h][2], bf[h][3]);
      hmma(dn, q[h].x, q[h].y, q[h].z, q[h].w, bf[h][4], bf[h][5]);
      const float d0 = round_bf16(round_bf16(dn[0]) + 1e-6f), d1 = round_bf16(round_bf16(dn[2]) + 1e-6f);
      const uint32_t r0 = pack_bf16(__fdividef(round_bf16(n0[0]), d0), __fdividef(round_bf16(n0[1]), d0));
      const uint32_t r1 = pack_bf16(__fdividef(round_bf16(n0[2]), d1), __fdividef(round_bf16(n0[3]), d1));
      const uint32_t r2 = pack_bf16(__fdividef(round_bf16(n1[0]), d0), __fdividef(round_bf16(n1[1]), d0));
      const uint32_t r3 = pack_bf16(__fdividef(round_bf16(n1[2]), d1), __fdividef(round_bf16(n1[3]), d1));
      const int row = lane & 15;
      const int chunk = (h & 3) * 2 + (lane >> 4);
      const uint32_t addr = buf + (h >> 2) * 2048 + row * 128 + ((chunk ^ (row & 7)) << 4);
      asm volatile("stmatrix.sync.aligned.m8n8.x4.shared.b16 [%0], {%1,%2,%3,%4};" ::"r"(addr), "r"(r0), "r"(r1), "r"(r2), "r"(r3)
                   : "memory");
    }
    fence_proxy_async();
    __syncwarp();
    if (lane == 0) {
      tma_store_2d(mo16, buf, cta * 128, blk16 * 16);
      tma_store_2d(mo16, buf + 2048, cta * 128 + 64, blk16 * 16);
      asm volatile("cp.async.bulk.commit_group;" ::: "memory");
    }
  }
  if (lane == 0) asm volatile("cp.async.bulk.wait_group 0;" ::: "memory");
}

__global__ void __launch_bounds__(512, 1)
attn_kernel(const __grid_constant__ CUtensorMap mo16, const uint8_t* __restrict__ woA, const uint8_t* __restrict__ woB) {
  extern __shared__ uint8_t smem_raw[];
  const uint32_t sbase = (smem_u32(smem_raw) + 1023) & ~1023u;
  const uint32_t bar = sbase + KV_HEAD_BYTES;
  if (threadIdx.x == 0) { PROF_G(1, 30); PROF_T(1, 0); }
  if (threadIdx.x == 0) {
    for (int i = 0; i < 4; i++) mbar_init(bar + 8 * i, 2);
    asm volatile("st.shared.v4.u32 [%0], {%1, %2, %3, %4};" ::"r"(bar + 64), "r"(0x3C003C00u), "r"(0x00070000u), "r"(7u),
                 "r"(ATT_DEG == 3 ? 0x2cfd2cfdu : 0x35623562u)
                 : "memory");
    fence_barrier_init();
    fence_proxy_async();
  }
  __syncthreads();
  pdl_launch_dependents();
  if (blockIdx.x >= 128 && threadIdx.x < 16) {
    const int i = (blockIdx.x - 128) * 16 + threadIdx.x;
    const uint8_t* p = (i < 32 ? woA : woB) + (size_t)(i & 31) * 16384;
    asm volatile("cp.async.bulk.prefetch.L2.global [%0], %1;" ::"l"(p), "r"(16384) : "memory");
  }
  if (blockIdx.x >= 128) {
    pdl_wait();
    linear_attn_cta(smem_raw, sbase, &mo16, blockIdx.x - 128);
    if (threadIdx.x == 0) { PROF_T(1, 5); PROF_G(1, 31); }
    return;
  }
  const int head = blockIdx.x >> 2, qb = blockIdx.x & 3;
  const int lane = threadIdx.x & 31;
  const int wg = threadIdx.x >> 7, warp = (threadIdx.x >> 5) & 3;
  ExpC ec;
  asm volatile("ld.volatile.shared.v4.u32 {%0, %1, %2, %3}, [%4];" : "=r"(ec.k3c00), "=r"(ec.kmask), "=r"(ec.seven), "=r"(ec.c3) : "r"(bar + 64));
  const uint64_t dK = mkdesc(sbase, 128, 256, 0);
  const uint64_t dV = mkdesc(sbase + KV_K_BYTES, 384, 128, 0);
  uint4 qnext = make_uint4(0, 0, 0, 0);
  bool safe_path = false;
#pragma unroll 1
  for (int t = (K2_WARM && blockIdx.x < 4) ? -1 : 0; t < 2; t++) {
    if (t == 0) {
      pdl_wait();
      if (threadIdx.x == 0) { PROF_T(1, 7); PROF_G(1, 29); }
      if (threadIdx.x == 0) {
#pragma unroll
        for (int piece = 0; piece < 8; piece++) kv_fetch_piece(sbase, bar, piece);
      }
      qnext = g_qfrag[(head * 32 + qb * 8 + wg * 2) * 128 + (threadIdx.x & 127)];
      float4 n = make_float4(0.f, 0.f, 0.f, 0.f);
      if (lane < 16) n = *reinterpret_cast<const float4*>(&g_nrm[(head * 16 + lane) * 4]);
      uint32_t qm = ((lane >> 2) == qb) ? __float_as_uint(n.x) : 0u;
      qm = __reduce_max_sync(0xffffffffu, qm);
      const uint32_t km = __reduce_max_sync(0xffffffffu, __float_as_uint(n.y));
      const uint32_t vm = __reduce_max_sync(0xffffffffu, __float_as_uint(n.z));
      const float b2 = __uint_as_float(qm) * (QSCALE * QSCALE) * __uint_as_float(km) * 1.02f;
      const float vmax = __uint_as_float(vm);
      const bool ok = (b2 <= 21.5f * 21.5f) && (vmax <= 1.0e24f) && (vmax >= 1.0e-18f || vmax == 0.f);
      safe_path = !ok;
    }
    const int tile64 = qb * 8 + wg * 2 + t;
    const uint4 qf = qnext;
    if (t == 0) qnext = g_qfrag[(head * 32 + tile64 + 1) * 128 + (threadIdx.x & 127)];
    uint32_t r[4];
    if (threadIdx.x == 0 && t >= 0) PROF_T(1, 1 + t);
    if (!safe_path) attn_tile<false>(dK, dV, bar, qf, ec, r, t < 0);
    else attn_tile<true>(dK, dV, bar, qf, ec, r, false);
    if (t >= 0) store_o(g_o + (size_t)S_LEN * DM, tile64 * 64 + warp * 16, head, lane, r);
  }
  if (threadIdx.x == 0) { PROF_T(1, 5); PROF_G(1, 31); }
}

#define K3_WPRE 2
constexpr int K3_STAGES = 5;
constexpr int K3_W_BYTES = 8 * 16384;
constexpr int K3_BAR_OFF = K3_W_BYTES + K3_STAGES * 16384;
constexpr int K3_SMEM = K3_BAR_OFF + 256 + 1024;

__global__ void __launch_bounds__(288, 1)
out_gemm_kernel(const __grid_constant__ CUtensorMap mo, const __grid_constant__ CUtensorMap mwA,
                const __grid_constant__ CUtensorMap mwB, const __grid_constant__ CUtensorMap mout) {
  extern __shared__ uint8_t smem_raw[];
  const uint32_t sbase = (smem_u32(smem_raw) + 1023) & ~1023u;
  const uint32_t bar_full = sbase + K3_BAR_OFF;
  const uint32_t bar_empty = bar_full + 8 * K3_STAGES;
  const uint32_t bar_w = bar_empty + 8 * K3_STAGES;
  const int branch = blockIdx.x >> 6;
  const int rt = (blockIdx.x & 63) >> 2;
  const int ct = blockIdx.x & 3;
  const int warp = threadIdx.x >> 5;
  if (threadIdx.x == 0) { PROF_G(2, 30); PROF_T(2, 0); }
  if (threadIdx.x == 256) {
    const CUtensorMap* mw = branch ? &mwB : &mwA;
    asm volatile("prefetch.tensormap [%0];" ::"l"(mw) : "memory");
    asm volatile("prefetch.tensormap [%0];" ::"l"(&mo) : "memory");
    asm volatile("prefetch.tensormap [%0];" ::"l"(&mout) : "memory");
    for (int i = 0; i < K3_STAGES; i++) {
      mbar_init(bar_full + 8 * i, 1);
      mbar_init(bar_empty + 8 * i, 2);
    }
    for (int i = 0; i < 8; i++) mbar_init(bar_w + 8 * i, 1);
    fence_barrier_init();
    fence_proxy_async();
    for (int kb = 0; kb < K3_WPRE; kb++) {
      mbar_expect_tx(bar_w + 8 * kb, 16384);
      tma_load_2d(sbase + kb * 16384, mw, ct * 128, kb * 64, bar_w + 8 * kb);
      tma_load_2d(sbase + kb * 16384 + 8192, mw, ct * 128 + 64, kb * 64, bar_w + 8 * kb);
    }
  }
  __syncthreads();
  if (warp == 8) {
    if ((threadIdx.x & 31) == 0) {
      const CUtensorMap* mw = branch ? &mwB : &mwA;
      pdl_wait();
      PROF_T(2, 1);
      for (int kb = 0; kb < 8; kb++) {
        const int s = kb % K3_STAGES;
        if (kb >= K3_STAGES) mbar_wait(bar_empty + 8 * s, ((kb / K3_STAGES) - 1) & 1);
        mbar_expect_tx(bar_full + 8 * s, 16384);
        tma_load_2d(sbase + K3_W_BYTES + s * 16384, &mo, kb * 64, branch * S_LEN + rt * 128, bar_full + 8 * s);
        const int kw = kb + K3_WPRE;
        if (kw < 8) {
          mbar_expect_tx(bar_w + 8 * kw, 16384);
          tma_load_2d(sbase + kw * 16384, mw, ct * 128, kw * 64, bar_w + 8 * kw);
          tma_load_2d(sbase + kw * 16384 + 8192, mw, ct * 128 + 64, kw * 64, bar_w + 8 * kw);
        }
      }
    }
  } else {
    const int wg = warp >> 2;
    float acc[64];
    for (int kb = 0; kb < 8; kb++) {
      const int s = kb % K3_STAGES;
      mbar_wait(bar_w + 8 * kb, 0);
      mbar_wait(bar_full + 8 * s, (kb / K3_STAGES) & 1);
      if (threadIdx.x == 0) PROF_T(2, 2 + kb);
      const uint64_t dA = mkdesc(sbase + K3_W_BYTES + s * 16384 + wg * 8192, 16, 1024, 1);
      const uint64_t dB = mkdesc(sbase + kb * 16384, 8192, 1024, 1);
      wg_fence();
#pragma unroll
      for (int k = 0; k < 4; k++) wgmma_ss_n128_tb(acc, dA + k * 2, dB + k * 128, (kb | k) != 0);
      wg_commit();
      if (kb > 0) {
        wg_wait<1>();
        if ((threadIdx.x & 127) == 0) mbar_arrive(bar_empty + 8 * ((kb - 1) % K3_STAGES));
      }
    }
    wg_wait<0>();
    fence_regs(acc);
    if (threadIdx.x == 0) PROF_T(2, 10);
    const uint32_t stg = sbase + K3_W_BYTES + wg * 8192;
    const int lane = threadIdx.x & 31;
    const int rloc = (warp & 3) * 16 + (lane & 15);
#pragma unroll
    for (int c16 = 0; c16 < 8; c16++) {
      const float* a = &acc[c16 * 8];
      const uint32_t r0 = pack_bf16(a[0], a[1]), r1 = pack_bf16(a[2], a[3]), r2 = pack_bf16(a[4], a[5]), r3 = pack_bf16(a[6], a[7]);
      const int chunk = (c16 & 3) * 2 + (lane >> 4);
      const uint32_t addr = stg + (c16 >> 2) * 16384 + rloc * 128 + ((chunk ^ (rloc & 7)) << 4);
      asm volatile("stmatrix.sync.aligned.m8n8.x4.shared.b16 [%0], {%1,%2,%3,%4};" ::"r"(addr), "r"(r0), "r"(r1), "r"(r2), "r"(r3)
                   : "memory");
    }
    fence_proxy_async();
    asm volatile("bar.sync %0, 128;" ::"r"(2 + wg) : "memory");
    if ((threadIdx.x & 127) == 0) {
      tma_store_2d(&mout, stg, branch * DM + ct * 128, rt * 128 + wg * 64);
      tma_store_2d(&mout, stg + 16384, branch * DM + ct * 128 + 64, rt * 128 + wg * 64);
      asm volatile("cp.async.bulk.commit_group;" ::: "memory");
      asm volatile("cp.async.bulk.wait_group.read 0;" ::: "memory");
      if (threadIdx.x == 0) { PROF_T(2, 12); PROF_G(2, 31); }
    }
  }
}

typedef CUresult (*EncodeFn)(CUtensorMap*, CUtensorMapDataType, cuuint32_t, void*, const cuuint64_t*, const cuuint64_t*,
                             const cuuint32_t*, const cuuint32_t*, CUtensorMapInterleave, CUtensorMapSwizzle,
                             CUtensorMapL2promotion, CUtensorMapFloatOOBfill);

void make_map(EncodeFn enc, CUtensorMap* m, const void* ptr, uint64_t inner, uint64_t outer, uint32_t box_inner, uint32_t box_outer) {
  cuuint64_t dims[2] = {inner, outer};
  cuuint64_t strides[1] = {inner * 2};
  cuuint32_t box[2] = {box_inner, box_outer};
  cuuint32_t es[2] = {1, 1};
  enc(m, CU_TENSOR_MAP_DATA_TYPE_BFLOAT16, 2, const_cast<void*>(ptr), dims, strides, box, es, CU_TENSOR_MAP_INTERLEAVE_NONE,
      CU_TENSOR_MAP_SWIZZLE_128B, CU_TENSOR_MAP_L2_PROMOTION_L2_256B, CU_TENSOR_MAP_FLOAT_OOB_FILL_NONE);
}

struct HostState {
  bool init;
  const void* key[7];
  CUtensorMap mxA, mxB, mwA, mwB, mo, mo16, mwoA, mwoB, mout;
};
HostState g_hs;

}

extern "C" void kernel_launch(void* const* d_in, const int* in_sizes, int n_in, void* d_out, int out_size) {
  (void)in_sizes; (void)n_in; (void)out_size;
  HostState& hs = g_hs;
  bool same = hs.init && hs.key[6] == d_out;
  for (int i = 0; i < 6 && same; i++) same = hs.key[i] == d_in[i];
  if (!same) {
    void* fn = nullptr;
    cudaDriverEntryPointQueryResult qr;
    cudaGetDriverEntryPoint("cuTensorMapEncodeTiled", &fn, cudaEnableDefault, &qr);
    EncodeFn enc = (EncodeFn)fn;
    void* go = nullptr;
    cudaGetSymbolAddress(&go, g_o);
    make_map(enc, &hs.mxA, d_in[0], 512, 2048, 64, 128);
    make_map(enc, &hs.mwA, d_in[1], 1536, 512, 64, 32);
    make_map(enc, &hs.mwoA, d_in[2], 512, 512, 64, 64);
    make_map(enc, &hs.mxB, d_in[3], 512, 2048, 64, 128);
    make_map(enc, &hs.mwB, d_in[4], 1536, 512, 64, 32);
    make_map(enc, &hs.mwoB, d_in[5], 512, 512, 64, 64);
    make_map(enc, &hs.mo, go, 512, 4096, 64, 128);
    make_map(enc, &hs.mo16, go, 512, 4096, 64, 16);
    make_map(enc, &hs.mout, d_out, 1024, 2048, 64, 64);
    cudaFuncSetAttribute(qkv_gemm_kernel, cudaFuncAttributeMaxDynamicSharedMemorySize, K1_SMEM);
    cudaFuncSetAttribute(attn_kernel, cudaFuncAttributeMaxDynamicSharedMemorySize, K2_SMEM);
    cudaFuncSetAttribute(out_gemm_kernel, cudaFuncAttributeMaxDynamicSharedMemorySize, K3_SMEM);
    for (int i = 0; i < 6; i++) hs.key[i] = d_in[i];
    hs.key[6] = d_out;
    hs.init = true;
  }
  cudaStream_t st = cudaStreamPerThread;
  {
    cudaLaunchConfig_t cfg = {};
    cfg.gridDim = dim3(128);
    cfg.blockDim = dim3(384);
    cfg.dynamicSmemBytes = K1_SMEM;
    cfg.stream = st;
    cudaLaunchAttribute at[1];
    at[0].id = cudaLaunchAttributeClusterDimension;
    at[0].val.clusterDim.x = 2;
    at[0].val.clusterDim.y = 1;
    at[0].val.clusterDim.z = 1;
    cfg.attrs = at;
    cfg.numAttrs = 1;
    cudaLaunchKernelEx(&cfg, qkv_gemm_kernel, hs.mxA, hs.mxB, hs.mwA, hs.mwB);
  }
  {
    cudaLaunchConfig_t cfg = {};
    cfg.gridDim = dim3(132);
    cfg.blockDim = dim3(512);
    cfg.dynamicSmemBytes = K2_SMEM;
    cfg.stream = st;
    cudaLaunchAttribute at[1];
    at[0].id = cudaLaunchAttributeProgrammaticStreamSerialization;
    at[0].val.programmaticStreamSerializationAllowed = 1;
    cfg.attrs = at;
    cfg.numAttrs = 1;
    cudaLaunchKernelEx(&cfg, attn_kernel, hs.mo16, (const uint8_t*)d_in[2], (const uint8_t*)d_in[5]);
    cfg.gridDim = dim3(128);
    cfg.blockDim = dim3(288);
    cfg.dynamicSmemBytes = K3_SMEM;
    cudaLaunchKernelEx(&cfg, out_gemm_kernel, hs.mo, hs.mwoA, hs.mwoB, hs.mout);
  }
}
```

```cpp
#include <cuda_runtime.h>
#include <cuda_bf16.h>
#include <cuda.h>
#include <stdint.h>

namespace {

constexpr int S_LEN = 2048;
constexpr int DM = 512;
constexpr int NH = 32;

constexpr int KV_K_BYTES = 65536;
constexpr int KV_HEAD_BYTES = KV_K_BYTES + 98304;
__device__ uint4 g_qfrag[2 * NH * 32 * 128];
__device__ uint4 g_kv[NH * KV_HEAD_BYTES / 16];
__device__ float g_kvpart[16 * NH * 384];
__device__ float g_nrm[NH * 16 * 4];
__device__ uint32_t g_sync[8];
__device__ __nv_bfloat16 g_o[2 * S_LEN * DM];

#define g_prof_set(k, i, v)
#define g_prof_dummy(i) true
#define PROF_T(k, i) do {} while (0)
#define PROF_G(k, i) do {} while (0)
__device__ __forceinline__ uint32_t smem_u32(const void* p) { return (uint32_t)__cvta_generic_to_shared(p); }
__device__ __forceinline__ void mbar_init(uint32_t bar, int cnt) {
  asm volatile("mbarrier.init.shared::cta.b64 [%0], %1;" ::"r"(bar), "r"(cnt) : "memory");
}
__device__ __forceinline__ void mbar_expect_tx(uint32_t bar, uint32_t bytes) {
  asm volatile("mbarrier.arrive.expect_tx.shared::cta.b64 _, [%0], %1;" ::"r"(bar), "r"(bytes) : "memory");
}
__device__ __forceinline__ void mbar_arrive(uint32_t bar) {
  asm volatile("mbarrier.arrive.shared::cta.b64 _, [%0];" ::"r"(bar) : "memory");
}
__device__ __forceinline__ void mbar_arrive_cluster(uint32_t bar, uint32_t cta) {
  asm volatile(
      "{\n.reg .b32 ra;\nmapa.shared::cluster.u32 ra, %0, %1;\n"
      "mbarrier.arrive.shared::cluster.b64 _, [ra];\n}" ::"r"(bar), "r"(cta) : "memory");
}
__device__ __forceinline__ void mbar_wait(uint32_t bar, uint32_t parity) {
  asm volatile(
      "{\n.reg .pred p;\n.reg .u32 n;\n"
      "mov.u32 n, 0;\n"
      "WAIT_LOOP:\n"
      "mbarrier.try_wait.parity.shared::cta.b64 p, [%0], %1, 0x400000;\n"
      "@p bra WAIT_DONE;\n"
      "add.u32 n, n, 1;\n"
      "setp.lt.u32 p, n, 4000000;\n"
      "@p bra WAIT_LOOP;\n"
      "trap;\n"
      "WAIT_DONE:\n}" ::"r"(bar), "r"(parity) : "memory");
}
__device__ __forceinline__ void fence_barrier_init() {
  asm volatile("fence.mbarrier_init.release.cluster;" ::: "memory");
}
__device__ __forceinline__ void fence_proxy_async() { asm volatile("fence.proxy.async.shared::cta;" ::: "memory"); }
__device__ __forceinline__ void cluster_sync_relaxed() {
  asm volatile("barrier.cluster.arrive.relaxed.aligned;\nbarrier.cluster.wait.aligned;" ::: "memory");
}
__device__ __forceinline__ void tma_load_2d(uint32_t dst, const CUtensorMap* m, int x, int y, uint32_t bar) {
  asm volatile(
      "cp.async.bulk.tensor.2d.shared::cluster.global.mbarrier::complete_tx::bytes [%0], [%1, {%3, %4}], [%2];" ::"r"(dst),
      "l"(m), "r"(bar), "r"(x), "r"(y)
      : "memory");
}
__device__ __forceinline__ void tma_load_2d_mc(uint32_t dst, const CUtensorMap* m, int x, int y, uint32_t bar, uint16_t mask) {
  asm volatile(
      "cp.async.bulk.tensor.2d.shared::cluster.global.mbarrier::complete_tx::bytes.multicast::cluster [%0], [%1, {%3, %4}], "
      "[%2], %5;" ::"r"(dst),
      "l"(m), "r"(bar), "r"(x), "r"(y), "h"(mask)
      : "memory");
}
__device__ __forceinline__ void tma_store_2d(const CUtensorMap* m, uint32_t src, int x, int y) {
  asm volatile("cp.async.bulk.tensor.2d.global.shared::cta.bulk_group [%0, {%2, %3}], [%1];" ::"l"(m), "r"(src), "r"(x),
               "r"(y)
               : "memory");
}
__device__ __forceinline__ void bulk_load(uint32_t dst, const void* src, uint32_t bytes, uint32_t bar) {
  asm volatile("cp.async.bulk.shared::cluster.global.mbarrier::complete_tx::bytes [%0], [%1], %2, [%3];" ::"r"(dst),
               "l"(src), "r"(bytes), "r"(bar)
               : "memory");
}
__device__ __forceinline__ void bulk_load_mc(uint32_t dst, const void* src, uint32_t bytes, uint32_t bar, uint16_t mask) {
  asm volatile("cp.async.bulk.shared::cluster.global.mbarrier::complete_tx::bytes.multicast::cluster [%0], [%1], %2, [%3], %4;" ::"r"(dst),
               "l"(src), "r"(bytes), "r"(bar), "h"(mask)
               : "memory");
}
__device__ __forceinline__ void flag_arrive(uint32_t* p) {
  asm volatile("red.release.gpu.global.add.u32 [%0], 1;" ::"l"(p) : "memory");
}
__device__ __forceinline__ void flag_wait(const uint32_t* p, uint32_t target) {
  asm volatile(
      "{\n.reg .pred p;\n.reg .u32 n, v;\n"
      "mov.u32 n, 0;\n"
      "FLAG_LOOP:\n"
      "ld.acquire.gpu.global.u32 v, [%0];\n"
      "setp.ge.u32 p, v, %1;\n"
      "@p bra FLAG_DONE;\n"
      "add.u32 n, n, 1;\n"
      "setp.lt.u32 p, n, 20000000;\n"
      "@p bra FLAG_LOOP;\n"
      "trap;\n"
      "FLAG_DONE:\n}" ::"l"(p), "r"(target) : "memory");
}
__device__ __forceinline__ void fence_proxy_async_all() { asm volatile("fence.proxy.async;" ::: "memory"); }
__device__ __forceinline__ void pdl_launch_dependents() { asm volatile("griddepcontrol.launch_dependents;" ::: "memory"); }
__device__ __forceinline__ void pdl_wait() { asm volatile("griddepcontrol.wait;" ::: "memory"); }
__device__ __forceinline__ void wg_fence() { asm volatile("wgmma.fence.sync.aligned;" ::: "memory"); }
__device__ __forceinline__ void wg_commit() { asm volatile("wgmma.commit_group.sync.aligned;" ::: "memory"); }
template <int N>
__device__ __forceinline__ void wg_wait() {
  asm volatile("wgmma.wait_group.sync.aligned %0;" ::"n"(N) : "memory");
}
template <int M>
__device__ __forceinline__ void fence_regs(float (&r)[M]) {
#pragma unroll
  for (int i = 0; i < M; i++) asm volatile("" : "+f"(r[i])::"memory");
}
__device__ __forceinline__ uint64_t mkdesc(uint32_t addr, uint32_t lbo, uint32_t sbo, uint32_t layout) {
  return (uint64_t)((addr & 0x3FFFF) >> 4) | ((uint64_t)(lbo >> 4) << 16) | ((uint64_t)(sbo >> 4) << 32) |
         ((uint64_t)layout << 62);
}
__device__ __forceinline__ uint32_t pack_bf16(float lo, float hi) {
  uint32_t r;
  asm("cvt.rn.bf16x2.f32 %0, %1, %2;" : "=r"(r) : "f"(hi), "f"(lo));
  return r;
}
__device__ __forceinline__ float bf_lo(uint32_t v) { return __uint_as_float(v << 16); }
__device__ __forceinline__ float bf_hi(uint32_t v) { return __uint_as_float(v & 0xFFFF0000u); }
__device__ __forceinline__ float round_bf16(float x) { return bf_lo(pack_bf16(x, 0.f)); }
__device__ __forceinline__ float ex2f(float x) {
  float y;
  asm("ex2.approx.ftz.f32 %0, %1;" : "=f"(y) : "f"(x));
  return y;
}

__device__ __forceinline__ void wgmma_rs_n24_tb(float (&d)[12], uint32_t a0, uint32_t a1, uint32_t a2, uint32_t a3, uint64_t descB, int scaleD) {
  asm volatile("{\n.reg .pred p;\nsetp.ne.b32 p, %17, 0;\n"
    "wgmma.mma_async.sync.aligned.m64n24k16.f32.bf16.bf16 "
    "{%0, %1, %2, %3, %4, %5, %6, %7, %8, %9, %10, %11}, {%12, %13, %14, %15}, %16, p, 1, 1, 1;\n}\n"
    : "+f"(d[0]), "+f"(d[1]), "+f"(d[2]), "+f"(d[3]), "+f"(d[4]), "+f"(d[5]), "+f"(d[6]), "+f"(d[7]),
      "+f"(d[8]), "+f"(d[9]), "+f"(d[10]), "+f"(d[11])
    : "r"(a0), "r"(a1), "r"(a2), "r"(a3), "l"(descB), "r"(scaleD));
}
__device__ __forceinline__ void wgmma_rs_n64_z(float (&d)[32], uint32_t a0, uint32_t a1, uint32_t a2, uint32_t a3, uint64_t descB) {
  asm volatile("{\n.reg .pred p;\nsetp.ne.b32 p, %37, 0;\n"
    "wgmma.mma_async.sync.aligned.m64n64k16.f32.bf16.bf16 "
    "{%0, %1, %2, %3, %4, %5, %6, %7, %8, %9, %10, %11, %12, %13, %14, %15, %16, %17, %18, %19, %20, %21, %22, %23, %24, %25, %26, %27, %28, %29, %30, %31}, {%32, %33, %34, %35}, %36, p, 1, 1, 0;\n}\n"
    : "=f"(d[0]), "=f"(d[1]), "=f"(d[2]), "=f"(d[3]), "=f"(d[4]), "=f"(d[5]), "=f"(d[6]), "=f"(d[7]),
      "=f"(d[8]), "=f"(d[9]), "=f"(d[10]), "=f"(d[11]), "=f"(d[12]), "=f"(d[13]), "=f"(d[14]), "=f"(d[15]),
      "=f"(d[16]), "=f"(d[17]), "=f"(d[18]), "=f"(d[19]), "=f"(d[20]), "=f"(d[21]), "=f"(d[22]), "=f"(d[23]),
      "=f"(d[24]), "=f"(d[25]), "=f"(d[26]), "=f"(d[27]), "=f"(d[28]), "=f"(d[29]), "=f"(d[30]), "=f"(d[31])
    : "r"(a0), "r"(a1), "r"(a2), "r"(a3), "l"(descB), "n"(0));
}
__device__ __forceinline__ void wgmma_ss_n192_tb(float (&d)[96], uint64_t descA, uint64_t descB, int scaleD) {
  asm volatile("{\n.reg .pred p;\nsetp.ne.b32 p, %98, 0;\n"
    "wgmma.mma_async.sync.aligned.m64n192k16.f32.bf16.bf16 "
    "{%0, %1, %2, %3, %4, %5, %6, %7, %8, %9, %10, %11, %12, %13, %14, %15, %16, %17, %18, %19, %20, %21, %22, %23, %24, %25, %26, %27, %28, %29, %30, %31, %32, %33, %34, %35, %36, %37, %38, %39, %40, %41, %42, %43, %44, %45, %46, %47, %48, %49, %50, %51, %52, %53, %54, %55, %56, %57, %58, %59, %60, %61, %62, %63, %64, %65, %66, %67, %68, %69, %70, %71, %72, %73, %74, %75, %76, %77, %78, %79, %80, %81, %82, %83, %84, %85, %86, %87, %88, %89, %90, %91, %92, %93, %94, %95}, %96, %97, p, 1, 1, 0, 1;\n}\n"
    : "+f"(d[0]), "+f"(d[1]), "+f"(d[2]), "+f"(d[3]), "+f"(d[4]), "+f"(d[5]), "+f"(d[6]), "+f"(d[7]),
      "+f"(d[8]), "+f"(d[9]), "+f"(d[10]), "+f"(d[11]), "+f"(d[12]), "+f"(d[13]), "+f"(d[14]), "+f"(d[15]),
      "+f"(d[16]), "+f"(d[17]), "+f"(d[18]), "+f"(d[19]), "+f"(d[20]), "+f"(d[21]), "+f"(d[22]), "+f"(d[23]),
      "+f"(d[24]), "+f"(d[25]), "+f"(d[26]), "+f"(d[27]), "+f"(d[28]), "+f"(d[29]), "+f"(d[30]), "+f"(d[31]),
      "+f"(d[32]), "+f"(d[33]), "+f"(d[34]), "+f"(d[35]), "+f"(d[36]), "+f"(d[37]), "+f"(d[38]), "+f"(d[39]),
      "+f"(d[40]), "+f"(d[41]), "+f"(d[42]), "+f"(d[43]), "+f"(d[44]), "+f"(d[45]), "+f"(d[46]), "+f"(d[47]),
      "+f"(d[48]), "+f"(d[49]), "+f"(d[50]), "+f"(d[51]), "+f"(d[52]), "+f"(d[53]), "+f"(d[54]), "+f"(d[55]),
      "+f"(d[56]), "+f"(d[57]), "+f"(d[58]), "+f"(d[59]), "+f"(d[60]), "+f"(d[61]), "+f"(d[62]), "+f"(d[63]),
      "+f"(d[64]), "+f"(d[65]), "+f"(d[66]), "+f"(d[67]), "+f"(d[68]), "+f"(d[69]), "+f"(d[70]), "+f"(d[71]),
      "+f"(d[72]), "+f"(d[73]), "+f"(d[74]), "+f"(d[75]), "+f"(d[76]), "+f"(d[77]), "+f"(d[78]), "+f"(d[79]),
      "+f"(d[80]), "+f"(d[81]), "+f"(d[82]), "+f"(d[83]), "+f"(d[84]), "+f"(d[85]), "+f"(d[86]), "+f"(d[87]),
      "+f"(d[88]), "+f"(d[89]), "+f"(d[90]), "+f"(d[91]), "+f"(d[92]), "+f"(d[93]), "+f"(d[94]), "+f"(d[95])
    : "l"(descA), "l"(descB), "r"(scaleD));
}
__device__ __forceinline__ void wgmma_ss_n64_tb(float (&d)[32], uint64_t descA, uint64_t descB, int scaleD) {
  asm volatile("{\n.reg .pred p;\nsetp.ne.b32 p, %34, 0;\n"
    "wgmma.mma_async.sync.aligned.m64n64k16.f32.bf16.bf16 "
    "{%0, %1, %2, %3, %4, %5, %6, %7, %8, %9, %10, %11, %12, %13, %14, %15, %16, %17, %18, %19, %20, %21, %22, %23, %24, %25, %26, %27, %28, %29, %30, %31}, %32, %33, p, 1, 1, 0, 1;\n}\n"
    : "+f"(d[0]), "+f"(d[1]), "+f"(d[2]), "+f"(d[3]), "+f"(d[4]), "+f"(d[5]), "+f"(d[6]), "+f"(d[7]),
      "+f"(d[8]), "+f"(d[9]), "+f"(d[10]), "+f"(d[11]), "+f"(d[12]), "+f"(d[13]), "+f"(d[14]), "+f"(d[15]),
      "+f"(d[16]), "+f"(d[17]), "+f"(d[18]), "+f"(d[19]), "+f"(d[20]), "+f"(d[21]), "+f"(d[22]), "+f"(d[23]),
      "+f"(d[24]), "+f"(d[25]), "+f"(d[26]), "+f"(d[27]), "+f"(d[28]), "+f"(d[29]), "+f"(d[30]), "+f"(d[31])
    : "l"(descA), "l"(descB), "r"(scaleD));
}

__device__ __forceinline__ void ldsm4t(uint32_t (&b)[4], uint32_t addr) {
  asm volatile("ldmatrix.sync.aligned.m8n8.x4.trans.shared.b16 {%0,%1,%2,%3}, [%4];"
               : "=r"(b[0]), "=r"(b[1]), "=r"(b[2]), "=r"(b[3])
               : "r"(addr));
}
__device__ __forceinline__ void hmma(float (&c)[4], uint32_t a0, uint32_t a1, uint32_t a2, uint32_t a3, uint32_t b0, uint32_t b1) {
  asm("mma.sync.aligned.m16n8k16.row.col.f32.bf16.bf16.f32 {%0,%1,%2,%3}, {%4,%5,%6,%7}, {%8,%9}, {%0,%1,%2,%3};"
      : "+f"(c[0]), "+f"(c[1]), "+f"(c[2]), "+f"(c[3])
      : "r"(a0), "r"(a1), "r"(a2), "r"(a3), "r"(b0), "r"(b1));
}

__device__ __forceinline__ uint32_t movm(uint32_t a) {
  uint32_t d;
  asm volatile("movmatrix.sync.aligned.m8n8.trans.b16 %0, %1;" : "=r"(d) : "r"(a));
  return d;
}

#define K1_WARM 0
constexpr int K1_STAGES = 4;
constexpr int K1_W_BYTES = 3 * 8192;
constexpr int K1_X_BYTES = 8 * 16384;
constexpr int K1_BAR_OFF = K1_X_BYTES + K1_STAGES * K1_W_BYTES;
constexpr int K1_SMEM = K1_BAR_OFF + 192 + 1024;
constexpr float QSCALE = 0.25f * 1.4426950408889634f;

__device__ __forceinline__ uint32_t phi2(uint32_t t2) {
  uint32_t a2, mask, r2, o2;
  asm("add.rn.bf16x2 %0, %1, %2;" : "=r"(a2) : "r"(t2), "r"(0x3F803F80u));
  const uint32_t e2 = pack_bf16(ex2f(bf_lo(t2) * 1.4426950408889634f), ex2f(bf_hi(t2) * 1.4426950408889634f));
  asm("set.gt.u32.bf16x2 %0, %1, %2;" : "=r"(mask) : "r"(t2), "r"(0u));
  r2 = (a2 & mask) | (e2 & ~mask);
  asm("add.rn.bf16x2 %0, %1, %2;" : "=r"(o2) : "r"(r2), "r"(0x35863586u));
  return o2;
}

#define K1_SLOT_KB(h) ((h) < 4 ? 2 * (h) : 2 * ((h) - 4) + 1)
struct EpiCtx {
  uint4* qf;
  uint32_t* kp;
  uint32_t* vp;
  uint32_t* s_red;
  float* red;
  int lane;
};

template <bool LINEAR, int HH, int PART>
__device__ __forceinline__ void epi_slice(const float (&acc)[96], const EpiCtx& c, uint32_t (&pk)[4], float& vmax, bool live) {
  const float* a = &acc[HH * 8];
  const float* k = &acc[32 + HH * 8];
  const float* v = &acc[64 + HH * 8];
  if (!LINEAR) {
    if (PART == 0) {
      uint32_t* kh = c.kp + HH * (KV_HEAD_BYTES / 4);
      if (live) {
        c.qf[HH * 32 * 128] = make_uint4(pack_bf16(a[0] * QSCALE, a[1] * QSCALE), pack_bf16(a[2] * QSCALE, a[3] * QSCALE),
                                         pack_bf16(a[4] * QSCALE, a[5] * QSCALE), pack_bf16(a[6] * QSCALE, a[7] * QSCALE));
        kh[0] = pack_bf16(k[0], k[1]);
        kh[64] = pack_bf16(k[2], k[3]);
        kh[32] = pack_bf16(k[4], k[5]);
        kh[96] = pack_bf16(k[6], k[7]);
      }
      float q0 = a[0] * a[0] + a[1] * a[1] + a[4] * a[4] + a[5] * a[5];
      float q1 = a[2] * a[2] + a[3] * a[3] + a[6] * a[6] + a[7] * a[7];
      float k0 = k[0] * k[0] + k[1] * k[1] + k[4] * k[4] + k[5] * k[5];
      float k1 = k[2] * k[2] + k[3] * k[3] + k[6] * k[6] + k[7] * k[7];
#pragma unroll
      for (int o = 1; o <= 2; o <<= 1) {
        q0 += __shfl_xor_sync(0xffffffffu, q0, o);
        q1 += __shfl_xor_sync(0xffffffffu, q1, o);
        k0 += __shfl_xor_sync(0xffffffffu, k0, o);
        k1 += __shfl_xor_sync(0xffffffffu, k1, o);
      }
      const uint32_t qm = __reduce_max_sync(0xffffffffu, max(__float_as_uint(q0) & 0x7FFFFFFFu, __float_as_uint(q1) & 0x7FFFFFFFu));
      const uint32_t km = __reduce_max_sync(0xffffffffu, max(__float_as_uint(k0) & 0x7FFFFFFFu, __float_as_uint(k1) & 0x7FFFFFFFu));
      if (c.lane == 0 && live) {
        atomicMax(&c.s_red[HH * 2 + 0], qm);
        atomicMax(&c.s_red[HH * 2 + 1], km);
      }
    } else {
      uint32_t* vh = c.vp + HH * (KV_HEAD_BYTES / 4);
      if (live) {
        vh[0] = pack_bf16(v[0], v[1]);
        vh[96] = pack_bf16(v[2], v[3]);
        vh[32] = pack_bf16(v[4], v[5]);
        vh[128] = pack_bf16(v[6], v[7]);
        vh[64] = 0x3F803F80u;
        vh[160] = 0x3F803F80u;
      }
#pragma unroll
      for (int i = 0; i < 8; i++) asm("max.NaN.f32 %0, %0, %1;" : "+f"(vmax) : "f"(fabsf(v[i])));
    }
  } else {
    if (PART == 0) {
      const uint4 pq = make_uint4(phi2(pack_bf16(a[0], a[1])), phi2(pack_bf16(a[2], a[3])), phi2(pack_bf16(a[4], a[5])),
                                  phi2(pack_bf16(a[6], a[7])));
      if (live) c.qf[HH * 32 * 128] = pq;
      pk[0] = movm(phi2(pack_bf16(k[0], k[1])));
      pk[2] = movm(phi2(pack_bf16(k[2], k[3])));
      pk[1] = movm(phi2(pack_bf16(k[4], k[5])));
      pk[3] = movm(phi2(pack_bf16(k[6], k[7])));
    } else {
      const uint32_t b0 = movm(pack_bf16(v[0], v[1]));
      const uint32_t b1 = movm(pack_bf16(v[2], v[3]));
      const uint32_t b2 = movm(pack_bf16(v[4], v[5]));
      const uint32_t b3 = movm(pack_bf16(v[6], v[7]));
      float c0[4] = {0, 0, 0, 0}, c1[4] = {0, 0, 0, 0}, c2[4] = {0, 0, 0, 0};
      hmma(c0, pk[0], pk[1], pk[2], pk[3], b0, b1);
      hmma(c1, pk[0], pk[1], pk[2], pk[3], b2, b3);
      hmma(c2, pk[0], pk[1], pk[2], pk[3], 0x3F803F80u, 0x3F803F80u);
      float* slot = c.red + HH * 2 * 4096;
      if (live) {
#pragma unroll
        for (int i = 0; i < 4; i++) {
          slot[i * 32] = c0[i];
          slot[(4 + i) * 32] = c1[i];
          slot[(8 + i) * 32] = c2[i];
        }
      }
    }
  }
}

template <bool LINEAR>
__device__ __forceinline__ void qkv_consumer(uint32_t sbase, uint8_t* smem_gen, uint32_t* s_red, int cp, int rt) {
  const uint32_t bar_full = sbase + K1_BAR_OFF;
  const uint32_t bar_empty = bar_full + 8 * K1_STAGES;
  const int warp = threadIdx.x >> 5;
  const int wg = warp >> 2;
  const int lane = threadIdx.x & 31;
  float accN[96], accP[96];
  EpiCtx c;
  {
    const int row0 = rt * 128 + wg * 64 + (warp & 3) * 16;
    c.qf = g_qfrag + ((size_t)((LINEAR ? NH : 0) + cp * 8) * 32 + (rt * 2 + wg)) * 128 + (threadIdx.x & 127);
    uint32_t* img = reinterpret_cast<uint32_t*>(reinterpret_cast<uint8_t*>(g_kv) + (size_t)(cp * 8) * KV_HEAD_BYTES);
    c.kp = img + (row0 >> 3) * 64 + lane;
    c.vp = img + KV_K_BYTES / 4 + (row0 >> 3) * 96 + lane;
    c.s_red = s_red;
    c.red = reinterpret_cast<float*>(smem_gen + wg * 8192) + (warp & 3) * 384 + lane;
    c.lane = lane;
  }
  uint32_t pk[4] = {0, 0, 0, 0};
  float vmax = 0.f;
#pragma unroll
  for (int i = 0; i < 96; i++) asm volatile("mov.f32 %0, 0f00000000;" : "=f"(accN[i]));
  int npass;
  asm volatile("mov.u32 %0, 2;" : "=r"(npass));
#pragma unroll 1
  for (int pass = K1_WARM ? 0 : 1; pass < npass; pass++) {
    const bool live = K1_WARM ? pass != 0 : true;
    if (live) {
#pragma unroll 1
      for (int kb = 0; kb < 8; kb++) {
        const int s = kb % K1_STAGES;
        mbar_wait(bar_full + 8 * s, (kb / K1_STAGES) & 1);
        if (threadIdx.x == 0) PROF_T(0, 2 + (kb >> 1));
        const uint64_t dA = mkdesc(sbase + kb * 16384 + wg * 8192, 16, 1024, 1);
        const uint64_t dB = mkdesc(sbase + K1_X_BYTES + s * K1_W_BYTES, 8192, 1024, 1);
        wg_fence();
#pragma unroll
        for (int k = 0; k < 4; k++) wgmma_ss_n192_tb(accP, dA + k * 2, dB + k * 128, (kb | k) != 0);
        wg_commit();
        if (kb > 0) {
          wg_wait<1>();
          if ((threadIdx.x & 127) == 0) {
            const int sp = (kb - 1) % K1_STAGES;
            mbar_arrive_cluster(bar_empty + 8 * sp, 0);
            mbar_arrive_cluster(bar_empty + 8 * sp, 1);
          }
        }
      }
      wg_wait<0>();
      fence_regs(accP);
      if ((threadIdx.x & 127) == 0) {
        mbar_arrive_cluster(bar_empty + 8 * (7 % K1_STAGES), 0);
        mbar_arrive_cluster(bar_empty + 8 * (7 % K1_STAGES), 1);
      }
      if (threadIdx.x == 0) PROF_T(0, 6);
#define K1_T1_STEP(KB)                                                                           \
  {                                                                                              \
    constexpr int g = 8 + KB;                                                                    \
    constexpr int s = g % K1_STAGES;                                                             \
    mbar_wait(bar_full + 8 * s, (g / K1_STAGES) & 1);                                            \
    const uint64_t dA = mkdesc(sbase + KB * 16384 + wg * 8192, 16, 1024, 1);                     \
    const uint64_t dB = mkdesc(sbase + K1_X_BYTES + s * K1_W_BYTES, 8192, 1024, 1);              \
    wg_fence();                                                                                  \
    _Pragma("unroll") for (int k = 0; k < 4; k++) wgmma_ss_n192_tb(accN, dA + k * 2, dB + k * 128, (KB | k) != 0); \
    wg_commit();                                                                                 \
    epi_slice<LINEAR, KB / 2, KB & 1>(accP, c, pk, vmax, true);                                  \
    wg_wait<0>();                                                                                \
    if (KB + K1_STAGES < 8 && (threadIdx.x & 127) == 0) {                                        \
      mbar_arrive_cluster(bar_empty + 8 * s, 0);                                                 \
      mbar_arrive_cluster(bar_empty + 8 * s, 1);                                                 \
    }                                                                                            \
  }
      K1_T1_STEP(0) K1_T1_STEP(1) K1_T1_STEP(2) K1_T1_STEP(3) K1_T1_STEP(4) K1_T1_STEP(5) K1_T1_STEP(6) K1_T1_STEP(7)
#undef K1_T1_STEP
      fence_regs(accN);
      if (threadIdx.x == 0) PROF_T(0, 10);
      c.qf += 4 * 32 * 128;
      c.kp += 4 * (KV_HEAD_BYTES / 4);
      c.vp += 4 * (KV_HEAD_BYTES / 4);
      c.s_red += 8;
      c.red += 4096;
    }
    float vm1 = 0.f;
    epi_slice<LINEAR, 0, 0>(accN, c, pk, vm1, live);
    epi_slice<LINEAR, 0, 1>(accN, c, pk, vm1, live);
    epi_slice<LINEAR, 1, 0>(accN, c, pk, vm1, live);
    epi_slice<LINEAR, 1, 1>(accN, c, pk, vm1, live);
    epi_slice<LINEAR, 2, 0>(accN, c, pk, vm1, live);
    epi_slice<LINEAR, 2, 1>(accN, c, pk, vm1, live);
    epi_slice<LINEAR, 3, 0>(accN, c, pk, vm1, live);
    epi_slice<LINEAR, 3, 1>(accN, c, pk, vm1, live);
    if (live) asm("max.NaN.f32 %0, %0, %1;" : "+f"(vmax) : "f"(vm1));
  }
  if (!LINEAR) {
    const uint32_t vm = __reduce_max_sync(0xffffffffu, __float_as_uint(vmax) & 0x7FFFFFFFu);
    if (lane == 0) atomicMax(&s_red[16], vm);
    asm volatile("bar.sync 1, 256;" ::: "memory");
    if (threadIdx.x < 8) {
      *reinterpret_cast<float4*>(&g_nrm[((cp * 8 + threadIdx.x) * 16 + rt) * 4]) =
          make_float4(__uint_as_float(s_red[threadIdx.x * 2]), __uint_as_float(s_red[threadIdx.x * 2 + 1]), __uint_as_float(s_red[16]), 0.f);
    }
  } else {
    asm volatile("bar.sync 1, 256;" ::: "memory");
    float* dst = g_kvpart + ((size_t)rt * NH + cp * 8) * 384;
#pragma unroll
    for (int i = 0; i < 12; i++) {
      const int o = threadIdx.x + i * 256;
      const int h = o / 384, e = o - h * 384;
      const float* src = reinterpret_cast<const float*>(smem_gen) + K1_SLOT_KB(h) * 4096 + e;
      float sum = 0.f;
#pragma unroll
      for (int w = 0; w < 8; w++) sum += src[(w >> 2) * 2048 + (w & 3) * 384];
      dst[o] = sum;
    }
  }
}

__global__ void __launch_bounds__(384, 1)
qkv_gemm_kernel(const __grid_constant__ CUtensorMap mxA, const __grid_constant__ CUtensorMap mxB,
                const __grid_constant__ CUtensorMap mwA, const __grid_constant__ CUtensorMap mwB) {
  extern __shared__ uint8_t smem_raw[];
  const uint32_t sbase = (smem_u32(smem_raw) + 1023) & ~1023u;
  uint8_t* smem_gen = smem_raw + (sbase - smem_u32(smem_raw));
  const uint32_t bar_full = sbase + K1_BAR_OFF;
  const uint32_t bar_empty = bar_full + 8 * K1_STAGES;
  uint32_t* s_red = reinterpret_cast<uint32_t*>(smem_gen + K1_BAR_OFF + 64);

  const int rank = blockIdx.x & 1;
  const int pair = blockIdx.x >> 1;
  const int branch = pair >> 5;
  const int rp = (pair & 31) >> 2;
  const int cp = pair & 3;
  const int rt = rp * 2 + rank;
  const int warp = threadIdx.x >> 5;
  if (threadIdx.x == 0) { PROF_G(0, 30); PROF_T(0, 0); }
  const CUtensorMap* mx = branch ? &mxA : &mxB;
  const CUtensorMap* mw = branch ? &mwA : &mwB;

  if (threadIdx.x == 256) {
    asm volatile("prefetch.tensormap [%0];" ::"l"(mx) : "memory");
    asm volatile("prefetch.tensormap [%0];" ::"l"(mw) : "memory");
    for (int i = 0; i < K1_STAGES; i++) {
      mbar_init(bar_full + 8 * i, 1);
      mbar_init(bar_empty + 8 * i, 4);
    }
    fence_barrier_init();
    fence_proxy_async();
    for (int kb = 0; kb < K1_STAGES; kb++) mbar_expect_tx(bar_full + 8 * kb, 16384 + K1_W_BYTES);
    tma_load_2d(sbase, mx, 0, rt * 128, bar_full);
  }
  pdl_launch_dependents();
  if (threadIdx.x < 32) s_red[threadIdx.x] = 0;
  if (blockIdx.x == 0 && threadIdx.x < 8) g_sync[threadIdx.x] = 0;
  __syncthreads();
  cluster_sync_relaxed();
  if (threadIdx.x == 0) PROF_T(0, 1);

  if (warp >= 8) {
    asm volatile("setmaxnreg.dec.sync.aligned.u32 40;");
    if (threadIdx.x == 256) {
      for (int g = 0; g < 16; g++) {
        const int s = g % K1_STAGES;
        const int kb = g & 7;
        if (g >= K1_STAGES) {
          mbar_wait(bar_empty + 8 * s, ((g / K1_STAGES) - 1) & 1);
          mbar_expect_tx(bar_full + 8 * s, (g < 8 ? 16384 : 0) + K1_W_BYTES);
        }
        if (g > 0 && g < 8) tma_load_2d(sbase + kb * 16384, mx, kb * 64, rt * 128, bar_full + 8 * s);
        const int h0 = cp * 8 + (g >> 3) * 4;
        const uint32_t st = sbase + K1_X_BYTES + s * K1_W_BYTES + rank * 4096;
#pragma unroll
        for (int p = 0; p < 3; p++)
          tma_load_2d_mc(st + p * 8192, mw, p * 512 + h0 * 16, kb * 64 + rank * 32, bar_full + 8 * s, (uint16_t)3);
      }
    }
    __syncwarp();
    cluster_sync_relaxed();
  } else {
    asm volatile("setmaxnreg.inc.sync.aligned.u32 232;");
    if (branch == 0) qkv_consumer<false>(sbase, smem_gen, s_red, cp, rt);
    else qkv_consumer<true>(sbase, smem_gen, s_red, cp, rt);
    if (threadIdx.x == 0) PROF_T(0, 11);
    __syncwarp();
    cluster_sync_relaxed();
    if (threadIdx.x == 0) { PROF_T(0, 12); PROF_G(0, 31); }
  }
}

constexpr int T_WA0 = KV_HEAD_BYTES;
constexpr int T_S0 = T_WA0 + 32768;
constexpr int K2_BAR = T_S0 + 32768;
constexpr int T_WA1 = 0;
constexpr int T_WB = 32768;
constexpr int T_S2 = 98304;
constexpr int K2_SMEM = K2_BAR + 256 + 1024;

#define ATT_NPOLY 18
#define ATT_CH 8
#define ATT_D 1
#define PRO_MODE 1
#define STAGGER 0
#define K2_WARM 0
#define K2_FIRST 2
#define CONST_SMID 0
#define ATT_STRUCT 1
#define ATT_PIN 0
#define ATT_GM 1
#define ATT_DEG 2
struct ExpC {
  uint32_t k3c00, kmask, seven, c3;
};
__device__ __forceinline__ uint32_t hfma2(uint32_t a, uint32_t b, uint32_t c) {
  uint32_t r;
  asm("fma.rn.f16x2 %0, %1, %2, %3;" : "=r"(r) : "r"(a), "r"(b), "r"(c));
  return r;
}
__device__ __forceinline__ uint32_t exp2_poly_pair(float t0, float t1, const ExpC& c) {
  uint32_t u;
  asm("prmt.b32 %0, %1, %2, 0x5410;" : "=r"(u) : "r"(__float_as_uint(t0)), "r"(__float_as_uint(t1)));
  uint32_t m;
  asm("lop3.b32 %0, %1, 0x03FF03FF, %2, 0xEA;" : "=r"(m) : "r"(u), "r"(c.k3c00));
  uint32_t p = hfma2(m, c.c3, 0xa385a385u);
  p = hfma2(p, m, 0x4ad64ad7u);
  uint32_t mu;
  asm("lop3.b32 %0, %1, 0xFC00FC00, %2, 0xEA;" : "=r"(mu) : "r"(u), "r"(c.kmask));
  uint32_t r;
  asm("{.reg .b32 t; shf.r.wrap.b32 t, %1, %2, 3; add.u32 %0, t, %3;}" : "=r"(r) : "r"(mu), "r"(c.seven), "r"(p));
  return r;
}
__device__ __forceinline__ float gadd(float x, float M, uint32_t g) {
  float r = x;
  asm("{.reg .pred p; setp.ne.b32 p, %2, -1; @p add.f32 %0, %0, %1;}" : "+f"(r) : "f"(M), "r"(g));
  return r;
}
__device__ __forceinline__ float gex2(float x, uint32_t g) {
  float r = x;
  asm("{.reg .pred p; setp.ne.b32 p, %1, -1; @p ex2.approx.ftz.f32 %0, %0;}" : "+f"(r) : "r"(g));
  return r;
}
template <int NPOLY, int NPAIR, int CH, int D, bool G0 = false>
__device__ __forceinline__ void exp_tile(const float (&s)[2 * NPAIR], uint32_t (&p)[NPAIR], const ExpC& c, uint32_t g0 = 0) {
#pragma unroll
  for (int i = 0; i < NPAIR; i++) {
    const bool isPoly = ((i + 1) * NPOLY / 32) != (i * NPOLY / 32);
    const int ch = i / CH;
    const bool gated = ch >= D || G0;
    int gi = (ch - D) * CH + CH - 1;
    if (ch >= D) {
      while (gi > (ch - D) * CH && !(((gi + 1) * NPOLY / 32) != (gi * NPOLY / 32))) gi--;
    }
    const uint32_t g = ch >= D ? p[gi] : g0;
    if (!isPoly) {
      if (gated && ATT_GM) p[i] = pack_bf16(gex2(s[2 * i], g), gex2(s[2 * i + 1], g));
      else p[i] = pack_bf16(ex2f(s[2 * i]), ex2f(s[2 * i + 1]));
    } else {
      if (gated) p[i] = exp2_poly_pair(gadd(s[2 * i], 12329.f, g), gadd(s[2 * i + 1], 12329.f, g), c);
      else p[i] = exp2_poly_pair(s[2 * i] + 12329.f, s[2 * i + 1] + 12329.f, c);
    }
  }
}

__device__ __forceinline__ void store_o(__nv_bfloat16* o, int row0, int head, int lane, const uint32_t (&r)[4]) {
  const int g = lane >> 2, t = lane & 3;
  uint32_t* p0 = reinterpret_cast<uint32_t*>(o + (size_t)(row0 + g) * DM + head * 16) + t;
  uint32_t* p1 = reinterpret_cast<uint32_t*>(o + (size_t)(row0 + g + 8) * DM + head * 16) + t;
  p0[0] = r[0];
  p1[0] = r[1];
  p0[4] = r[2];
  p1[4] = r[3];
}

__device__ __forceinline__ void kv_fetch_piece(uint32_t sbase, uint32_t bar, int piece) {
  const uint8_t* img = reinterpret_cast<const uint8_t*>(g_kv) + (size_t)(blockIdx.x >> 2) * KV_HEAD_BYTES;
  const int g = piece >> 1, isv = piece & 1;
  const int e0 = g == 0 ? 0 : (isv ? 256 : 320) + (g - 1) * 512;
  const int e1 = g == 3 ? 2048 : (isv ? 256 : 320) + g * 512;
  const int bytes = (e1 - e0) * (isv ? 48 : 32);
  const int off = isv ? KV_K_BYTES + e0 * 48 : e0 * 32;
  mbar_expect_tx(bar + 8 * g, bytes);
  bulk_load(sbase + off, img + off, bytes, bar + 8 * g);
}

__device__ __forceinline__ void safe_exp(const float (&s)[32], uint32_t (&p)[16], float (&o)[12], float& m0, float& m1) {
  float x0 = s[0], x1 = s[2];
#pragma unroll
  for (int i = 0; i < 8; i++) {
    x0 = fmaxf(x0, fmaxf(s[4 * i], s[4 * i + 1]));
    x1 = fmaxf(x1, fmaxf(s[4 * i + 2], s[4 * i + 3]));
  }
  x0 = fmaxf(x0, __shfl_xor_sync(0xffffffffu, x0, 1));
  x1 = fmaxf(x1, __shfl_xor_sync(0xffffffffu, x1, 1));
  x0 = fmaxf(x0, __shfl_xor_sync(0xffffffffu, x0, 2));
  x1 = fmaxf(x1, __shfl_xor_sync(0xffffffffu, x1, 2));
  const float n0 = fmaxf(m0, x0), n1 = fmaxf(m1, x1);
  const float c0 = ex2f(m0 - n0), c1 = ex2f(m1 - n1);
  m0 = n0;
  m1 = n1;
#pragma unroll
  for (int i = 0; i < 3; i++) {
    o[4 * i] *= c0;
    o[4 * i + 1] *= c0;
    o[4 * i + 2] *= c1;
    o[4 * i + 3] *= c1;
  }
#pragma unroll
  for (int i = 0; i < 8; i++) {
    p[2 * i] = pack_bf16(ex2f(s[4 * i] - n0), ex2f(s[4 * i + 1] - n0));
    p[2 * i + 1] = pack_bf16(ex2f(s[4 * i + 2] - n1), ex2f(s[4 * i + 3] - n1));
  }
}

__device__ __forceinline__ void attn_step(float (&sx)[32], float (&sy)[32], float (&o)[12], const uint4& qf, uint64_t dK, uint64_t dV,
                                          const ExpC& ec) {
  uint32_t pa[16], pb[16];
  wg_fence();
  wgmma_rs_n64_z(sy, qf.x, qf.y, qf.z, qf.w, dK + 128);
  wg_commit();
  exp_tile<ATT_NPOLY, 16, ATT_CH, ATT_D>(sx, pa, ec);
  wg_fence();
  wgmma_rs_n24_tb(o, pa[12], pa[13], pa[14], pa[15], dV + 3 * 48, 1);
  wg_commit();
  wg_wait<1>();
  fence_regs(sy);
  exp_tile<ATT_NPOLY, 16, ATT_CH, ATT_D>(sy, pb, ec);
  wg_fence();
#pragma unroll
  for (int k = 0; k < 3; k++) wgmma_rs_n24_tb(o, pa[4 * k], pa[4 * k + 1], pa[4 * k + 2], pa[4 * k + 3], dV + k * 48, 1);
#pragma unroll
  for (int k = 0; k < 4; k++) wgmma_rs_n24_tb(o, pb[4 * k], pb[4 * k + 1], pb[4 * k + 2], pb[4 * k + 3], dV + (4 + k) * 48, 1);
  wgmma_rs_n64_z(sy, qf.x, qf.y, qf.z, qf.w, dK + 256);
  wg_commit();
  wg_wait<0>();
  fence_regs(sy);
}

template <bool SAFE>
__device__ __forceinline__ void attn_tile(uint64_t dK, uint64_t dV, uint32_t bar, const uint4 qf, const ExpC& ec, uint32_t (&outp)[4],
                                          bool warm) {
  float o[12];
#pragma unroll
  for (int i = 0; i < 12; i++) asm volatile("mov.f32 %0, 0f00000000;" : "=f"(o[i]));
  if (!warm) mbar_wait(bar, 0);
  if (!SAFE) {
    float s0[32], s1[32];
    wg_fence();
    wgmma_rs_n64_z(s0, qf.x, qf.y, qf.z, qf.w, dK);
    wg_commit();
    wg_wait<0>();
    fence_regs(s0);
#pragma unroll 1
    for (int p = warm ? 7 : 0; p < 8; p++) {
      if ((p & 1) && !warm) mbar_wait(bar + 8 * min((p + 1) >> 1, 3), 0);
      attn_step(s0, s1, o, qf, dK, dV, ec);
      attn_step(s1, s0, o, qf, dK + 256, dV + 384, ec);
      dK += 512;
      dV += 768;
    }
  } else {
    float m0 = -INFINITY, m1 = -INFINITY;
#pragma unroll 1
    for (int j = 0; j < 32; j++) {
      if (j == 4) { mbar_wait(bar + 8, 0); mbar_wait(bar + 16, 0); mbar_wait(bar + 24, 0); }
      float s[32];
      uint32_t p[16];
      wg_fence();
      wgmma_rs_n64_z(s, qf.x, qf.y, qf.z, qf.w, dK);
      wg_commit();
      wg_wait<0>();
      fence_regs(s);
      safe_exp(s, p, o, m0, m1);
      wg_fence();
#pragma unroll
      for (int k = 0; k < 4; k++) wgmma_rs_n24_tb(o, p[4 * k], p[4 * k + 1], p[4 * k + 2], p[4 * k + 3], dV + k * 48, 1);
      wg_commit();
      wg_wait<0>();
      fence_regs(o);
      dK += 128;
      dV += 192;
    }
  }
  fence_regs(o);
  const float r0 = 1.0f / o[8], r1 = 1.0f / o[10];
  outp[0] = pack_bf16(o[0] * r0, o[1] * r0);
  outp[1] = pack_bf16(o[2] * r1, o[3] * r1);
  outp[2] = pack_bf16(o[4] * r0, o[5] * r0);
  outp[3] = pack_bf16(o[6] * r1, o[7] * r1);
}

__device__ __forceinline__ void linear_attn_cta(uint8_t* smem_raw, uint32_t sbase, const CUtensorMap* mo16, int cta) {
  const int warp = threadIdx.x >> 5, lane = threadIdx.x & 31;
  float* red = reinterpret_cast<float*>(smem_raw + (sbase - smem_u32(smem_raw)) + 131072);
  {
    const float* src = g_kvpart + (size_t)cta * 8 * 384;
    float sum[6];
#pragma unroll
    for (int i = 0; i < 6; i++) sum[i] = 0.f;
#pragma unroll
    for (int r = 0; r < 16; r++) {
#pragma unroll
      for (int i = 0; i < 6; i++) sum[i] += src[(size_t)r * NH * 384 + threadIdx.x + i * 512];
    }
#pragma unroll
    for (int i = 0; i < 6; i++) red[threadIdx.x + i * 512] = round_bf16(sum[i]);
  }
  __syncthreads();
  uint32_t bf[8][6];
  {
    const int g = lane >> 2, t = lane & 3;
#pragma unroll
    for (int h = 0; h < 8; h++) {
#pragma unroll
      for (int f = 0; f < 6; f++) {
        const int blk = f >> 1, half = f & 1;
        const int e = (blk == 2) ? 0 : g;
        const int d = 2 * t + 8 * half;
        const int base = h * 384 + (blk * 4 + half * 2 + (e & 1)) * 32 + (e >> 1);
        bf[h][f] = pack_bf16(red[base + (d & 7) * 4], red[base + ((d + 1) & 7) * 4]);
      }
    }
  }
  const uint32_t stg = sbase + warp * 8192;
#pragma unroll 1
  for (int rb = 0; rb < 8; rb++) {
    const int blk16 = rb * 16 + warp;
    const uint4* qp = g_qfrag + ((size_t)(NH + cta * 8) * 32 + (blk16 >> 2)) * 128 + (blk16 & 3) * 32 + lane;
    uint4 q[8];
#pragma unroll
    for (int h = 0; h < 8; h++) q[h] = qp[h * 32 * 128];
    const uint32_t buf = stg + (rb & 1) * 4096;
    if (rb >= 2) {
      if (lane == 0) asm volatile("cp.async.bulk.wait_group.read 1;" ::: "memory");
      __syncwarp();
    }
#pragma unroll
    for (int h = 0; h < 8; h++) {
      float n0[4] = {0, 0, 0, 0}, n1[4] = {0, 0, 0, 0}, dn[4] = {0, 0, 0, 0};
      hmma(n0, q[h].x, q[h].y, q[h].z, q[h].w, bf[h][0], bf[h][1]);
      hmma(n1, q[h].x, q[h].y, q[h].z, q[h].w, bf[h][2], bf[h][3]);
      hmma(dn, q[h].x, q[h].y, q[h].z, q[h].w, bf[h][4], bf[h][5]);
      const float d0 = round_bf16(round_bf16(dn[0]) + 1e-6f), d1 = round_bf16(round_bf16(dn[2]) + 1e-6f);
      const uint32_t r0 = pack_bf16(__fdividef(round_bf16(n0[0]), d0), __fdividef(round_bf16(n0[1]), d0));
      const uint32_t r1 = pack_bf16(__fdividef(round_bf16(n0[2]), d1), __fdividef(round_bf16(n0[3]), d1));
      const uint32_t r2 = pack_bf16(__fdividef(round_bf16(n1[0]), d0), __fdividef(round_bf16(n1[1]), d0));
      const uint32_t r3 = pack_bf16(__fdividef(round_bf16(n1[2]), d1), __fdividef(round_bf16(n1[3]), d1));
      const int row = lane & 15;
      const int chunk = (h & 3) * 2 + (lane >> 4);
      const uint32_t addr = buf + (h >> 2) * 2048 + row * 128 + ((chunk ^ (row & 7)) << 4);
      asm volatile("stmatrix.sync.aligned.m8n8.x4.shared.b16 [%0], {%1,%2,%3,%4};" ::"r"(addr), "r"(r0), "r"(r1), "r"(r2), "r"(r3)
                   : "memory");
    }
    fence_proxy_async();
    __syncwarp();
    if (lane == 0) {
      tma_store_2d(mo16, buf, cta * 128, blk16 * 16);
      tma_store_2d(mo16, buf + 2048, cta * 128 + 64, blk16 * 16);
      asm volatile("cp.async.bulk.commit_group;" ::: "memory");
    }
  }
  if (lane == 0) {
    asm volatile("cp.async.bulk.wait_group 0;" ::: "memory");
    fence_proxy_async_all();
    __threadfence();
  }
  __syncthreads();
  if (threadIdx.x == 0) flag_arrive(&g_sync[4]);
}

__device__ __forceinline__ uint32_t tail_stage(uint32_t sbase, int s) { return sbase + (s < 2 ? T_S0 + s * 16384 : T_S2 + (s - 2) * 16384); }

__device__ __forceinline__ void tail_consumer(uint32_t sbase, const CUtensorMap* mout, int rt, int ct) {
  const uint32_t tb = sbase + K2_BAR + 96;
  const int wg = threadIdx.x >> 7, warp = (threadIdx.x >> 5) & 3, lane = threadIdx.x & 31;
#pragma unroll 1
  for (int tile = 0; tile < 2; tile++) {
    float acc[32];
#pragma unroll 1
    for (int kb = 0; kb < 8; kb++) {
      const int g = tile * 8 + kb;
      const int s = g % 6;
      if (g == 0) mbar_wait(tb + 96, 0);
      if (g == 4) mbar_wait(tb + 104, 0);
      if (g == 8) mbar_wait(tb + 112, 0);
      mbar_wait(tb + 8 * s, (g / 6) & 1);
      if (threadIdx.x == 0) PROF_T(2, 1 + (g >> 1));
      const uint32_t wa = sbase + (tile ? T_WB + kb * 8192 : (kb < 4 ? T_WA0 + kb * 8192 : T_WA1 + (kb - 4) * 8192));
      const uint64_t dA = mkdesc(tail_stage(sbase, s) + wg * 8192, 16, 1024, 1);
      const uint64_t dB = mkdesc(wa, 8192, 1024, 1);
      wg_fence();
#pragma unroll
      for (int k = 0; k < 4; k++) wgmma_ss_n64_tb(acc, dA + k * 2, dB + k * 128, (kb | k) != 0);
      wg_commit();
      wg_wait<0>();
      if ((threadIdx.x & 127) == 0) mbar_arrive(tb + 48 + 8 * s);
    }
    fence_regs(acc);
    if (tile == 0) asm volatile("bar.sync 3, 256;" ::: "memory");
    const uint32_t stg = sbase + T_WA0 + tile * 16384 + wg * 8192;
    const int rloc = warp * 16 + (lane & 15);
#pragma unroll
    for (int c16 = 0; c16 < 4; c16++) {
      const float* a = &acc[c16 * 8];
      const uint32_t r0 = pack_bf16(a[0], a[1]), r1 = pack_bf16(a[2], a[3]), r2 = pack_bf16(a[4], a[5]), r3 = pack_bf16(a[6], a[7]);
      const int chunk = c16 * 2 + (lane >> 4);
      const uint32_t addr = stg + rloc * 128 + ((chunk ^ (rloc & 7)) << 4);
      asm volatile("stmatrix.sync.aligned.m8n8.x4.shared.b16 [%0], {%1,%2,%3,%4};" ::"r"(addr), "r"(r0), "r"(r1), "r"(r2), "r"(r3)
                   : "memory");
    }
    fence_proxy_async();
    asm volatile("bar.sync %0, 128;" ::"r"(4 + wg) : "memory");
    if ((threadIdx.x & 127) == 0) {
      tma_store_2d(mout, stg, tile * DM + ct * 64, rt * 128 + wg * 64);
      asm volatile("cp.async.bulk.commit_group;" ::: "memory");
    }
  }
  if ((threadIdx.x & 127) == 0) asm volatile("cp.async.bulk.wait_group.read 0;" ::: "memory");
}

__device__ __forceinline__ void tail_producer(uint32_t sbase, const CUtensorMap* mo, const CUtensorMap* mwA, const CUtensorMap* mwB, int rt,
                                              int ct, int qb) {
  const uint32_t tb = sbase + K2_BAR + 96;
  flag_arrive(&g_sync[qb]);
  mbar_expect_tx(tb + 104, 32768);
  for (int kb = 4; kb < 8; kb++) tma_load_2d(sbase + T_WA1 + (kb - 4) * 8192, mwA, ct * 64, kb * 64, tb + 104);
  for (int g = 2; g < 6; g++) {
    mbar_expect_tx(tb + 8 * g, 16384);
    tma_load_2d(tail_stage(sbase, g), mo, g * 64, rt * 128, tb + 8 * g);
  }
  mbar_expect_tx(tb + 112, 65536);
  for (int kb = 0; kb < 8; kb++) tma_load_2d(sbase + T_WB + kb * 8192, mwB, ct * 64, kb * 64, tb + 112);
  for (int g = 6; g < 16; g++) {
    const int s = g % 6;
    if (g == 8) {
      flag_wait(&g_sync[qb], 32);
      fence_proxy_async_all();
    }
    mbar_wait(tb + 48 + 8 * s, ((g / 6) - 1) & 1);
    mbar_expect_tx(tb + 8 * s, 16384);
    tma_load_2d(tail_stage(sbase, s), mo, (g & 7) * 64, (g >> 3) * S_LEN + rt * 128, tb + 8 * s);
  }
}

__global__ void __launch_bounds__(512, 1)
attn_kernel(const __grid_constant__ CUtensorMap mo16, const __grid_constant__ CUtensorMap mo, const __grid_constant__ CUtensorMap mwA,
            const __grid_constant__ CUtensorMap mwB, const __grid_constant__ CUtensorMap mout, const uint8_t* __restrict__ woA,
            const uint8_t* __restrict__ woB) {
  extern __shared__ uint8_t smem_raw[];
  const uint32_t sbase = (smem_u32(smem_raw) + 1023) & ~1023u;
  const uint32_t bar = sbase + K2_BAR;
  if (threadIdx.x == 0) { PROF_G(1, 30); PROF_T(1, 0); PROF_T(2, 0); }
  if (threadIdx.x == 0) {
    for (int i = 0; i < 4; i++) mbar_init(bar + 8 * i, 2);
    for (int i = 0; i < 6; i++) {
      mbar_init(bar + 96 + 8 * i, 1);
      mbar_init(bar + 96 + 48 + 8 * i, 2);
    }
    for (int i = 0; i < 3; i++) mbar_init(bar + 96 + 96 + 8 * i, 1);
    asm volatile("st.shared.v4.u32 [%0], {%1, %2, %3, %4};" ::"r"(bar + 64), "r"(0x3C003C00u), "r"(0x00070000u), "r"(7u),
                 "r"(ATT_DEG == 3 ? 0x2cfd2cfdu : 0x35623562u)
                 : "memory");
    fence_barrier_init();
    fence_proxy_async();
  }
  __syncthreads();
  if (blockIdx.x >= 128) {
    if (threadIdx.x < 16) {
      const int i = (blockIdx.x - 128) * 16 + threadIdx.x;
      const uint8_t* p = (i < 32 ? woA : woB) + (size_t)(i & 31) * 16384;
      asm volatile("cp.async.bulk.prefetch.L2.global [%0], %1;" ::"l"(p), "r"(16384) : "memory");
    }
    pdl_wait();
    linear_attn_cta(smem_raw, sbase, &mo16, blockIdx.x - 128);
    if (threadIdx.x == 0) { PROF_T(1, 5); PROF_G(1, 31); }
    return;
  }
  const int head = blockIdx.x >> 2, qb = blockIdx.x & 3;
  const int lane = threadIdx.x & 31;
  const int wg = __shfl_sync(0xffffffffu, threadIdx.x >> 7, 0), warp = __shfl_sync(0xffffffffu, (threadIdx.x >> 5) & 3, 0);
  const int ort = qb * 4 + ((blockIdx.x >> 2) & 3), oct = blockIdx.x >> 4;
  ExpC ec;
  asm volatile("ld.volatile.shared.v4.u32 {%0, %1, %2, %3}, [%4];" : "=r"(ec.k3c00), "=r"(ec.kmask), "=r"(ec.seven), "=r"(ec.c3) : "r"(bar + 64));
  const uint64_t dK = mkdesc(sbase, 128, 256, 0);
  const uint64_t dV = mkdesc(sbase + KV_K_BYTES, 384, 128, 0);
  pdl_wait();
  if (threadIdx.x == 0) { PROF_T(1, 7); PROF_G(1, 29); }
  if (threadIdx.x == 0) {
#pragma unroll
    for (int piece = 0; piece < 8; piece++) kv_fetch_piece(sbase, bar, piece);
    mbar_expect_tx(bar + 96 + 96, 32768);
    for (int kb = 0; kb < 4; kb++) tma_load_2d(sbase + T_WA0 + kb * 8192, &mwA, oct * 64, kb * 64, bar + 96 + 96);
  }
  uint4 qnext = g_qfrag[(head * 32 + qb * 8 + wg * 2) * 128 + (threadIdx.x & 127)];
  bool safe_path;
  {
    float4 n = make_float4(0.f, 0.f, 0.f, 0.f);
    if (lane < 16) n = *reinterpret_cast<const float4*>(&g_nrm[(head * 16 + lane) * 4]);
    uint32_t qm = ((lane >> 2) == qb) ? __float_as_uint(n.x) : 0u;
    qm = __reduce_max_sync(0xffffffffu, qm);
    const uint32_t km = __reduce_max_sync(0xffffffffu, __float_as_uint(n.y));
    const uint32_t vm = __reduce_max_sync(0xffffffffu, __float_as_uint(n.z));
    const float b2 = __uint_as_float(qm) * (QSCALE * QSCALE) * __uint_as_float(km) * 1.02f;
    const float vmax = __uint_as_float(vm);
    const bool ok = (b2 <= 21.5f * 21.5f) && (vmax <= 1.0e24f) && (vmax >= 1.0e-18f || vmax == 0.f);
    safe_path = !ok;
  }
#pragma unroll 1
  for (int t = 0; t < 2; t++) {
    const int tile64 = qb * 8 + wg * 2 + t;
    const uint4 qf = qnext;
    if (t == 0) qnext = g_qfrag[(head * 32 + tile64 + 1) * 128 + (threadIdx.x & 127)];
    if (t == 1 && wg == 3) {
      flag_wait(&g_sync[4], 4);
      if (warp == 0 && lane == 0) {
        fence_proxy_async_all();
        for (int g = 0; g < 2; g++) {
          mbar_expect_tx(bar + 96 + 8 * g, 16384);
          tma_load_2d(tail_stage(sbase, g), &mo, g * 64, ort * 128, bar + 96 + 8 * g);
        }
      }
    }
    uint32_t r[4];
    if (threadIdx.x == 0) PROF_T(1, 1 + t);
    if (!safe_path) attn_tile<false>(dK, dV, bar, qf, ec, r, false);
    else attn_tile<true>(dK, dV, bar, qf, ec, r, false);
    store_o(g_o + (size_t)S_LEN * DM, tile64 * 64 + warp * 16, head, lane, r);
  }
  if (threadIdx.x == 0) PROF_T(1, 5);
  fence_proxy_async_all();
  __threadfence();
  if (wg == 2 && warp == 0) {
    asm volatile("bar.sync 2, 512;" ::: "memory");
    if (lane == 0) tail_producer(sbase, &mo, &mwA, &mwB, ort, oct, qb);
  } else {
    asm volatile("bar.arrive 2, 512;" ::: "memory");
    if (wg < 2) tail_consumer(sbase, &mout, ort, oct);
  }
  if (threadIdx.x == 0) { PROF_T(2, 12); PROF_G(1, 31); }
}

typedef CUresult (*EncodeFn)(CUtensorMap*, CUtensorMapDataType, cuuint32_t, void*, const cuuint64_t*, const cuuint64_t*,
                             const cuuint32_t*, const cuuint32_t*, CUtensorMapInterleave, CUtensorMapSwizzle,
                             CUtensorMapL2promotion, CUtensorMapFloatOOBfill);

void make_map(EncodeFn enc, CUtensorMap* m, const void* ptr, uint64_t inner, uint64_t outer, uint32_t box_inner, uint32_t box_outer) {
  cuuint64_t dims[2] = {inner, outer};
  cuuint64_t strides[1] = {inner * 2};
  cuuint32_t box[2] = {box_inner, box_outer};
  cuuint32_t es[2] = {1, 1};
  enc(m, CU_TENSOR_MAP_DATA_TYPE_BFLOAT16, 2, const_cast<void*>(ptr), dims, strides, box, es, CU_TENSOR_MAP_INTERLEAVE_NONE,
      CU_TENSOR_MAP_SWIZZLE_128B, CU_TENSOR_MAP_L2_PROMOTION_L2_256B, CU_TENSOR_MAP_FLOAT_OOB_FILL_NONE);
}

struct HostState {
  bool init;
  const void* key[7];
  CUtensorMap mxA, mxB, mwA, mwB, mo, mo16, mwoA, mwoB, mout;
};
HostState g_hs;

}

extern "C" void kernel_launch(void* const* d_in, const int* in_sizes, int n_in, void* d_out, int out_size) {
  (void)in_sizes; (void)n_in; (void)out_size;
  HostState& hs = g_hs;
  bool same = hs.init && hs.key[6] == d_out;
  for (int i = 0; i < 6 && same; i++) same = hs.key[i] == d_in[i];
  if (!same) {
    void* fn = nullptr;
    cudaDriverEntryPointQueryResult qr;
    cudaGetDriverEntryPoint("cuTensorMapEncodeTiled", &fn, cudaEnableDefault, &qr);
    EncodeFn enc = (EncodeFn)fn;
    void* go = nullptr;
    cudaGetSymbolAddress(&go, g_o);
    make_map(enc, &hs.mxA, d_in[0], 512, 2048, 64, 128);
    make_map(enc, &hs.mwA, d_in[1], 1536, 512, 64, 32);
    make_map(enc, &hs.mwoA, d_in[2], 512, 512, 64, 64);
    make_map(enc, &hs.mxB, d_in[3], 512, 2048, 64, 128);
    make_map(enc, &hs.mwB, d_in[4], 1536, 512, 64, 32);
    make_map(enc, &hs.mwoB, d_in[5], 512, 512, 64, 64);
    make_map(enc, &hs.mo, go, 512, 4096, 64, 128);
    make_map(enc, &hs.mo16, go, 512, 4096, 64, 16);
    make_map(enc, &hs.mout, d_out, 1024, 2048, 64, 64);
    cudaFuncSetAttribute(qkv_gemm_kernel, cudaFuncAttributeMaxDynamicSharedMemorySize, K1_SMEM);
    cudaFuncSetAttribute(attn_kernel, cudaFuncAttributeMaxDynamicSharedMemorySize, K2_SMEM);
    for (int i = 0; i < 6; i++) hs.key[i] = d_in[i];
    hs.key[6] = d_out;
    hs.init = true;
  }
  cudaStream_t st = cudaStreamPerThread;
  {
    cudaLaunchConfig_t cfg = {};
    cfg.gridDim = dim3(128);
    cfg.blockDim = dim3(384);
    cfg.dynamicSmemBytes = K1_SMEM;
    cfg.stream = st;
    cudaLaunchAttribute at[1];
    at[0].id = cudaLaunchAttributeClusterDimension;
    at[0].val.clusterDim.x = 2;
    at[0].val.clusterDim.y = 1;
    at[0].val.clusterDim.z = 1;
    cfg.attrs = at;
    cfg.numAttrs = 1;
    cudaLaunchKernelEx(&cfg, qkv_gemm_kernel, hs.mxA, hs.mxB, hs.mwA, hs.mwB);
  }
  {
    cudaLaunchConfig_t cfg = {};
    cfg.gridDim = dim3(132);
    cfg.blockDim = dim3(512);
    cfg.dynamicSmemBytes = K2_SMEM;
    cfg.stream = st;
    cudaLaunchAttribute at[1];
    at[0].id = cudaLaunchAttributeProgrammaticStreamSerialization;
    at[0].val.programmaticStreamSerializationAllowed = 1;
    cfg.attrs = at;
    cfg.numAttrs = 1;
    cudaLaunchKernelEx(&cfg, attn_kernel, hs.mo16, hs.mo, hs.mwoA, hs.mwoB, hs.mout, (const uint8_t*)d_in[2], (const uint8_t*)d_in[5]);
  }
}
```

```cpp
#include <cuda_runtime.h>
#include <cuda_bf16.h>
#include <cuda.h>
#include <stdint.h>

namespace {

constexpr int S_LEN = 2048;
constexpr int DM = 512;
constexpr int NH = 32;

constexpr int KV_K_BYTES = 65536;
constexpr int KV_HEAD_BYTES = KV_K_BYTES + 98304;
__device__ uint4 g_qfrag[2 * NH * 32 * 128];
__device__ uint4 g_kv[NH * KV_HEAD_BYTES / 16];
__device__ float g_kvpart[16 * NH * 384];
__device__ float g_nrm[NH * 16 * 4];
__device__ uint32_t g_sync[8];
__device__ __nv_bfloat16 g_o[2 * S_LEN * DM];

#define g_prof_set(k, i, v)
#define g_prof_dummy(i) true
#define PROF_T(k, i) do {} while (0)
#define PROF_G(k, i) do {} while (0)
__device__ __forceinline__ uint32_t smem_u32(const void* p) { return (uint32_t)__cvta_generic_to_shared(p); }
__device__ __forceinline__ void mbar_init(uint32_t bar, int cnt) {
  asm volatile("mbarrier.init.shared::cta.b64 [%0], %1;" ::"r"(bar), "r"(cnt) : "memory");
}
__device__ __forceinline__ void mbar_expect_tx(uint32_t bar, uint32_t bytes) {
  asm volatile("mbarrier.arrive.expect_tx.shared::cta.b64 _, [%0], %1;" ::"r"(bar), "r"(bytes) : "memory");
}
__device__ __forceinline__ void mbar_arrive(uint32_t bar) {
  asm volatile("mbarrier.arrive.shared::cta.b64 _, [%0];" ::"r"(bar) : "memory");
}
__device__ __forceinline__ void mbar_arrive_cluster(uint32_t bar, uint32_t cta) {
  asm volatile(
      "{\n.reg .b32 ra;\nmapa.shared::cluster.u32 ra, %0, %1;\n"
      "mbarrier.arrive.shared::cluster.b64 _, [ra];\n}" ::"r"(bar), "r"(cta) : "memory");
}
__device__ __forceinline__ void mbar_wait(uint32_t bar, uint32_t parity) {
  asm volatile(
      "{\n.reg .pred p;\n.reg .u32 n;\n"
      "mov.u32 n, 0;\n"
      "WAIT_LOOP:\n"
      "mbarrier.try_wait.parity.shared::cta.b64 p, [%0], %1, 0x400000;\n"
      "@p bra WAIT_DONE;\n"
      "add.u32 n, n, 1;\n"
      "setp.lt.u32 p, n, 4000000;\n"
      "@p bra WAIT_LOOP;\n"
      "trap;\n"
      "WAIT_DONE:\n}" ::"r"(bar), "r"(parity) : "memory");
}
__device__ __forceinline__ void fence_barrier_init() {
  asm volatile("fence.mbarrier_init.release.cluster;" ::: "memory");
}
__device__ __forceinline__ void fence_proxy_async() { asm volatile("fence.proxy.async.shared::cta;" ::: "memory"); }
__device__ __forceinline__ void cluster_sync_relaxed() {
  asm volatile("barrier.cluster.arrive.relaxed.aligned;\nbarrier.cluster.wait.aligned;" ::: "memory");
}
__device__ __forceinline__ void tma_load_2d(uint32_t dst, const CUtensorMap* m, int x, int y, uint32_t bar) {
  asm volatile(
      "cp.async.bulk.tensor.2d.shared::cluster.global.mbarrier::complete_tx::bytes [%0], [%1, {%3, %4}], [%2];" ::"r"(dst),
      "l"(m), "r"(bar), "r"(x), "r"(y)
      : "memory");
}
__device__ __forceinline__ void tma_load_2d_mc(uint32_t dst, const CUtensorMap* m, int x, int y, uint32_t bar, uint16_t mask) {
  asm volatile(
      "cp.async.bulk.tensor.2d.shared::cluster.global.mbarrier::complete_tx::bytes.multicast::cluster [%0], [%1, {%3, %4}], "
      "[%2], %5;" ::"r"(dst),
      "l"(m), "r"(bar), "r"(x), "r"(y), "h"(mask)
      : "memory");
}
__device__ __forceinline__ void tma_store_2d(const CUtensorMap* m, uint32_t src, int x, int y) {
  asm volatile("cp.async.bulk.tensor.2d.global.shared::cta.bulk_group [%0, {%2, %3}], [%1];" ::"l"(m), "r"(src), "r"(x),
               "r"(y)
               : "memory");
}
__device__ __forceinline__ void bulk_load(uint32_t dst, const void* src, uint32_t bytes, uint32_t bar) {
  asm volatile("cp.async.bulk.shared::cluster.global.mbarrier::complete_tx::bytes [%0], [%1], %2, [%3];" ::"r"(dst),
               "l"(src), "r"(bytes), "r"(bar)
               : "memory");
}
__device__ __forceinline__ void bulk_load_mc(uint32_t dst, const void* src, uint32_t bytes, uint32_t bar, uint16_t mask) {
  asm volatile("cp.async.bulk.shared::cluster.global.mbarrier::complete_tx::bytes.multicast::cluster [%0], [%1], %2, [%3], %4;" ::"r"(dst),
               "l"(src), "r"(bytes), "r"(bar), "h"(mask)
               : "memory");
}
__device__ __forceinline__ void flag_arrive(uint32_t* p) {
  asm volatile("red.release.gpu.global.add.u32 [%0], 1;" ::"l"(p) : "memory");
}
__device__ __forceinline__ void flag_wait(const uint32_t* p, uint32_t target) {
  asm volatile(
      "{\n.reg .pred p;\n.reg .u32 n, v;\n"
      "mov.u32 n, 0;\n"
      "FLAG_LOOP:\n"
      "ld.acquire.gpu.global.u32 v, [%0];\n"
      "setp.ge.u32 p, v, %1;\n"
      "@p bra FLAG_DONE;\n"
      "add.u32 n, n, 1;\n"
      "setp.lt.u32 p, n, 20000000;\n"
      "@p bra FLAG_LOOP;\n"
      "trap;\n"
      "FLAG_DONE:\n}" ::"l"(p), "r"(target) : "memory");
}
__device__ __forceinline__ void fence_proxy_async_all() { asm volatile("fence.proxy.async;" ::: "memory"); }
__device__ __forceinline__ void pdl_launch_dependents() { asm volatile("griddepcontrol.launch_dependents;" ::: "memory"); }
__device__ __forceinline__ void pdl_wait() { asm volatile("griddepcontrol.wait;" ::: "memory"); }
__device__ __forceinline__ void wg_fence() { asm volatile("wgmma.fence.sync.aligned;" ::: "memory"); }
__device__ __forceinline__ void wg_commit() { asm volatile("wgmma.commit_group.sync.aligned;" ::: "memory"); }
template <int N>
__device__ __forceinline__ void wg_wait() {
  asm volatile("wgmma.wait_group.sync.aligned %0;" ::"n"(N) : "memory");
}
template <int M>
__device__ __forceinline__ void fence_regs(float (&r)[M]) {
#pragma unroll
  for (int i = 0; i < M; i++) asm volatile("" : "+f"(r[i])::"memory");
}
__device__ __forceinline__ uint64_t mkdesc(uint32_t addr, uint32_t lbo, uint32_t sbo, uint32_t layout) {
  return (uint64_t)((addr & 0x3FFFF) >> 4) | ((uint64_t)(lbo >> 4) << 16) | ((uint64_t)(sbo >> 4) << 32) |
         ((uint64_t)layout << 62);
}
__device__ __forceinline__ uint32_t pack_bf16(float lo, float hi) {
  uint32_t r;
  asm("cvt.rn.bf16x2.f32 %0, %1, %2;" : "=r"(r) : "f"(hi), "f"(lo));
  return r;
}
__device__ __forceinline__ float bf_lo(uint32_t v) { return __uint_as_float(v << 16); }
__device__ __forceinline__ float bf_hi(uint32_t v) { return __uint_as_float(v & 0xFFFF0000u); }
__device__ __forceinline__ float round_bf16(float x) { return bf_lo(pack_bf16(x, 0.f)); }
__device__ __forceinline__ float ex2f(float x) {
  float y;
  asm("ex2.approx.ftz.f32 %0, %1;" : "=f"(y) : "f"(x));
  return y;
}

__device__ __forceinline__ void wgmma_rs_n24_tb(float (&d)[12], uint32_t a0, uint32_t a1, uint32_t a2, uint32_t a3, uint64_t descB, int scaleD) {
  asm volatile("{\n.reg .pred p;\nsetp.ne.b32 p, %17, 0;\n"
    "wgmma.mma_async.sync.aligned.m64n24k16.f32.bf16.bf16 "
    "{%0, %1, %2, %3, %4, %5, %6, %7, %8, %9, %10, %11}, {%12, %13, %14, %15}, %16, p, 1, 1, 1;\n}\n"
    : "+f"(d[0]), "+f"(d[1]), "+f"(d[2]), "+f"(d[3]), "+f"(d[4]), "+f"(d[5]), "+f"(d[6]), "+f"(d[7]),
      "+f"(d[8]), "+f"(d[9]), "+f"(d[10]), "+f"(d[11])
    : "r"(a0), "r"(a1), "r"(a2), "r"(a3), "l"(descB), "r"(scaleD));
}
__device__ __forceinline__ void wgmma_rs_n64_z(float (&d)[32], uint32_t a0, uint32_t a1, uint32_t a2, uint32_t a3, uint64_t descB) {
  asm volatile("{\n.reg .pred p;\nsetp.ne.b32 p, %37, 0;\n"
    "wgmma.mma_async.sync.aligned.m64n64k16.f32.bf16.bf16 "
    "{%0, %1, %2, %3, %4, %5, %6, %7, %8, %9, %10, %11, %12, %13, %14, %15, %16, %17, %18, %19, %20, %21, %22, %23, %24, %25, %26, %27, %28, %29, %30, %31}, {%32, %33, %34, %35}, %36, p, 1, 1, 0;\n}\n"
    : "=f"(d[0]), "=f"(d[1]), "=f"(d[2]), "=f"(d[3]), "=f"(d[4]), "=f"(d[5]), "=f"(d[6]), "=f"(d[7]),
      "=f"(d[8]), "=f"(d[9]), "=f"(d[10]), "=f"(d[11]), "=f"(d[12]), "=f"(d[13]), "=f"(d[14]), "=f"(d[15]),
      "=f"(d[16]), "=f"(d[17]), "=f"(d[18]), "=f"(d[19]), "=f"(d[20]), "=f"(d[21]), "=f"(d[22]), "=f"(d[23]),
      "=f"(d[24]), "=f"(d[25]), "=f"(d[26]), "=f"(d[27]), "=f"(d[28]), "=f"(d[29]), "=f"(d[30]), "=f"(d[31])
    : "r"(a0), "r"(a1), "r"(a2), "r"(a3), "l"(descB), "n"(0));
}
__device__ __forceinline__ void wgmma_ss_n192_tb(float (&d)[96], uint64_t descA, uint64_t descB, int scaleD) {
  asm volatile("{\n.reg .pred p;\nsetp.ne.b32 p, %98, 0;\n"
    "wgmma.mma_async.sync.aligned.m64n192k16.f32.bf16.bf16 "
    "{%0, %1, %2, %3, %4, %5, %6, %7, %8, %9, %10, %11, %12, %13, %14, %15, %16, %17, %18, %19, %20, %21, %22, %23, %24, %25, %26, %27, %28, %29, %30, %31, %32, %33, %34, %35, %36, %37, %38, %39, %40, %41, %42, %43, %44, %45, %46, %47, %48, %49, %50, %51, %52, %53, %54, %55, %56, %57, %58, %59, %60, %61, %62, %63, %64, %65, %66, %67, %68, %69, %70, %71, %72, %73, %74, %75, %76, %77, %78, %79, %80, %81, %82, %83, %84, %85, %86, %87, %88, %89, %90, %91, %92, %93, %94, %95}, %96, %97, p, 1, 1, 0, 1;\n}\n"
    : "+f"(d[0]), "+f"(d[1]), "+f"(d[2]), "+f"(d[3]), "+f"(d[4]), "+f"(d[5]), "+f"(d[6]), "+f"(d[7]),
      "+f"(d[8]), "+f"(d[9]), "+f"(d[10]), "+f"(d[11]), "+f"(d[12]), "+f"(d[13]), "+f"(d[14]), "+f"(d[15]),
      "+f"(d[16]), "+f"(d[17]), "+f"(d[18]), "+f"(d[19]), "+f"(d[20]), "+f"(d[21]), "+f"(d[22]), "+f"(d[23]),
      "+f"(d[24]), "+f"(d[25]), "+f"(d[26]), "+f"(d[27]), "+f"(d[28]), "+f"(d[29]), "+f"(d[30]), "+f"(d[31]),
      "+f"(d[32]), "+f"(d[33]), "+f"(d[34]), "+f"(d[35]), "+f"(d[36]), "+f"(d[37]), "+f"(d[38]), "+f"(d[39]),
      "+f"(d[40]), "+f"(d[41]), "+f"(d[42]), "+f"(d[43]), "+f"(d[44]), "+f"(d[45]), "+f"(d[46]), "+f"(d[47]),
      "+f"(d[48]), "+f"(d[49]), "+f"(d[50]), "+f"(d[51]), "+f"(d[52]), "+f"(d[53]), "+f"(d[54]), "+f"(d[55]),
      "+f"(d[56]), "+f"(d[57]), "+f"(d[58]), "+f"(d[59]), "+f"(d[60]), "+f"(d[61]), "+f"(d[62]), "+f"(d[63]),
      "+f"(d[64]), "+f"(d[65]), "+f"(d[66]), "+f"(d[67]), "+f"(d[68]), "+f"(d[69]), "+f"(d[70]), "+f"(d[71]),
      "+f"(d[72]), "+f"(d[73]), "+f"(d[74]), "+f"(d[75]), "+f"(d[76]), "+f"(d[77]), "+f"(d[78]), "+f"(d[79]),
      "+f"(d[80]), "+f"(d[81]), "+f"(d[82]), "+f"(d[83]), "+f"(d[84]), "+f"(d[85]), "+f"(d[86]), "+f"(d[87]),
      "+f"(d[88]), "+f"(d[89]), "+f"(d[90]), "+f"(d[91]), "+f"(d[92]), "+f"(d[93]), "+f"(d[94]), "+f"(d[95])
    : "l"(descA), "l"(descB), "r"(scaleD));
}
__device__ __forceinline__ void wgmma_ss_n64_tb(float (&d)[32], uint64_t descA, uint64_t descB, int scaleD) {
  asm volatile("{\n.reg .pred p;\nsetp.ne.b32 p, %34, 0;\n"
    "wgmma.mma_async.sync.aligned.m64n64k16.f32.bf16.bf16 "
    "{%0, %1, %2, %3, %4, %5, %6, %7, %8, %9, %10, %11, %12, %13, %14, %15, %16, %17, %18, %19, %20, %21, %22, %23, %24, %25, %26, %27, %28, %29, %30, %31}, %32, %33, p, 1, 1, 0, 1;\n}\n"
    : "+f"(d[0]), "+f"(d[1]), "+f"(d[2]), "+f"(d[3]), "+f"(d[4]), "+f"(d[5]), "+f"(d[6]), "+f"(d[7]),
      "+f"(d[8]), "+f"(d[9]), "+f"(d[10]), "+f"(d[11]), "+f"(d[12]), "+f"(d[13]), "+f"(d[14]), "+f"(d[15]),
      "+f"(d[16]), "+f"(d[17]), "+f"(d[18]), "+f"(d[19]), "+f"(d[20]), "+f"(d[21]), "+f"(d[22]), "+f"(d[23]),
      "+f"(d[24]), "+f"(d[25]), "+f"(d[26]), "+f"(d[27]), "+f"(d[28]), "+f"(d[29]), "+f"(d[30]), "+f"(d[31])
    : "l"(descA), "l"(descB), "r"(scaleD));
}

__device__ __forceinline__ void ldsm4t(uint32_t (&b)[4], uint32_t addr) {
  asm volatile("ldmatrix.sync.aligned.m8n8.x4.trans.shared.b16 {%0,%1,%2,%3}, [%4];"
               : "=r"(b[0]), "=r"(b[1]), "=r"(b[2]), "=r"(b[3])
               : "r"(addr));
}
__device__ __forceinline__ void hmma(float (&c)[4], uint32_t a0, uint32_t a1, uint32_t a2, uint32_t a3, uint32_t b0, uint32_t b1) {
  asm("mma.sync.aligned.m16n8k16.row.col.f32.bf16.bf16.f32 {%0,%1,%2,%3}, {%4,%5,%6,%7}, {%8,%9}, {%0,%1,%2,%3};"
      : "+f"(c[0]), "+f"(c[1]), "+f"(c[2]), "+f"(c[3])
      : "r"(a0), "r"(a1), "r"(a2), "r"(a3), "r"(b0), "r"(b1));
}

__device__ __forceinline__ uint32_t movm(uint32_t a) {
  uint32_t d;
  asm volatile("movmatrix.sync.aligned.m8n8.trans.b16 %0, %1;" : "=r"(d) : "r"(a));
  return d;
}

#define K1_WARM 0
constexpr int K1_STAGES = 4;
constexpr int K1_W_BYTES = 3 * 8192;
constexpr int K1_X_BYTES = 8 * 16384;
constexpr int K1_BAR_OFF = K1_X_BYTES + K1_STAGES * K1_W_BYTES;
constexpr int K1_SMEM = K1_BAR_OFF + 192 + 1024;
constexpr float QSCALE = 0.25f * 1.4426950408889634f;

__device__ __forceinline__ uint32_t phi2(uint32_t t2) {
  uint32_t a2, mask, r2, o2;
  asm("add.rn.bf16x2 %0, %1, %2;" : "=r"(a2) : "r"(t2), "r"(0x3F803F80u));
  const uint32_t e2 = pack_bf16(ex2f(bf_lo(t2) * 1.4426950408889634f), ex2f(bf_hi(t2) * 1.4426950408889634f));
  asm("set.gt.u32.bf16x2 %0, %1, %2;" : "=r"(mask) : "r"(t2), "r"(0u));
  r2 = (a2 & mask) | (e2 & ~mask);
  asm("add.rn.bf16x2 %0, %1, %2;" : "=r"(o2) : "r"(r2), "r"(0x35863586u));
  return o2;
}

#define K1_SLOT_KB(h) ((h) < 4 ? 2 * (h) : 2 * ((h) - 4) + 1)
struct EpiCtx {
  uint4* qf;
  uint32_t* kp;
  uint32_t* vp;
  uint32_t* s_red;
  float* red;
  int lane;
};

template <bool LINEAR, int HH, int PART>
__device__ __forceinline__ void epi_slice(const float (&acc)[96], const EpiCtx& c, uint32_t (&pk)[4], float& vmax, bool live) {
  const float* a = &acc[HH * 8];
  const float* k = &acc[32 + HH * 8];
  const float* v = &acc[64 + HH * 8];
  if (!LINEAR) {
    if (PART == 0) {
      uint32_t* kh = c.kp + HH * (KV_HEAD_BYTES / 4);
      if (live) {
        c.qf[HH * 32 * 128] = make_uint4(pack_bf16(a[0] * QSCALE, a[1] * QSCALE), pack_bf16(a[2] * QSCALE, a[3] * QSCALE),
                                         pack_bf16(a[4] * QSCALE, a[5] * QSCALE), pack_bf16(a[6] * QSCALE, a[7] * QSCALE));
        kh[0] = pack_bf16(k[0], k[1]);
        kh[64] = pack_bf16(k[2], k[3]);
        kh[32] = pack_bf16(k[4], k[5]);
        kh[96] = pack_bf16(k[6], k[7]);
      }
      float q0 = a[0] * a[0] + a[1] * a[1] + a[4] * a[4] + a[5] * a[5];
      float q1 = a[2] * a[2] + a[3] * a[3] + a[6] * a[6] + a[7] * a[7];
      float k0 = k[0] * k[0] + k[1] * k[1] + k[4] * k[4] + k[5] * k[5];
      float k1 = k[2] * k[2] + k[3] * k[3] + k[6] * k[6] + k[7] * k[7];
#pragma unroll
      for (int o = 1; o <= 2; o <<= 1) {
        q0 += __shfl_xor_sync(0xffffffffu, q0, o);
        q1 += __shfl_xor_sync(0xffffffffu, q1, o);
        k0 += __shfl_xor_sync(0xffffffffu, k0, o);
        k1 += __shfl_xor_sync(0xffffffffu, k1, o);
      }
      const uint32_t qm = __reduce_max_sync(0xffffffffu, max(__float_as_uint(q0) & 0x7FFFFFFFu, __float_as_uint(q1) & 0x7FFFFFFFu));
      const uint32_t km = __reduce_max_sync(0xffffffffu, max(__float_as_uint(k0) & 0x7FFFFFFFu, __float_as_uint(k1) & 0x7FFFFFFFu));
      if (c.lane == 0 && live) {
        atomicMax(&c.s_red[HH * 2 + 0], qm);
        atomicMax(&c.s_red[HH * 2 + 1], km);
      }
    } else {
      uint32_t* vh = c.vp + HH * (KV_HEAD_BYTES / 4);
      if (live) {
        vh[0] = pack_bf16(v[0], v[1]);
        vh[96] = pack_bf16(v[2], v[3]);
        vh[32] = pack_bf16(v[4], v[5]);
        vh[128] = pack_bf16(v[6], v[7]);
        vh[64] = 0x3F803F80u;
        vh[160] = 0x3F803F80u;
      }
#pragma unroll
      for (int i = 0; i < 8; i++) asm("max.NaN.f32 %0, %0, %1;" : "+f"(vmax) : "f"(fabsf(v[i])));
    }
  } else {
    if (PART == 0) {
      const uint4 pq = make_uint4(phi2(pack_bf16(a[0], a[1])), phi2(pack_bf16(a[2], a[3])), phi2(pack_bf16(a[4], a[5])),
                                  phi2(pack_bf16(a[6], a[7])));
      if (live) c.qf[HH * 32 * 128] = pq;
      pk[0] = movm(phi2(pack_bf16(k[0], k[1])));
      pk[2] = movm(phi2(pack_bf16(k[2], k[3])));
      pk[1] = movm(phi2(pack_bf16(k[4], k[5])));
      pk[3] = movm(phi2(pack_bf16(k[6], k[7])));
    } else {
      const uint32_t b0 = movm(pack_bf16(v[0], v[1]));
      const uint32_t b1 = movm(pack_bf16(v[2], v[3]));
      const uint32_t b2 = movm(pack_bf16(v[4], v[5]));
      const uint32_t b3 = movm(pack_bf16(v[6], v[7]));
      float c0[4] = {0, 0, 0, 0}, c1[4] = {0, 0, 0, 0}, c2[4] = {0, 0, 0, 0};
      hmma(c0, pk[0], pk[1], pk[2], pk[3], b0, b1);
      hmma(c1, pk[0], pk[1], pk[2], pk[3], b2, b3);
      hmma(c2, pk[0], pk[1], pk[2], pk[3], 0x3F803F80u, 0x3F803F80u);
      float* slot = c.red + HH * 2 * 4096;
      if (live) {
#pragma unroll
        for (int i = 0; i < 4; i++) {
          slot[i * 32] = c0[i];
          slot[(4 + i) * 32] = c1[i];
          slot[(8 + i) * 32] = c2[i];
        }
      }
    }
  }
}

template <bool LINEAR>
__device__ __forceinline__ void qkv_consumer(uint32_t sbase, uint8_t* smem_gen, uint32_t* s_red, int cp, int rt) {
  const uint32_t bar_full = sbase + K1_BAR_OFF;
  const uint32_t bar_empty = bar_full + 8 * K1_STAGES;
  const int warp = threadIdx.x >> 5;
  const int wg = warp >> 2;
  const int lane = threadIdx.x & 31;
  float accN[96], accP[96];
  EpiCtx c;
  {
    const int row0 = rt * 128 + wg * 64 + (warp & 3) * 16;
    c.qf = g_qfrag + ((size_t)((LINEAR ? NH : 0) + cp * 8) * 32 + (rt * 2 + wg)) * 128 + (threadIdx.x & 127);
    uint32_t* img = reinterpret_cast<uint32_t*>(reinterpret_cast<uint8_t*>(g_kv) + (size_t)(cp * 8) * KV_HEAD_BYTES);
    c.kp = img + (row0 >> 3) * 64 + lane;
    c.vp = img + KV_K_BYTES / 4 + (row0 >> 3) * 96 + lane;
    c.s_red = s_red;
    c.red = reinterpret_cast<float*>(smem_gen + wg * 8192) + (warp & 3) * 384 + lane;
    c.lane = lane;
  }
  uint32_t pk[4] = {0, 0, 0, 0};
  float vmax = 0.f;
#pragma unroll
  for (int i = 0; i < 96; i++) asm volatile("mov.f32 %0, 0f00000000;" : "=f"(accN[i]));
  int npass;
  asm volatile("mov.u32 %0, 2;" : "=r"(npass));
#pragma unroll 1
  for (int pass = K1_WARM ? 0 : 1; pass < npass; pass++) {
    const bool live = K1_WARM ? pass != 0 : true;
    if (live) {
#pragma unroll 1
      for (int kb = 0; kb < 8; kb++) {
        const int s = kb % K1_STAGES;
        mbar_wait(bar_full + 8 * s, (kb / K1_STAGES) & 1);
        if (threadIdx.x == 0) PROF_T(0, 2 + (kb >> 1));
        const uint64_t dA = mkdesc(sbase + kb * 16384 + wg * 8192, 16, 1024, 1);
        const uint64_t dB = mkdesc(sbase + K1_X_BYTES + s * K1_W_BYTES, 8192, 1024, 1);
        wg_fence();
#pragma unroll
        for (int k = 0; k < 4; k++) wgmma_ss_n192_tb(accP, dA + k * 2, dB + k * 128, (kb | k) != 0);
        wg_commit();
        if (kb > 0) {
          wg_wait<1>();
          if ((threadIdx.x & 127) == 0) {
            const int sp = (kb - 1) % K1_STAGES;
            mbar_arrive_cluster(bar_empty + 8 * sp, 0);
            mbar_arrive_cluster(bar_empty + 8 * sp, 1);
          }
        }
      }
      wg_wait<0>();
      fence_regs(accP);
      if ((threadIdx.x & 127) == 0) {
        mbar_arrive_cluster(bar_empty + 8 * (7 % K1_STAGES), 0);
        mbar_arrive_cluster(bar_empty + 8 * (7 % K1_STAGES), 1);
      }
      if (threadIdx.x == 0) PROF_T(0, 6);
#define K1_T1_STEP(KB)                                                                           \
  {                                                                                              \
    constexpr int g = 8 + KB;                                                                    \
    constexpr int s = g % K1_STAGES;                                                             \
    mbar_wait(bar_full + 8 * s, (g / K1_STAGES) & 1);                                            \
    const uint64_t dA = mkdesc(sbase + KB * 16384 + wg * 8192, 16, 1024, 1);                     \
    const uint64_t dB = mkdesc(sbase + K1_X_BYTES + s * K1_W_BYTES, 8192, 1024, 1);              \
    wg_fence();                                                                                  \
    _Pragma("unroll") for (int k = 0; k < 4; k++) wgmma_ss_n192_tb(accN, dA + k * 2, dB + k * 128, (KB | k) != 0); \
    wg_commit();                                                                                 \
    epi_slice<LINEAR, KB / 2, KB & 1>(accP, c, pk, vmax, true);                                  \
    wg_wait<0>();                                                                                \
    if (KB + K1_STAGES < 8 && (threadIdx.x & 127) == 0) {                                        \
      mbar_arrive_cluster(bar_empty + 8 * s, 0);                                                 \
      mbar_arrive_cluster(bar_empty + 8 * s, 1);                                                 \
    }                                                                                            \
  }
      K1_T1_STEP(0) K1_T1_STEP(1) K1_T1_STEP(2) K1_T1_STEP(3) K1_T1_STEP(4) K1_T1_STEP(5) K1_T1_STEP(6) K1_T1_STEP(7)
#undef K1_T1_STEP
      fence_regs(accN);
      if (threadIdx.x == 0) PROF_T(0, 10);
      c.qf += 4 * 32 * 128;
      c.kp += 4 * (KV_HEAD_BYTES / 4);
      c.vp += 4 * (KV_HEAD_BYTES / 4);
      c.s_red += 8;
      c.red += 4096;
    }
    float vm1 = 0.f;
    epi_slice<LINEAR, 0, 0>(accN, c, pk, vm1, live);
    epi_slice<LINEAR, 0, 1>(accN, c, pk, vm1, live);
    epi_slice<LINEAR, 1, 0>(accN, c, pk, vm1, live);
    epi_slice<LINEAR, 1, 1>(accN, c, pk, vm1, live);
    epi_slice<LINEAR, 2, 0>(accN, c, pk, vm1, live);
    epi_slice<LINEAR, 2, 1>(accN, c, pk, vm1, live);
    epi_slice<LINEAR, 3, 0>(accN, c, pk, vm1, live);
    epi_slice<LINEAR, 3, 1>(accN, c, pk, vm1, live);
    if (live) asm("max.NaN.f32 %0, %0, %1;" : "+f"(vmax) : "f"(vm1));
  }
  if (!LINEAR) {
    const uint32_t vm = __reduce_max_sync(0xffffffffu, __float_as_uint(vmax) & 0x7FFFFFFFu);
    if (lane == 0) atomicMax(&s_red[16], vm);
    asm volatile("bar.sync 1, 256;" ::: "memory");
    if (threadIdx.x < 8) {
      *reinterpret_cast<float4*>(&g_nrm[((cp * 8 + threadIdx.x) * 16 + rt) * 4]) =
          make_float4(__uint_as_float(s_red[threadIdx.x * 2]), __uint_as_float(s_red[threadIdx.x * 2 + 1]), __uint_as_float(s_red[16]), 0.f);
    }
  } else {
    asm volatile("bar.sync 1, 256;" ::: "memory");
    float* dst = g_kvpart + ((size_t)rt * NH + cp * 8) * 384;
#pragma unroll
    for (int i = 0; i < 12; i++) {
      const int o = threadIdx.x + i * 256;
      const int h = o / 384, e = o - h * 384;
      const float* src = reinterpret_cast<const float*>(smem_gen) + K1_SLOT_KB(h) * 4096 + e;
      float sum = 0.f;
#pragma unroll
      for (int w = 0; w < 8; w++) sum += src[(w >> 2) * 2048 + (w & 3) * 384];
      dst[o] = sum;
    }
  }
}

__global__ void __launch_bounds__(384, 1)
qkv_gemm_kernel(const __grid_constant__ CUtensorMap mxA, const __grid_constant__ CUtensorMap mxB,
                const __grid_constant__ CUtensorMap mwA, const __grid_constant__ CUtensorMap mwB) {
  extern __shared__ uint8_t smem_raw[];
  const uint32_t sbase = (smem_u32(smem_raw) + 1023) & ~1023u;
  uint8_t* smem_gen = smem_raw + (sbase - smem_u32(smem_raw));
  const uint32_t bar_full = sbase + K1_BAR_OFF;
  const uint32_t bar_empty = bar_full + 8 * K1_STAGES;
  uint32_t* s_red = reinterpret_cast<uint32_t*>(smem_gen + K1_BAR_OFF + 64);

  const int rank = blockIdx.x & 1;
  const int pair = blockIdx.x >> 1;
  const int branch = pair >> 5;
  const int rp = (pair & 31) >> 2;
  const int cp = pair & 3;
  const int rt = rp * 2 + rank;
  const int warp = threadIdx.x >> 5;
  if (threadIdx.x == 0) { PROF_G(0, 30); PROF_T(0, 0); }
  const CUtensorMap* mx = branch ? &mxA : &mxB;
  const CUtensorMap* mw = branch ? &mwA : &mwB;

  if (threadIdx.x == 256) {
    asm volatile("prefetch.tensormap [%0];" ::"l"(mx) : "memory");
    asm volatile("prefetch.tensormap [%0];" ::"l"(mw) : "memory");
    for (int i = 0; i < K1_STAGES; i++) {
      mbar_init(bar_full + 8 * i, 1);
      mbar_init(bar_empty + 8 * i, 4);
    }
    fence_barrier_init();
    fence_proxy_async();
    for (int kb = 0; kb < K1_STAGES; kb++) mbar_expect_tx(bar_full + 8 * kb, 16384 + K1_W_BYTES);
    tma_load_2d(sbase, mx, 0, rt * 128, bar_full);
  }
  pdl_launch_dependents();
  if (threadIdx.x < 32) s_red[threadIdx.x] = 0;
  if (blockIdx.x == 0 && threadIdx.x < 8) g_sync[threadIdx.x] = 0;
  __syncthreads();
  cluster_sync_relaxed();
  if (threadIdx.x == 0) PROF_T(0, 1);

  if (warp >= 8) {
    asm volatile("setmaxnreg.dec.sync.aligned.u32 40;");
    if (threadIdx.x == 256) {
      for (int g = 0; g < 16; g++) {
        const int s = g % K1_STAGES;
        const int kb = g & 7;
        if (g >= K1_STAGES) {
          mbar_wait(bar_empty + 8 * s, ((g / K1_STAGES) - 1) & 1);
          mbar_expect_tx(bar_full + 8 * s, (g < 8 ? 16384 : 0) + K1_W_BYTES);
        }
        if (g > 0 && g < 8) tma_load_2d(sbase + kb * 16384, mx, kb * 64, rt * 128, bar_full + 8 * s);
        const int h0 = cp * 8 + (g >> 3) * 4;
        const uint32_t st = sbase + K1_X_BYTES + s * K1_W_BYTES + rank * 4096;
#pragma unroll
        for (int p = 0; p < 3; p++)
          tma_load_2d_mc(st + p * 8192, mw, p * 512 + h0 * 16, kb * 64 + rank * 32, bar_full + 8 * s, (uint16_t)3);
      }
    }
    __syncwarp();
    cluster_sync_relaxed();
  } else {
    asm volatile("setmaxnreg.inc.sync.aligned.u32 232;");
    if (branch == 0) qkv_consumer<false>(sbase, smem_gen, s_red, cp, rt);
    else qkv_consumer<true>(sbase, smem_gen, s_red, cp, rt);
    if (threadIdx.x == 0) PROF_T(0, 11);
    __syncwarp();
    cluster_sync_relaxed();
    if (threadIdx.x == 0) { PROF_T(0, 12); PROF_G(0, 31); }
  }
}

constexpr int T_WA0 = KV_HEAD_BYTES;
constexpr int T_S0 = T_WA0 + 32768;
constexpr int K2_BAR = T_S0 + 32768;
constexpr int T_WA1 = 0;
constexpr int T_WB = 32768;
constexpr int T_S2 = 98304;
constexpr int K2_SMEM = K2_BAR + 256 + 1024;

#define ATT_NPOLY 18
#define ATT_CH 8
#define ATT_D 1
#define PRO_MODE 1
#define STAGGER 0
#define K2_WARM 0
#define K2_FIRST 2
#define CONST_SMID 0
#define ATT_STRUCT 1
#define ATT_PIN 0
#define ATT_GM 1
#define ATT_DEG 2
struct ExpC {
  uint32_t k3c00, kmask, seven, c3;
};
__device__ __forceinline__ uint32_t hfma2(uint32_t a, uint32_t b, uint32_t c) {
  uint32_t r;
  asm("fma.rn.f16x2 %0, %1, %2, %3;" : "=r"(r) : "r"(a), "r"(b), "r"(c));
  return r;
}
__device__ __forceinline__ uint32_t exp2_poly_pair(float t0, float t1, const ExpC& c) {
  uint32_t u;
  asm("prmt.b32 %0, %1, %2, 0x5410;" : "=r"(u) : "r"(__float_as_uint(t0)), "r"(__float_as_uint(t1)));
  uint32_t m;
  asm("lop3.b32 %0, %1, 0x03FF03FF, %2, 0xEA;" : "=r"(m) : "r"(u), "r"(c.k3c00));
  uint32_t p = hfma2(m, c.c3, 0xa385a385u);
  p = hfma2(p, m, 0x4ad64ad7u);
  uint32_t mu;
  asm("lop3.b32 %0, %1, 0xFC00FC00, %2, 0xEA;" : "=r"(mu) : "r"(u), "r"(c.kmask));
  uint32_t r;
  asm("{.reg .b32 t; shf.r.wrap.b32 t, %1, %2, 3; add.u32 %0, t, %3;}" : "=r"(r) : "r"(mu), "r"(c.seven), "r"(p));
  return r;
}
__device__ __forceinline__ float gadd(float x, float M, uint32_t g) {
  float r = x;
  asm("{.reg .pred p; setp.ne.b32 p, %2, -1; @p add.f32 %0, %0, %1;}" : "+f"(r) : "f"(M), "r"(g));
  return r;
}
__device__ __forceinline__ float gex2(float x, uint32_t g) {
  float r = x;
  asm("{.reg .pred p; setp.ne.b32 p, %1, -1; @p ex2.approx.ftz.f32 %0, %0;}" : "+f"(r) : "r"(g));
  return r;
}
template <int NPOLY, int NPAIR, int CH, int D, bool G0 = false>
__device__ __forceinline__ void exp_tile(const float (&s)[2 * NPAIR], uint32_t (&p)[NPAIR], const ExpC& c, uint32_t g0 = 0) {
#pragma unroll
  for (int i = 0; i < NPAIR; i++) {
    const bool isPoly = ((i + 1) * NPOLY / 32) != (i * NPOLY / 32);
    const int ch = i / CH;
    const bool gated = ch >= D || G0;
    int gi = (ch - D) * CH + CH - 1;
    if (ch >= D) {
      while (gi > (ch - D) * CH && !(((gi + 1) * NPOLY / 32) != (gi * NPOLY / 32))) gi--;
    }
    const uint32_t g = ch >= D ? p[gi] : g0;
    if (!isPoly) {
      if (gated && ATT_GM) p[i] = pack_bf16(gex2(s[2 * i], g), gex2(s[2 * i + 1], g));
      else p[i] = pack_bf16(ex2f(s[2 * i]), ex2f(s[2 * i + 1]));
    } else {
      if (gated) p[i] = exp2_poly_pair(gadd(s[2 * i], 12329.f, g), gadd(s[2 * i + 1], 12329.f, g), c);
      else p[i] = exp2_poly_pair(s[2 * i] + 12329.f, s[2 * i + 1] + 12329.f, c);
    }
  }
}

__device__ __forceinline__ void store_o(__nv_bfloat16* o, int row0, int head, int lane, const uint32_t (&r)[4]) {
  const int g = lane >> 2, t = lane & 3;
  uint32_t* p0 = reinterpret_cast<uint32_t*>(o + (size_t)(row0 + g) * DM + head * 16) + t;
  uint32_t* p1 = reinterpret_cast<uint32_t*>(o + (size_t)(row0 + g + 8) * DM + head * 16) + t;
  p0[0] = r[0];
  p1[0] = r[1];
  p0[4] = r[2];
  p1[4] = r[3];
}

__device__ __forceinline__ void kv_fetch_piece(uint32_t sbase, uint32_t bar, int piece) {
  const uint8_t* img = reinterpret_cast<const uint8_t*>(g_kv) + (size_t)(blockIdx.x >> 2) * KV_HEAD_BYTES;
  const int g = piece >> 1, isv = piece & 1;
  const int e0 = g == 0 ? 0 : (isv ? 256 : 320) + (g - 1) * 512;
  const int e1 = g == 3 ? 2048 : (isv ? 256 : 320) + g * 512;
  const int bytes = (e1 - e0) * (isv ? 48 : 32);
  const int off = isv ? KV_K_BYTES + e0 * 48 : e0 * 32;
  mbar_expect_tx(bar + 8 * g, bytes);
  bulk_load(sbase + off, img + off, bytes, bar + 8 * g);
}

__device__ __forceinline__ void safe_exp(const float (&s)[32], uint32_t (&p)[16], float (&o)[12], float& m0, float& m1) {
  float x0 = s[0], x1 = s[2];
#pragma unroll
  for (int i = 0; i < 8; i++) {
    x0 = fmaxf(x0, fmaxf(s[4 * i], s[4 * i + 1]));
    x1 = fmaxf(x1, fmaxf(s[4 * i + 2], s[4 * i + 3]));
  }
  x0 = fmaxf(x0, __shfl_xor_sync(0xffffffffu, x0, 1));
  x1 = fmaxf(x1, __shfl_xor_sync(0xffffffffu, x1, 1));
  x0 = fmaxf(x0, __shfl_xor_sync(0xffffffffu, x0, 2));
  x1 = fmaxf(x1, __shfl_xor_sync(0xffffffffu, x1, 2));
  const float n0 = fmaxf(m0, x0), n1 = fmaxf(m1, x1);
  const float c0 = ex2f(m0 - n0), c1 = ex2f(m1 - n1);
  m0 = n0;
  m1 = n1;
#pragma unroll
  for (int i = 0; i < 3; i++) {
    o[4 * i] *= c0;
    o[4 * i + 1] *= c0;
    o[4 * i + 2] *= c1;
    o[4 * i + 3] *= c1;
  }
#pragma unroll
  for (int i = 0; i < 8; i++) {
    p[2 * i] = pack_bf16(ex2f(s[4 * i] - n0), ex2f(s[4 * i + 1] - n0));
    p[2 * i + 1] = pack_bf16(ex2f(s[4 * i + 2] - n1), ex2f(s[4 * i + 3] - n1));
  }
}

__device__ __forceinline__ void attn_step(float (&sx)[32], float (&sy)[32], float (&o)[12], const uint4& qf, uint64_t dK, uint64_t dV,
                                          const ExpC& ec) {
  uint32_t pa[16], pb[16];
  wg_fence();
  wgmma_rs_n64_z(sy, qf.x, qf.y, qf.z, qf.w, dK + 128);
  wg_commit();
  exp_tile<ATT_NPOLY, 16, ATT_CH, ATT_D>(sx, pa, ec);
  wg_fence();
  wgmma_rs_n24_tb(o, pa[12], pa[13], pa[14], pa[15], dV + 3 * 48, 1);
  wg_commit();
  wg_wait<1>();
  fence_regs(sy);
  exp_tile<ATT_NPOLY, 16, ATT_CH, ATT_D>(sy, pb, ec);
  wg_fence();
#pragma unroll
  for (int k = 0; k < 3; k++) wgmma_rs_n24_tb(o, pa[4 * k], pa[4 * k + 1], pa[4 * k + 2], pa[4 * k + 3], dV + k * 48, 1);
#pragma unroll
  for (int k = 0; k < 4; k++) wgmma_rs_n24_tb(o, pb[4 * k], pb[4 * k + 1], pb[4 * k + 2], pb[4 * k + 3], dV + (4 + k) * 48, 1);
  wgmma_rs_n64_z(sy, qf.x, qf.y, qf.z, qf.w, dK + 256);
  wg_commit();
  wg_wait<0>();
  fence_regs(sy);
}

template <bool SAFE>
__device__ __forceinline__ void attn_tile(uint64_t dK, uint64_t dV, uint32_t bar, const uint4 qf, const ExpC& ec, uint32_t (&outp)[4],
                                          bool warm) {
  float o[12];
#pragma unroll
  for (int i = 0; i < 12; i++) asm volatile("mov.f32 %0, 0f00000000;" : "=f"(o[i]));
  if (!warm) mbar_wait(bar, 0);
  if (!SAFE) {
    float s0[32], s1[32];
    wg_fence();
    wgmma_rs_n64_z(s0, qf.x, qf.y, qf.z, qf.w, dK);
    wg_commit();
    wg_wait<0>();
    fence_regs(s0);
#pragma unroll 1
    for (int p = warm ? 7 : 0; p < 8; p++) {
      if ((p & 1) && !warm) mbar_wait(bar + 8 * min((p + 1) >> 1, 3), 0);
      attn_step(s0, s1, o, qf, dK, dV, ec);
      attn_step(s1, s0, o, qf, dK + 256, dV + 384, ec);
      dK += 512;
      dV += 768;
    }
  } else {
    float m0 = -INFINITY, m1 = -INFINITY;
#pragma unroll 1
    for (int j = 0; j < 32; j++) {
      if (j == 4) { mbar_wait(bar + 8, 0); mbar_wait(bar + 16, 0); mbar_wait(bar + 24, 0); }
      float s[32];
      uint32_t p[16];
      wg_fence();
      wgmma_rs_n64_z(s, qf.x, qf.y, qf.z, qf.w, dK);
      wg_commit();
      wg_wait<0>();
      fence_regs(s);
      safe_exp(s, p, o, m0, m1);
      wg_fence();
#pragma unroll
      for (int k = 0; k < 4; k++) wgmma_rs_n24_tb(o, p[4 * k], p[4 * k + 1], p[4 * k + 2], p[4 * k + 3], dV + k * 48, 1);
      wg_commit();
      wg_wait<0>();
      fence_regs(o);
      dK += 128;
      dV += 192;
    }
  }
  fence_regs(o);
  const float r0 = 1.0f / o[8], r1 = 1.0f / o[10];
  outp[0] = pack_bf16(o[0] * r0, o[1] * r0);
  outp[1] = pack_bf16(o[2] * r1, o[3] * r1);
  outp[2] = pack_bf16(o[4] * r0, o[5] * r0);
  outp[3] = pack_bf16(o[6] * r1, o[7] * r1);
}

__device__ __forceinline__ void linear_attn_cta(uint8_t* smem_raw, uint32_t sbase, const CUtensorMap* mo16, int cta) {
  const int warp = threadIdx.x >> 5, lane = threadIdx.x & 31;
  const int hg = warp & 1;
  const uint4* qp = g_qfrag + (size_t)(NH + cta * 8 + hg * 4) * 32 * 128 + lane;
  auto qaddr = [&](int i) {
    const int blk16 = i * 8 + (warp >> 1);
    return qp + (blk16 >> 2) * 128 + (blk16 & 3) * 32;
  };
  uint4 q[4];
#pragma unroll
  for (int h = 0; h < 4; h++) q[h] = qaddr(0)[h * 32 * 128];
  float* red = reinterpret_cast<float*>(smem_raw + (sbase - smem_u32(smem_raw)) + 131072);
  {
    const float* src = g_kvpart + (size_t)cta * 8 * 384;
    float sum[6];
#pragma unroll
    for (int i = 0; i < 6; i++) sum[i] = 0.f;
#pragma unroll
    for (int r = 0; r < 16; r++) {
#pragma unroll
      for (int i = 0; i < 6; i++) sum[i] += src[(size_t)r * NH * 384 + threadIdx.x + i * 512];
    }
#pragma unroll
    for (int i = 0; i < 6; i++) red[threadIdx.x + i * 512] = round_bf16(sum[i]);
  }
  __syncthreads();
  uint32_t bf[4][6];
  {
    const int g = lane >> 2, t = lane & 3;
#pragma unroll
    for (int h = 0; h < 4; h++) {
#pragma unroll
      for (int f = 0; f < 6; f++) {
        const int blk = f >> 1, half = f & 1;
        const int e = (blk == 2) ? 0 : g;
        const int d = 2 * t + 8 * half;
        const int base = (hg * 4 + h) * 384 + (blk * 4 + half * 2 + (e & 1)) * 32 + (e >> 1);
        bf[h][f] = pack_bf16(red[base + (d & 7) * 4], red[base + ((d + 1) & 7) * 4]);
      }
    }
  }
  const uint32_t stg = sbase + warp * 4096;
#pragma unroll 1
  for (int i = 0; i < 16; i++) {
    uint4 qc[4];
#pragma unroll
    for (int h = 0; h < 4; h++) qc[h] = q[h];
    if (i + 1 < 16) {
#pragma unroll
      for (int h = 0; h < 4; h++) q[h] = qaddr(i + 1)[h * 32 * 128];
    }
    const uint32_t buf = stg + (i & 1) * 2048;
    if (i >= 2) {
      if (lane == 0) asm volatile("cp.async.bulk.wait_group.read 1;" ::: "memory");
      __syncwarp();
    }
#pragma unroll
    for (int h = 0; h < 4; h++) {
      float n0[4] = {0, 0, 0, 0}, n1[4] = {0, 0, 0, 0}, dn[4] = {0, 0, 0, 0};
      hmma(n0, qc[h].x, qc[h].y, qc[h].z, qc[h].w, bf[h][0], bf[h][1]);
      hmma(n1, qc[h].x, qc[h].y, qc[h].z, qc[h].w, bf[h][2], bf[h][3]);
      hmma(dn, qc[h].x, qc[h].y, qc[h].z, qc[h].w, bf[h][4], bf[h][5]);
      const float d0 = round_bf16(round_bf16(dn[0]) + 1e-6f), d1 = round_bf16(round_bf16(dn[2]) + 1e-6f);
      const uint32_t r0 = pack_bf16(__fdividef(round_bf16(n0[0]), d0), __fdividef(round_bf16(n0[1]), d0));
      const uint32_t r1 = pack_bf16(__fdividef(round_bf16(n0[2]), d1), __fdividef(round_bf16(n0[3]), d1));
      const uint32_t r2 = pack_bf16(__fdividef(round_bf16(n1[0]), d0), __fdividef(round_bf16(n1[1]), d0));
      const uint32_t r3 = pack_bf16(__fdividef(round_bf16(n1[2]), d1), __fdividef(round_bf16(n1[3]), d1));
      const int row = lane & 15;
      const int chunk = h * 2 + (lane >> 4);
      const uint32_t addr = buf + row * 128 + ((chunk ^ (row & 7)) << 4);
      asm volatile("stmatrix.sync.aligned.m8n8.x4.shared.b16 [%0], {%1,%2,%3,%4};" ::"r"(addr), "r"(r0), "r"(r1), "r"(r2), "r"(r3)
                   : "memory");
    }
    fence_proxy_async();
    __syncwarp();
    if (lane == 0) {
      tma_store_2d(mo16, buf, cta * 128 + hg * 64, (i * 8 + (warp >> 1)) * 16);
      asm volatile("cp.async.bulk.commit_group;" ::: "memory");
    }
  }
  if (lane == 0) {
    asm volatile("cp.async.bulk.wait_group 0;" ::: "memory");
    fence_proxy_async_all();
  }
  __syncthreads();
  if (threadIdx.x == 0) flag_arrive(&g_sync[4]);
}

__device__ __forceinline__ uint32_t tail_stage(uint32_t sbase, int s) { return sbase + (s < 2 ? T_S0 + s * 16384 : T_S2 + (s - 2) * 16384); }

__device__ __forceinline__ void tail_consumer(uint32_t sbase, const CUtensorMap* mout, int rt, int ct) {
  const uint32_t tb = sbase + K2_BAR + 96;
  const int wg = threadIdx.x >> 7, warp = (threadIdx.x >> 5) & 3, lane = threadIdx.x & 31;
#pragma unroll 1
  for (int tile = 0; tile < 2; tile++) {
    float acc[32];
#pragma unroll 1
    for (int kb = 0; kb < 8; kb++) {
      const int g = tile * 8 + kb;
      const int s = g % 6;
      if (g == 0) mbar_wait(tb + 96, 0);
      if (g == 4) mbar_wait(tb + 104, 0);
      if (g == 8) mbar_wait(tb + 112, 0);
      mbar_wait(tb + 8 * s, (g / 6) & 1);
      if (threadIdx.x == 0) PROF_T(2, 1 + (g >> 1));
      const uint32_t wa = sbase + (tile ? T_WB + kb * 8192 : (kb < 4 ? T_WA0 + kb * 8192 : T_WA1 + (kb - 4) * 8192));
      const uint64_t dA = mkdesc(tail_stage(sbase, s) + wg * 8192, 16, 1024, 1);
      const uint64_t dB = mkdesc(wa, 8192, 1024, 1);
      wg_fence();
#pragma unroll
      for (int k = 0; k < 4; k++) wgmma_ss_n64_tb(acc, dA + k * 2, dB + k * 128, (kb | k) != 0);
      wg_commit();
      if (kb > 0) {
        wg_wait<1>();
        if ((threadIdx.x & 127) == 0) mbar_arrive(tb + 48 + 8 * ((g - 1) % 6));
      }
    }
    wg_wait<0>();
    if ((threadIdx.x & 127) == 0) mbar_arrive(tb + 48 + 8 * ((tile * 8 + 7) % 6));
    fence_regs(acc);
    if (tile == 0) asm volatile("bar.sync 3, 256;" ::: "memory");
    const uint32_t stg = sbase + T_WA0 + tile * 16384 + wg * 8192;
    const int rloc = warp * 16 + (lane & 15);
#pragma unroll
    for (int c16 = 0; c16 < 4; c16++) {
      const float* a = &acc[c16 * 8];
      const uint32_t r0 = pack_bf16(a[0], a[1]), r1 = pack_bf16(a[2], a[3]), r2 = pack_bf16(a[4], a[5]), r3 = pack_bf16(a[6], a[7]);
      const int chunk = c16 * 2 + (lane >> 4);
      const uint32_t addr = stg + rloc * 128 + ((chunk ^ (rloc & 7)) << 4);
      asm volatile("stmatrix.sync.aligned.m8n8.x4.shared.b16 [%0], {%1,%2,%3,%4};" ::"r"(addr), "r"(r0), "r"(r1), "r"(r2), "r"(r3)
                   : "memory");
    }
    fence_proxy_async();
    asm volatile("bar.sync %0, 128;" ::"r"(4 + wg) : "memory");
    if ((threadIdx.x & 127) == 0) {
      tma_store_2d(mout, stg, tile * DM + ct * 64, rt * 128 + wg * 64);
      asm volatile("cp.async.bulk.commit_group;" ::: "memory");
    }
  }
  if ((threadIdx.x & 127) == 0) asm volatile("cp.async.bulk.wait_group.read 0;" ::: "memory");
}

__device__ __forceinline__ void tail_producer_local(uint32_t sbase, const CUtensorMap* mo, const CUtensorMap* mwA, const CUtensorMap* mwB,
                                                    int rt, int ct) {
  const uint32_t tb = sbase + K2_BAR + 96;
  for (int g = 2; g < 6; g++) {
    if (g == 4) {
      mbar_expect_tx(tb + 104, 32768);
      for (int kb = 4; kb < 8; kb++) tma_load_2d(sbase + T_WA1 + (kb - 4) * 8192, mwA, ct * 64, kb * 64, tb + 104);
    }
    mbar_expect_tx(tb + 8 * g, 16384);
    tma_load_2d(tail_stage(sbase, g), mo, g * 64, rt * 128, tb + 8 * g);
  }
  mbar_expect_tx(tb + 112, 65536);
  for (int kb = 0; kb < 8; kb++) tma_load_2d(sbase + T_WB + kb * 8192, mwB, ct * 64, kb * 64, tb + 112);
  for (int g = 6; g < 8; g++) {
    mbar_wait(tb + 48 + 8 * (g % 6), 0);
    mbar_expect_tx(tb + 8 * (g % 6), 16384);
    tma_load_2d(tail_stage(sbase, g % 6), mo, g * 64, rt * 128, tb + 8 * (g % 6));
  }
}
__device__ __forceinline__ void tail_producer_grid(uint32_t sbase, const CUtensorMap* mo, int rt, int qb) {
  const uint32_t tb = sbase + K2_BAR + 96;
  flag_arrive(&g_sync[qb]);
  flag_wait(&g_sync[qb], 32);
  fence_proxy_async_all();
  for (int g = 8; g < 16; g++) {
    const int s = g % 6;
    mbar_wait(tb + 48 + 8 * s, ((g / 6) - 1) & 1);
    mbar_expect_tx(tb + 8 * s, 16384);
    tma_load_2d(tail_stage(sbase, s), mo, (g & 7) * 64, S_LEN + rt * 128, tb + 8 * s);
  }
}

__global__ void __launch_bounds__(512, 1)
attn_kernel(const __grid_constant__ CUtensorMap mo16, const __grid_constant__ CUtensorMap mo, const __grid_constant__ CUtensorMap mwA,
            const __grid_constant__ CUtensorMap mwB, const __grid_constant__ CUtensorMap mout, const uint8_t* __restrict__ woA,
            const uint8_t* __restrict__ woB) {
  extern __shared__ uint8_t smem_raw[];
  const uint32_t sbase = (smem_u32(smem_raw) + 1023) & ~1023u;
  const uint32_t bar = sbase + K2_BAR;
  if (threadIdx.x == 0) { PROF_G(1, 30); PROF_T(1, 0); PROF_T(2, 0); }
  if (threadIdx.x == 0) {
    for (int i = 0; i < 4; i++) mbar_init(bar + 8 * i, 2);
    for (int i = 0; i < 6; i++) {
      mbar_init(bar + 96 + 8 * i, 1);
      mbar_init(bar + 96 + 48 + 8 * i, 2);
    }
    for (int i = 0; i < 3; i++) mbar_init(bar + 96 + 96 + 8 * i, 1);
    asm volatile("st.shared.v4.u32 [%0], {%1, %2, %3, %4};" ::"r"(bar + 64), "r"(0x3C003C00u), "r"(0x00070000u), "r"(7u),
                 "r"(ATT_DEG == 3 ? 0x2cfd2cfdu : 0x35623562u)
                 : "memory");
    fence_barrier_init();
    fence_proxy_async();
  }
  __syncthreads();
  if (blockIdx.x >= 128) {
    if (threadIdx.x < 16) {
      const int i = (blockIdx.x - 128) * 16 + threadIdx.x;
      const uint8_t* p = (i < 32 ? woA : woB) + (size_t)(i & 31) * 16384;
      asm volatile("cp.async.bulk.prefetch.L2.global [%0], %1;" ::"l"(p), "r"(16384) : "memory");
    }
    pdl_wait();
    linear_attn_cta(smem_raw, sbase, &mo16, blockIdx.x - 128);
    if (threadIdx.x == 0) { PROF_T(1, 5); PROF_G(1, 31); }
    return;
  }
  const int head = blockIdx.x >> 2, qb = blockIdx.x & 3;
  const int lane = threadIdx.x & 31;
  const int wg = __shfl_sync(0xffffffffu, threadIdx.x >> 7, 0), warp = __shfl_sync(0xffffffffu, (threadIdx.x >> 5) & 3, 0);
  const int ort = qb * 4 + ((blockIdx.x >> 2) & 3), oct = blockIdx.x >> 4;
  ExpC ec;
  asm volatile("ld.volatile.shared.v4.u32 {%0, %1, %2, %3}, [%4];" : "=r"(ec.k3c00), "=r"(ec.kmask), "=r"(ec.seven), "=r"(ec.c3) : "r"(bar + 64));
  const uint64_t dK = mkdesc(sbase, 128, 256, 0);
  const uint64_t dV = mkdesc(sbase + KV_K_BYTES, 384, 128, 0);
  pdl_wait();
  if (threadIdx.x == 0) { PROF_T(1, 7); PROF_G(1, 29); }
  if (threadIdx.x == 0) {
#pragma unroll
    for (int piece = 0; piece < 8; piece++) kv_fetch_piece(sbase, bar, piece);
    mbar_expect_tx(bar + 96 + 96, 32768);
    for (int kb = 0; kb < 4; kb++) tma_load_2d(sbase + T_WA0 + kb * 8192, &mwA, oct * 64, kb * 64, bar + 96 + 96);
  }
  uint4 qnext = g_qfrag[(head * 32 + qb * 8 + wg * 2) * 128 + (threadIdx.x & 127)];
  bool safe_path;
  {
    float4 n = make_float4(0.f, 0.f, 0.f, 0.f);
    if (lane < 16) n = *reinterpret_cast<const float4*>(&g_nrm[(head * 16 + lane) * 4]);
    uint32_t qm = ((lane >> 2) == qb) ? __float_as_uint(n.x) : 0u;
    qm = __reduce_max_sync(0xffffffffu, qm);
    const uint32_t km = __reduce_max_sync(0xffffffffu, __float_as_uint(n.y));
    const uint32_t vm = __reduce_max_sync(0xffffffffu, __float_as_uint(n.z));
    const float b2 = __uint_as_float(qm) * (QSCALE * QSCALE) * __uint_as_float(km) * 1.02f;
    const float vmax = __uint_as_float(vm);
    const bool ok = (b2 <= 21.5f * 21.5f) && (vmax <= 1.0e24f) && (vmax >= 1.0e-18f || vmax == 0.f);
    safe_path = !ok;
  }
#pragma unroll 1
  for (int t = 0; t < 2; t++) {
    const int tile64 = qb * 8 + wg * 2 + t;
    const uint4 qf = qnext;
    if (t == 0) qnext = g_qfrag[(head * 32 + tile64 + 1) * 128 + (threadIdx.x & 127)];
    if (t == 1 && wg == 3) {
      if (threadIdx.x == 384) PROF_T(1, 8);
      flag_wait(&g_sync[4], 4);
      if (threadIdx.x == 384) PROF_T(1, 9);
      if (warp == 0 && lane == 0) {
        fence_proxy_async_all();
        for (int g = 0; g < 2; g++) {
          mbar_expect_tx(bar + 96 + 8 * g, 16384);
          tma_load_2d(tail_stage(sbase, g), &mo, g * 64, ort * 128, bar + 96 + 8 * g);
        }
      }
    }
    uint32_t r[4];
    if (threadIdx.x == 0) PROF_T(1, 1 + t);
    if (!safe_path) attn_tile<false>(dK, dV, bar, qf, ec, r, false);
    else attn_tile<true>(dK, dV, bar, qf, ec, r, false);
    store_o(g_o + (size_t)S_LEN * DM, tile64 * 64 + warp * 16, head, lane, r);
  }
  if (threadIdx.x == 0) PROF_T(1, 5);
  if (threadIdx.x == 384) PROF_T(1, 10);
  fence_proxy_async_all();
  if (threadIdx.x == 384) PROF_T(1, 11);
  if (wg == 2 && warp < 2) {
    asm volatile("bar.sync 2, 512;" ::: "memory");
    if (threadIdx.x == 256) PROF_T(1, 12);
    if (lane == 0) {
      if (warp == 0) tail_producer_grid(sbase, &mo, ort, qb);
      else tail_producer_local(sbase, &mo, &mwA, &mwB, ort, oct);
    }
  } else {
    asm volatile("bar.arrive 2, 512;" ::: "memory");
    if (wg < 2) tail_consumer(sbase, &mout, ort, oct);
  }
  if (threadIdx.x == 0) { PROF_T(2, 12); PROF_G(1, 31); }
}

typedef CUresult (*EncodeFn)(CUtensorMap*, CUtensorMapDataType, cuuint32_t, void*, const cuuint64_t*, const cuuint64_t*,
                             const cuuint32_t*, const cuuint32_t*, CUtensorMapInterleave, CUtensorMapSwizzle,
                             CUtensorMapL2promotion, CUtensorMapFloatOOBfill);

void make_map(EncodeFn enc, CUtensorMap* m, const void* ptr, uint64_t inner, uint64_t outer, uint32_t box_inner, uint32_t box_outer) {
  cuuint64_t dims[2] = {inner, outer};
  cuuint64_t strides[1] = {inner * 2};
  cuuint32_t box[2] = {box_inner, box_outer};
  cuuint32_t es[2] = {1, 1};
  enc(m, CU_TENSOR_MAP_DATA_TYPE_BFLOAT16, 2, const_cast<void*>(ptr), dims, strides, box, es, CU_TENSOR_MAP_INTERLEAVE_NONE,
      CU_TENSOR_MAP_SWIZZLE_128B, CU_TENSOR_MAP_L2_PROMOTION_L2_256B, CU_TENSOR_MAP_FLOAT_OOB_FILL_NONE);
}

struct HostState {
  bool init;
  const void* key[7];
  CUtensorMap mxA, mxB, mwA, mwB, mo, mo16, mwoA, mwoB, mout;
};
HostState g_hs;

}

extern "C" void kernel_launch(void* const* d_in, const int* in_sizes, int n_in, void* d_out, int out_size) {
  (void)in_sizes; (void)n_in; (void)out_size;
  HostState& hs = g_hs;
  bool same = hs.init && hs.key[6] == d_out;
  for (int i = 0; i < 6 && same; i++) same = hs.key[i] == d_in[i];
  if (!same) {
    void* fn = nullptr;
    cudaDriverEntryPointQueryResult qr;
    cudaGetDriverEntryPoint("cuTensorMapEncodeTiled", &fn, cudaEnableDefault, &qr);
    EncodeFn enc = (EncodeFn)fn;
    void* go = nullptr;
    cudaGetSymbolAddress(&go, g_o);
    make_map(enc, &hs.mxA, d_in[0], 512, 2048, 64, 128);
    make_map(enc, &hs.mwA, d_in[1], 1536, 512, 64, 32);
    make_map(enc, &hs.mwoA, d_in[2], 512, 512, 64, 64);
    make_map(enc, &hs.mxB, d_in[3], 512, 2048, 64, 128);
    make_map(enc, &hs.mwB, d_in[4], 1536, 512, 64, 32);
    make_map(enc, &hs.mwoB, d_in[5], 512, 512, 64, 64);
    make_map(enc, &hs.mo, go, 512, 4096, 64, 128);
    make_map(enc, &hs.mo16, go, 512, 4096, 64, 16);
    make_map(enc, &hs.mout, d_out, 1024, 2048, 64, 64);
    cudaFuncSetAttribute(qkv_gemm_kernel, cudaFuncAttributeMaxDynamicSharedMemorySize, K1_SMEM);
    cudaFuncSetAttribute(attn_kernel, cudaFuncAttributeMaxDynamicSharedMemorySize, K2_SMEM);
    for (int i = 0; i < 6; i++) hs.key[i] = d_in[i];
    hs.key[6] = d_out;
    hs.init = true;
  }
  cudaStream_t st = cudaStreamPerThread;
  {
    cudaLaunchConfig_t cfg = {};
    cfg.gridDim = dim3(128);
    cfg.blockDim = dim3(384);
    cfg.dynamicSmemBytes = K1_SMEM;
    cfg.stream = st;
    cudaLaunchAttribute at[1];
    at[0].id = cudaLaunchAttributeClusterDimension;
    at[0].val.clusterDim.x = 2;
    at[0].val.clusterDim.y = 1;
    at[0].val.clusterDim.z = 1;
    cfg.attrs = at;
    cfg.numAttrs = 1;
    cudaLaunchKernelEx(&cfg, qkv_gemm_kernel, hs.mxA, hs.mxB, hs.mwA, hs.mwB);
  }
  {
    cudaLaunchConfig_t cfg = {};
    cfg.gridDim = dim3(132);
    cfg.blockDim = dim3(512);
    cfg.dynamicSmemBytes = K2_SMEM;
    cfg.stream = st;
    cudaLaunchAttribute at[1];
    at[0].id = cudaLaunchAttributeProgrammaticStreamSerialization;
    at[0].val.programmaticStreamSerializationAllowed = 1;
    cfg.attrs = at;
    cfg.numAttrs = 1;
    cudaLaunchKernelEx(&cfg, attn_kernel, hs.mo16, hs.mo, hs.mwoA, hs.mwoB, hs.mout, (const uint8_t*)d_in[2], (const uint8_t*)d_in[5]);
  }
}
```

```cpp
#include <cuda_runtime.h>
#include <cuda_bf16.h>
#include <cuda.h>
#include <stdint.h>

namespace {

constexpr int S_LEN = 2048;
constexpr int DM = 512;
constexpr int NH = 32;

constexpr int KV_K_BYTES = 65536;
constexpr int KV_HEAD_BYTES = KV_K_BYTES + 98304;
__device__ uint4 g_qfrag[2 * NH * 32 * 128];
__device__ uint4 g_kv[NH * KV_HEAD_BYTES / 16];
__device__ float g_kvpart[16 * NH * 384];
__device__ float g_nrm[NH * 16 * 4];
__device__ uint32_t g_sync[8];
__device__ __nv_bfloat16 g_o[2 * S_LEN * DM];

#define g_prof_set(k, i, v)
#define g_prof_dummy(i) true
#define PROF_T(k, i) do {} while (0)
#define PROF_G(k, i) do {} while (0)
__device__ __forceinline__ uint32_t smem_u32(const void* p) { return (uint32_t)__cvta_generic_to_shared(p); }
__device__ __forceinline__ void mbar_init(uint32_t bar, int cnt) {
  asm volatile("mbarrier.init.shared::cta.b64 [%0], %1;" ::"r"(bar), "r"(cnt) : "memory");
}
__device__ __forceinline__ void mbar_expect_tx(uint32_t bar, uint32_t bytes) {
  asm volatile("mbarrier.arrive.expect_tx.shared::cta.b64 _, [%0], %1;" ::"r"(bar), "r"(bytes) : "memory");
}
__device__ __forceinline__ void mbar_arrive(uint32_t bar) {
  asm volatile("mbarrier.arrive.shared::cta.b64 _, [%0];" ::"r"(bar) : "memory");
}
__device__ __forceinline__ void mbar_arrive_cluster(uint32_t bar, uint32_t cta) {
  asm volatile(
      "{\n.reg .b32 ra;\nmapa.shared::cluster.u32 ra, %0, %1;\n"
      "mbarrier.arrive.shared::cluster.b64 _, [ra];\n}" ::"r"(bar), "r"(cta) : "memory");
}
__device__ __forceinline__ void mbar_wait(uint32_t bar, uint32_t parity) {
  asm volatile(
      "{\n.reg .pred p;\n.reg .u32 n;\n"
      "mov.u32 n, 0;\n"
      "WAIT_LOOP:\n"
      "mbarrier.try_wait.parity.shared::cta.b64 p, [%0], %1, 0x400000;\n"
      "@p bra WAIT_DONE;\n"
      "add.u32 n, n, 1;\n"
      "setp.lt.u32 p, n, 4000000;\n"
      "@p bra WAIT_LOOP;\n"
      "trap;\n"
      "WAIT_DONE:\n}" ::"r"(bar), "r"(parity) : "memory");
}
__device__ __forceinline__ void fence_barrier_init() {
  asm volatile("fence.mbarrier_init.release.cluster;" ::: "memory");
}
__device__ __forceinline__ void fence_proxy_async() { asm volatile("fence.proxy.async.shared::cta;" ::: "memory"); }
__device__ __forceinline__ void cluster_sync_relaxed() {
  asm volatile("barrier.cluster.arrive.relaxed.aligned;\nbarrier.cluster.wait.aligned;" ::: "memory");
}
__device__ __forceinline__ void tma_load_2d(uint32_t dst, const CUtensorMap* m, int x, int y, uint32_t bar) {
  asm volatile(
      "cp.async.bulk.tensor.2d.shared::cluster.global.mbarrier::complete_tx::bytes [%0], [%1, {%3, %4}], [%2];" ::"r"(dst),
      "l"(m), "r"(bar), "r"(x), "r"(y)
      : "memory");
}
__device__ __forceinline__ void tma_load_2d_mc(uint32_t dst, const CUtensorMap* m, int x, int y, uint32_t bar, uint16_t mask) {
  asm volatile(
      "cp.async.bulk.tensor.2d.shared::cluster.global.mbarrier::complete_tx::bytes.multicast::cluster [%0], [%1, {%3, %4}], "
      "[%2], %5;" ::"r"(dst),
      "l"(m), "r"(bar), "r"(x), "r"(y), "h"(mask)
      : "memory");
}
__device__ __forceinline__ void tma_store_2d(const CUtensorMap* m, uint32_t src, int x, int y) {
  asm volatile("cp.async.bulk.tensor.2d.global.shared::cta.bulk_group [%0, {%2, %3}], [%1];" ::"l"(m), "r"(src), "r"(x),
               "r"(y)
               : "memory");
}
__device__ __forceinline__ void bulk_load(uint32_t dst, const void* src, uint32_t bytes, uint32_t bar) {
  asm volatile("cp.async.bulk.shared::cluster.global.mbarrier::complete_tx::bytes [%0], [%1], %2, [%3];" ::"r"(dst),
               "l"(src), "r"(bytes), "r"(bar)
               : "memory");
}
__device__ __forceinline__ void bulk_load_mc(uint32_t dst, const void* src, uint32_t bytes, uint32_t bar, uint16_t mask) {
  asm volatile("cp.async.bulk.shared::cluster.global.mbarrier::complete_tx::bytes.multicast::cluster [%0], [%1], %2, [%3], %4;" ::"r"(dst),
               "l"(src), "r"(bytes), "r"(bar), "h"(mask)
               : "memory");
}
__device__ __forceinline__ void flag_arrive(uint32_t* p) {
  asm volatile("red.release.gpu.global.add.u32 [%0], 1;" ::"l"(p) : "memory");
}
__device__ __forceinline__ void flag_wait(const uint32_t* p, uint32_t target) {
  asm volatile(
      "{\n.reg .pred p;\n.reg .u32 n, v;\n"
      "mov.u32 n, 0;\n"
      "FLAG_LOOP:\n"
      "ld.acquire.gpu.global.u32 v, [%0];\n"
      "setp.ge.u32 p, v, %1;\n"
      "@p bra FLAG_DONE;\n"
      "add.u32 n, n, 1;\n"
      "setp.lt.u32 p, n, 20000000;\n"
      "@p bra FLAG_LOOP;\n"
      "trap;\n"
      "FLAG_DONE:\n}" ::"l"(p), "r"(target) : "memory");
}
__device__ __forceinline__ void fence_proxy_async_all() { asm volatile("fence.proxy.async;" ::: "memory"); }
__device__ __forceinline__ void pdl_launch_dependents() { asm volatile("griddepcontrol.launch_dependents;" ::: "memory"); }
__device__ __forceinline__ void pdl_wait() { asm volatile("griddepcontrol.wait;" ::: "memory"); }
__device__ __forceinline__ void wg_fence() { asm volatile("wgmma.fence.sync.aligned;" ::: "memory"); }
__device__ __forceinline__ void wg_commit() { asm volatile("wgmma.commit_group.sync.aligned;" ::: "memory"); }
template <int N>
__device__ __forceinline__ void wg_wait() {
  asm volatile("wgmma.wait_group.sync.aligned %0;" ::"n"(N) : "memory");
}
template <int M>
__device__ __forceinline__ void fence_regs(float (&r)[M]) {
#pragma unroll
  for (int i = 0; i < M; i++) asm volatile("" : "+f"(r[i])::"memory");
}
__device__ __forceinline__ uint64_t mkdesc(uint32_t addr, uint32_t lbo, uint32_t sbo, uint32_t layout) {
  return (uint64_t)((addr & 0x3FFFF) >> 4) | ((uint64_t)(lbo >> 4) << 16) | ((uint64_t)(sbo >> 4) << 32) |
         ((uint64_t)layout << 62);
}
__device__ __forceinline__ uint32_t pack_bf16(float lo, float hi) {
  uint32_t r;
  asm("cvt.rn.bf16x2.f32 %0, %1, %2;" : "=r"(r) : "f"(hi), "f"(lo));
  return r;
}
__device__ __forceinline__ float bf_lo(uint32_t v) { return __uint_as_float(v << 16); }
__device__ __forceinline__ float bf_hi(uint32_t v) { return __uint_as_float(v & 0xFFFF0000u); }
__device__ __forceinline__ float round_bf16(float x) { return bf_lo(pack_bf16(x, 0.f)); }
__device__ __forceinline__ float ex2f(float x) {
  float y;
  asm("ex2.approx.ftz.f32 %0, %1;" : "=f"(y) : "f"(x));
  return y;
}

__device__ __forceinline__ void wgmma_rs_n24_tb(float (&d)[12], uint32_t a0, uint32_t a1, uint32_t a2, uint32_t a3, uint64_t descB, int scaleD) {
  asm volatile("{\n.reg .pred p;\nsetp.ne.b32 p, %17, 0;\n"
    "wgmma.mma_async.sync.aligned.m64n24k16.f32.bf16.bf16 "
    "{%0, %1, %2, %3, %4, %5, %6, %7, %8, %9, %10, %11}, {%12, %13, %14, %15}, %16, p, 1, 1, 1;\n}\n"
    : "+f"(d[0]), "+f"(d[1]), "+f"(d[2]), "+f"(d[3]), "+f"(d[4]), "+f"(d[5]), "+f"(d[6]), "+f"(d[7]),
      "+f"(d[8]), "+f"(d[9]), "+f"(d[10]), "+f"(d[11])
    : "r"(a0), "r"(a1), "r"(a2), "r"(a3), "l"(descB), "r"(scaleD));
}
__device__ __forceinline__ void wgmma_rs_n64_z(float (&d)[32], uint32_t a0, uint32_t a1, uint32_t a2, uint32_t a3, uint64_t descB) {
  asm volatile("{\n.reg .pred p;\nsetp.ne.b32 p, %37, 0;\n"
    "wgmma.mma_async.sync.aligned.m64n64k16.f32.bf16.bf16 "
    "{%0, %1, %2, %3, %4, %5, %6, %7, %8, %9, %10, %11, %12, %13, %14, %15, %16, %17, %18, %19, %20, %21, %22, %23, %24, %25, %26, %27, %28, %29, %30, %31}, {%32, %33, %34, %35}, %36, p, 1, 1, 0;\n}\n"
    : "=f"(d[0]), "=f"(d[1]), "=f"(d[2]), "=f"(d[3]), "=f"(d[4]), "=f"(d[5]), "=f"(d[6]), "=f"(d[7]),
      "=f"(d[8]), "=f"(d[9]), "=f"(d[10]), "=f"(d[11]), "=f"(d[12]), "=f"(d[13]), "=f"(d[14]), "=f"(d[15]),
      "=f"(d[16]), "=f"(d[17]), "=f"(d[18]), "=f"(d[19]), "=f"(d[20]), "=f"(d[21]), "=f"(d[22]), "=f"(d[23]),
      "=f"(d[24]), "=f"(d[25]), "=f"(d[26]), "=f"(d[27]), "=f"(d[28]), "=f"(d[29]), "=f"(d[30]), "=f"(d[31])
    : "r"(a0), "r"(a1), "r"(a2), "r"(a3), "l"(descB), "n"(0));
}
__device__ __forceinline__ void wgmma_ss_n192_tb(float (&d)[96], uint64_t descA, uint64_t descB, int scaleD) {
  asm volatile("{\n.reg .pred p;\nsetp.ne.b32 p, %98, 0;\n"
    "wgmma.mma_async.sync.aligned.m64n192k16.f32.bf16.bf16 "
    "{%0, %1, %2, %3, %4, %5, %6, %7, %8, %9, %10, %11, %12, %13, %14, %15, %16, %17, %18, %19, %20, %21, %22, %23, %24, %25, %26, %27, %28, %29, %30, %31, %32, %33, %34, %35, %36, %37, %38, %39, %40, %41, %42, %43, %44, %45, %46, %47, %48, %49, %50, %51, %52, %53, %54, %55, %56, %57, %58, %59, %60, %61, %62, %63, %64, %65, %66, %67, %68, %69, %70, %71, %72, %73, %74, %75, %76, %77, %78, %79, %80, %81, %82, %83, %84, %85, %86, %87, %88, %89, %90, %91, %92, %93, %94, %95}, %96, %97, p, 1, 1, 0, 1;\n}\n"
    : "+f"(d[0]), "+f"(d[1]), "+f"(d[2]), "+f"(d[3]), "+f"(d[4]), "+f"(d[5]), "+f"(d[6]), "+f"(d[7]),
      "+f"(d[8]), "+f"(d[9]), "+f"(d[10]), "+f"(d[11]), "+f"(d[12]), "+f"(d[13]), "+f"(d[14]), "+f"(d[15]),
      "+f"(d[16]), "+f"(d[17]), "+f"(d[18]), "+f"(d[19]), "+f"(d[20]), "+f"(d[21]), "+f"(d[22]), "+f"(d[23]),
      "+f"(d[24]), "+f"(d[25]), "+f"(d[26]), "+f"(d[27]), "+f"(d[28]), "+f"(d[29]), "+f"(d[30]), "+f"(d[31]),
      "+f"(d[32]), "+f"(d[33]), "+f"(d[34]), "+f"(d[35]), "+f"(d[36]), "+f"(d[37]), "+f"(d[38]), "+f"(d[39]),
      "+f"(d[40]), "+f"(d[41]), "+f"(d[42]), "+f"(d[43]), "+f"(d[44]), "+f"(d[45]), "+f"(d[46]), "+f"(d[47]),
      "+f"(d[48]), "+f"(d[49]), "+f"(d[50]), "+f"(d[51]), "+f"(d[52]), "+f"(d[53]), "+f"(d[54]), "+f"(d[55]),
      "+f"(d[56]), "+f"(d[57]), "+f"(d[58]), "+f"(d[59]), "+f"(d[60]), "+f"(d[61]), "+f"(d[62]), "+f"(d[63]),
      "+f"(d[64]), "+f"(d[65]), "+f"(d[66]), "+f"(d[67]), "+f"(d[68]), "+f"(d[69]), "+f"(d[70]), "+f"(d[71]),
      "+f"(d[72]), "+f"(d[73]), "+f"(d[74]), "+f"(d[75]), "+f"(d[76]), "+f"(d[77]), "+f"(d[78]), "+f"(d[79]),
      "+f"(d[80]), "+f"(d[81]), "+f"(d[82]), "+f"(d[83]), "+f"(d[84]), "+f"(d[85]), "+f"(d[86]), "+f"(d[87]),
      "+f"(d[88]), "+f"(d[89]), "+f"(d[90]), "+f"(d[91]), "+f"(d[92]), "+f"(d[93]), "+f"(d[94]), "+f"(d[95])
    : "l"(descA), "l"(descB), "r"(scaleD));
}
__device__ __forceinline__ void wgmma_ss_n64_tb(float (&d)[32], uint64_t descA, uint64_t descB, int scaleD) {
  asm volatile("{\n.reg .pred p;\nsetp.ne.b32 p, %34, 0;\n"
    "wgmma.mma_async.sync.aligned.m64n64k16.f32.bf16.bf16 "
    "{%0, %1, %2, %3, %4, %5, %6, %7, %8, %9, %10, %11, %12, %13, %14, %15, %16, %17, %18, %19, %20, %21, %22, %23, %24, %25, %26, %27, %28, %29, %30, %31}, %32, %33, p, 1, 1, 0, 1;\n}\n"
    : "+f"(d[0]), "+f"(d[1]), "+f"(d[2]), "+f"(d[3]), "+f"(d[4]), "+f"(d[5]), "+f"(d[6]), "+f"(d[7]),
      "+f"(d[8]), "+f"(d[9]), "+f"(d[10]), "+f"(d[11]), "+f"(d[12]), "+f"(d[13]), "+f"(d[14]), "+f"(d[15]),
      "+f"(d[16]), "+f"(d[17]), "+f"(d[18]), "+f"(d[19]), "+f"(d[20]), "+f"(d[21]), "+f"(d[22]), "+f"(d[23]),
      "+f"(d[24]), "+f"(d[25]), "+f"(d[26]), "+f"(d[27]), "+f"(d[28]), "+f"(d[29]), "+f"(d[30]), "+f"(d[31])
    : "l"(descA), "l"(descB), "r"(scaleD));
}

__device__ __forceinline__ void ldsm4t(uint32_t (&b)[4], uint32_t addr) {
  asm volatile("ldmatrix.sync.aligned.m8n8.x4.trans.shared.b16 {%0,%1,%2,%3}, [%4];"
               : "=r"(b[0]), "=r"(b[1]), "=r"(b[2]), "=r"(b[3])
               : "r"(addr));
}
__device__ __forceinline__ void hmma(float (&c)[4], uint32_t a0, uint32_t a1, uint32_t a2, uint32_t a3, uint32_t b0, uint32_t b1) {
  asm("mma.sync.aligned.m16n8k16.row.col.f32.bf16.bf16.f32 {%0,%1,%2,%3}, {%4,%5,%6,%7}, {%8,%9}, {%0,%1,%2,%3};"
      : "+f"(c[0]), "+f"(c[1]), "+f"(c[2]), "+f"(c[3])
      : "r"(a0), "r"(a1), "r"(a2), "r"(a3), "r"(b0), "r"(b1));
}

__device__ __forceinline__ uint32_t movm(uint32_t a) {
  uint32_t d;
  asm volatile("movmatrix.sync.aligned.m8n8.trans.b16 %0, %1;" : "=r"(d) : "r"(a));
  return d;
}

#define K1_WARM 0
constexpr int K1_STAGES = 4;
constexpr int K1_W_BYTES = 3 * 8192;
constexpr int K1_X_BYTES = 8 * 16384;
constexpr int K1_BAR_OFF = K1_X_BYTES + K1_STAGES * K1_W_BYTES;
constexpr int K1_SMEM = K1_BAR_OFF + 192 + 1024;
constexpr float QSCALE = 0.25f * 1.4426950408889634f;

__device__ __forceinline__ uint32_t phi2(uint32_t t2) {
  uint32_t a2, mask, r2, o2;
  asm("add.rn.bf16x2 %0, %1, %2;" : "=r"(a2) : "r"(t2), "r"(0x3F803F80u));
  const uint32_t e2 = pack_bf16(ex2f(bf_lo(t2) * 1.4426950408889634f), ex2f(bf_hi(t2) * 1.4426950408889634f));
  asm("set.gt.u32.bf16x2 %0, %1, %2;" : "=r"(mask) : "r"(t2), "r"(0u));
  r2 = (a2 & mask) | (e2 & ~mask);
  asm("add.rn.bf16x2 %0, %1, %2;" : "=r"(o2) : "r"(r2), "r"(0x35863586u));
  return o2;
}

#define K1_SLOT_KB(h) ((h) < 4 ? 2 * (h) : 2 * ((h) - 4) + 1)
struct EpiCtx {
  uint4* qf;
  uint32_t* kp;
  uint32_t* vp;
  uint32_t* s_red;
  float* red;
  int lane;
};

template <bool LINEAR, int HH, int PART>
__device__ __forceinline__ void epi_slice(const float (&acc)[96], const EpiCtx& c, uint32_t (&pk)[4], float& vmax, bool live) {
  const float* a = &acc[HH * 8];
  const float* k = &acc[32 + HH * 8];
  const float* v = &acc[64 + HH * 8];
  if (!LINEAR) {
    if (PART == 0) {
      uint32_t* kh = c.kp + HH * (KV_HEAD_BYTES / 4);
      if (live) {
        c.qf[HH * 32 * 128] = make_uint4(pack_bf16(a[0] * QSCALE, a[1] * QSCALE), pack_bf16(a[2] * QSCALE, a[3] * QSCALE),
                                         pack_bf16(a[4] * QSCALE, a[5] * QSCALE), pack_bf16(a[6] * QSCALE, a[7] * QSCALE));
        kh[0] = pack_bf16(k[0], k[1]);
        kh[64] = pack_bf16(k[2], k[3]);
        kh[32] = pack_bf16(k[4], k[5]);
        kh[96] = pack_bf16(k[6], k[7]);
      }
      float q0 = a[0] * a[0] + a[1] * a[1] + a[4] * a[4] + a[5] * a[5];
      float q1 = a[2] * a[2] + a[3] * a[3] + a[6] * a[6] + a[7] * a[7];
      float k0 = k[0] * k[0] + k[1] * k[1] + k[4] * k[4] + k[5] * k[5];
      float k1 = k[2] * k[2] + k[3] * k[3] + k[6] * k[6] + k[7] * k[7];
#pragma unroll
      for (int o = 1; o <= 2; o <<= 1) {
        q0 += __shfl_xor_sync(0xffffffffu, q0, o);
        q1 += __shfl_xor_sync(0xffffffffu, q1, o);
        k0 += __shfl_xor_sync(0xffffffffu, k0, o);
        k1 += __shfl_xor_sync(0xffffffffu, k1, o);
      }
      const uint32_t qm = __reduce_max_sync(0xffffffffu, max(__float_as_uint(q0) & 0x7FFFFFFFu, __float_as_uint(q1) & 0x7FFFFFFFu));
      const uint32_t km = __reduce_max_sync(0xffffffffu, max(__float_as_uint(k0) & 0x7FFFFFFFu, __float_as_uint(k1) & 0x7FFFFFFFu));
      if (c.lane == 0 && live) {
        atomicMax(&c.s_red[HH * 2 + 0], qm);
        atomicMax(&c.s_red[HH * 2 + 1], km);
      }
    } else {
      uint32_t* vh = c.vp + HH * (KV_HEAD_BYTES / 4);
      if (live) {
        vh[0] = pack_bf16(v[0], v[1]);
        vh[96] = pack_bf16(v[2], v[3]);
        vh[32] = pack_bf16(v[4], v[5]);
        vh[128] = pack_bf16(v[6], v[7]);
        vh[64] = 0x3F803F80u;
        vh[160] = 0x3F803F80u;
      }
#pragma unroll
      for (int i = 0; i < 8; i++) asm("max.NaN.f32 %0, %0, %1;" : "+f"(vmax) : "f"(fabsf(v[i])));
    }
  } else {
    if (PART == 0) {
      const uint4 pq = make_uint4(phi2(pack_bf16(a[0], a[1])), phi2(pack_bf16(a[2], a[3])), phi2(pack_bf16(a[4], a[5])),
                                  phi2(pack_bf16(a[6], a[7])));
      if (live) c.qf[HH * 32 * 128] = pq;
      pk[0] = movm(phi2(pack_bf16(k[0], k[1])));
      pk[2] = movm(phi2(pack_bf16(k[2], k[3])));
      pk[1] = movm(phi2(pack_bf16(k[4], k[5])));
      pk[3] = movm(phi2(pack_bf16(k[6], k[7])));
    } else {
      const uint32_t b0 = movm(pack_bf16(v[0], v[1]));
      const uint32_t b1 = movm(pack_bf16(v[2], v[3]));
      const uint32_t b2 = movm(pack_bf16(v[4], v[5]));
      const uint32_t b3 = movm(pack_bf16(v[6], v[7]));
      float c0[4] = {0, 0, 0, 0}, c1[4] = {0, 0, 0, 0}, c2[4] = {0, 0, 0, 0};
      hmma(c0, pk[0], pk[1], pk[2], pk[3], b0, b1);
      hmma(c1, pk[0], pk[1], pk[2], pk[3], b2, b3);
      hmma(c2, pk[0], pk[1], pk[2], pk[3], 0x3F803F80u, 0x3F803F80u);
      float* slot = c.red + HH * 2 * 4096;
      if (live) {
#pragma unroll
        for (int i = 0; i < 4; i++) {
          slot[i * 32] = c0[i];
          slot[(4 + i) * 32] = c1[i];
          slot[(8 + i) * 32] = c2[i];
        }
      }
    }
  }
}

template <bool LINEAR>
__device__ __forceinline__ void qkv_consumer(uint32_t sbase, uint8_t* smem_gen, uint32_t* s_red, int cp, int rt) {
  const uint32_t bar_full = sbase + K1_BAR_OFF;
  const uint32_t bar_empty = bar_full + 8 * K1_STAGES;
  const int warp = threadIdx.x >> 5;
  const int wg = warp >> 2;
  const int lane = threadIdx.x & 31;
  float accN[96], accP[96];
  EpiCtx c;
  {
    const int row0 = rt * 128 + wg * 64 + (warp & 3) * 16;
    c.qf = g_qfrag + ((size_t)((LINEAR ? NH : 0) + cp * 8) * 32 + (rt * 2 + wg)) * 128 + (threadIdx.x & 127);
    uint32_t* img = reinterpret_cast<uint32_t*>(reinterpret_cast<uint8_t*>(g_kv) + (size_t)(cp * 8) * KV_HEAD_BYTES);
    c.kp = img + (row0 >> 3) * 64 + lane;
    c.vp = img + KV_K_BYTES / 4 + (row0 >> 3) * 96 + lane;
    c.s_red = s_red;
    c.red = reinterpret_cast<float*>(smem_gen + wg * 8192) + (warp & 3) * 384 + lane;
    c.lane = lane;
  }
  uint32_t pk[4] = {0, 0, 0, 0};
  float vmax = 0.f;
#pragma unroll
  for (int i = 0; i < 96; i++) asm volatile("mov.f32 %0, 0f00000000;" : "=f"(accN[i]));
  int npass;
  asm volatile("mov.u32 %0, 2;" : "=r"(npass));
#pragma unroll 1
  for (int pass = K1_WARM ? 0 : 1; pass < npass; pass++) {
    const bool live = K1_WARM ? pass != 0 : true;
    if (live) {
#pragma unroll 1
      for (int kb = 0; kb < 8; kb++) {
        const int s = kb % K1_STAGES;
        mbar_wait(bar_full + 8 * s, (kb / K1_STAGES) & 1);
        if (threadIdx.x == 0) PROF_T(0, 2 + (kb >> 1));
        const uint64_t dA = mkdesc(sbase + kb * 16384 + wg * 8192, 16, 1024, 1);
        const uint64_t dB = mkdesc(sbase + K1_X_BYTES + s * K1_W_BYTES, 8192, 1024, 1);
        wg_fence();
#pragma unroll
        for (int k = 0; k < 4; k++) wgmma_ss_n192_tb(accP, dA + k * 2, dB + k * 128, (kb | k) != 0);
        wg_commit();
        if (kb > 0) {
          wg_wait<1>();
          if ((threadIdx.x & 127) == 0) {
            const int sp = (kb - 1) % K1_STAGES;
            mbar_arrive_cluster(bar_empty + 8 * sp, 0);
            mbar_arrive_cluster(bar_empty + 8 * sp, 1);
          }
        }
      }
      wg_wait<0>();
      fence_regs(accP);
      if ((threadIdx.x & 127) == 0) {
        mbar_arrive_cluster(bar_empty + 8 * (7 % K1_STAGES), 0);
        mbar_arrive_cluster(bar_empty + 8 * (7 % K1_STAGES), 1);
      }
      if (threadIdx.x == 0) PROF_T(0, 6);
#define K1_T1_STEP(KB)                                                                           \
  {                                                                                              \
    constexpr int g = 8 + KB;                                                                    \
    constexpr int s = g % K1_STAGES;                                                             \
    mbar_wait(bar_full + 8 * s, (g / K1_STAGES) & 1);                                            \
    const uint64_t dA = mkdesc(sbase + KB * 16384 + wg * 8192, 16, 1024, 1);                     \
    const uint64_t dB = mkdesc(sbase + K1_X_BYTES + s * K1_W_BYTES, 8192, 1024, 1);              \
    wg_fence();                                                                                  \
    _Pragma("unroll") for (int k = 0; k < 4; k++) wgmma_ss_n192_tb(accN, dA + k * 2, dB + k * 128, (KB | k) != 0); \
    wg_commit();                                                                                 \
    epi_slice<LINEAR, KB / 2, KB & 1>(accP, c, pk, vmax, true);                                  \
    wg_wait<0>();                                                                                \
    if (KB + K1_STAGES < 8 && (threadIdx.x & 127) == 0) {                                        \
      mbar_arrive_cluster(bar_empty + 8 * s, 0);                                                 \
      mbar_arrive_cluster(bar_empty + 8 * s, 1);                                                 \
    }                                                                                            \
  }
      K1_T1_STEP(0) K1_T1_STEP(1) K1_T1_STEP(2) K1_T1_STEP(3) K1_T1_STEP(4) K1_T1_STEP(5) K1_T1_STEP(6) K1_T1_STEP(7)
#undef K1_T1_STEP
      fence_regs(accN);
      if (threadIdx.x == 0) PROF_T(0, 10);
      c.qf += 4 * 32 * 128;
      c.kp += 4 * (KV_HEAD_BYTES / 4);
      c.vp += 4 * (KV_HEAD_BYTES / 4);
      c.s_red += 8;
      c.red += 4096;
    }
    float vm1 = 0.f;
    epi_slice<LINEAR, 0, 0>(accN, c, pk, vm1, live);
    epi_slice<LINEAR, 0, 1>(accN, c, pk, vm1, live);
    epi_slice<LINEAR, 1, 0>(accN, c, pk, vm1, live);
    epi_slice<LINEAR, 1, 1>(accN, c, pk, vm1, live);
    epi_slice<LINEAR, 2, 0>(accN, c, pk, vm1, live);
    epi_slice<LINEAR, 2, 1>(accN, c, pk, vm1, live);
    epi_slice<LINEAR, 3, 0>(accN, c, pk, vm1, live);
    epi_slice<LINEAR, 3, 1>(accN, c, pk, vm1, live);
    if (live) asm("max.NaN.f32 %0, %0, %1;" : "+f"(vmax) : "f"(vm1));
  }
  if (!LINEAR) {
    const uint32_t vm = __reduce_max_sync(0xffffffffu, __float_as_uint(vmax) & 0x7FFFFFFFu);
    if (lane == 0) atomicMax(&s_red[16], vm);
    asm volatile("bar.sync 1, 256;" ::: "memory");
    if (threadIdx.x < 8) {
      *reinterpret_cast<float4*>(&g_nrm[((cp * 8 + threadIdx.x) * 16 + rt) * 4]) =
          make_float4(__uint_as_float(s_red[threadIdx.x * 2]), __uint_as_float(s_red[threadIdx.x * 2 + 1]), __uint_as_float(s_red[16]), 0.f);
    }
  } else {
    asm volatile("bar.sync 1, 256;" ::: "memory");
    float* dst = g_kvpart + ((size_t)rt * NH + cp * 8) * 384;
#pragma unroll
    for (int i = 0; i < 12; i++) {
      const int o = threadIdx.x + i * 256;
      const int h = o / 384, e = o - h * 384;
      const float* src = reinterpret_cast<const float*>(smem_gen) + K1_SLOT_KB(h) * 4096 + e;
      float sum = 0.f;
#pragma unroll
      for (int w = 0; w < 8; w++) sum += src[(w >> 2) * 2048 + (w & 3) * 384];
      dst[o] = sum;
    }
  }
}

__global__ void __launch_bounds__(384, 1)
qkv_gemm_kernel(const __grid_constant__ CUtensorMap mxA, const __grid_constant__ CUtensorMap mxB,
                const __grid_constant__ CUtensorMap mwA, const __grid_constant__ CUtensorMap mwB) {
  extern __shared__ uint8_t smem_raw[];
  const uint32_t sbase = (smem_u32(smem_raw) + 1023) & ~1023u;
  uint8_t* smem_gen = smem_raw + (sbase - smem_u32(smem_raw));
  const uint32_t bar_full = sbase + K1_BAR_OFF;
  const uint32_t bar_empty = bar_full + 8 * K1_STAGES;
  uint32_t* s_red = reinterpret_cast<uint32_t*>(smem_gen + K1_BAR_OFF + 64);

  const int rank = blockIdx.x & 1;
  const int pair = blockIdx.x >> 1;
  const int branch = pair >> 5;
  const int rp = (pair & 31) >> 2;
  const int cp = pair & 3;
  const int rt = rp * 2 + rank;
  const int warp = threadIdx.x >> 5;
  if (threadIdx.x == 0) { PROF_G(0, 30); PROF_T(0, 0); }
  const CUtensorMap* mx = branch ? &mxA : &mxB;
  const CUtensorMap* mw = branch ? &mwA : &mwB;

  if (threadIdx.x == 256) {
    asm volatile("prefetch.tensormap [%0];" ::"l"(mx) : "memory");
    asm volatile("prefetch.tensormap [%0];" ::"l"(mw) : "memory");
    for (int i = 0; i < K1_STAGES; i++) {
      mbar_init(bar_full + 8 * i, 1);
      mbar_init(bar_empty + 8 * i, 4);
    }
    fence_barrier_init();
    fence_proxy_async();
    for (int kb = 0; kb < K1_STAGES; kb++) mbar_expect_tx(bar_full + 8 * kb, 16384 + K1_W_BYTES);
    tma_load_2d(sbase, mx, 0, rt * 128, bar_full);
  }
  pdl_launch_dependents();
  if (threadIdx.x < 32) s_red[threadIdx.x] = 0;
  if (blockIdx.x == 0 && threadIdx.x < 8) g_sync[threadIdx.x] = 0;
  __syncthreads();
  cluster_sync_relaxed();
  if (threadIdx.x == 0) PROF_T(0, 1);

  if (warp >= 8) {
    asm volatile("setmaxnreg.dec.sync.aligned.u32 40;");
    if (threadIdx.x == 256) {
      for (int g = 0; g < 16; g++) {
        const int s = g % K1_STAGES;
        const int kb = g & 7;
        if (g >= K1_STAGES) {
          mbar_wait(bar_empty + 8 * s, ((g / K1_STAGES) - 1) & 1);
          mbar_expect_tx(bar_full + 8 * s, (g < 8 ? 16384 : 0) + K1_W_BYTES);
        }
        if (g > 0 && g < 8) tma_load_2d(sbase + kb * 16384, mx, kb * 64, rt * 128, bar_full + 8 * s);
        const int h0 = cp * 8 + (g >> 3) * 4;
        const uint32_t st = sbase + K1_X_BYTES + s * K1_W_BYTES + rank * 4096;
#pragma unroll
        for (int p = 0; p < 3; p++)
          tma_load_2d_mc(st + p * 8192, mw, p * 512 + h0 * 16, kb * 64 + rank * 32, bar_full + 8 * s, (uint16_t)3);
      }
    }
    __syncwarp();
    cluster_sync_relaxed();
  } else {
    asm volatile("setmaxnreg.inc.sync.aligned.u32 232;");
    if (branch == 0) qkv_consumer<false>(sbase, smem_gen, s_red, cp, rt);
    else qkv_consumer<true>(sbase, smem_gen, s_red, cp, rt);
    if (threadIdx.x == 0) PROF_T(0, 11);
    __syncwarp();
    cluster_sync_relaxed();
    if (threadIdx.x == 0) { PROF_T(0, 12); PROF_G(0, 31); }
  }
}

constexpr int T_WA0 = KV_HEAD_BYTES;
constexpr int T_S0 = T_WA0 + 32768;
constexpr int K2_BAR = T_S0 + 32768;
constexpr int T_WA1 = 0;
constexpr int T_WB = 32768;
constexpr int T_S2 = 98304;
constexpr int K2_SMEM = K2_BAR + 256 + 1024;

#define ATT_NPOLY 18
#define ATT_CH 8
#define ATT_D 1
#define PRO_MODE 1
#define STAGGER 0
#define K2_WARM 0
#define K2_FIRST 2
#define CONST_SMID 0
#define ATT_STRUCT 1
#define ATT_PIN 0
#define ATT_GM 1
#define ATT_DEG 2
struct ExpC {
  uint32_t k3c00, kmask, seven, c3;
};
__device__ __forceinline__ uint32_t hfma2(uint32_t a, uint32_t b, uint32_t c) {
  uint32_t r;
  asm("fma.rn.f16x2 %0, %1, %2, %3;" : "=r"(r) : "r"(a), "r"(b), "r"(c));
  return r;
}
__device__ __forceinline__ uint32_t exp2_poly_pair(float t0, float t1, const ExpC& c) {
  uint32_t u;
  asm("prmt.b32 %0, %1, %2, 0x5410;" : "=r"(u) : "r"(__float_as_uint(t0)), "r"(__float_as_uint(t1)));
  uint32_t m;
  asm("lop3.b32 %0, %1, 0x03FF03FF, %2, 0xEA;" : "=r"(m) : "r"(u), "r"(c.k3c00));
  uint32_t p = hfma2(m, c.c3, 0xa385a385u);
  p = hfma2(p, m, 0x4ad64ad7u);
  uint32_t mu;
  asm("lop3.b32 %0, %1, 0xFC00FC00, %2, 0xEA;" : "=r"(mu) : "r"(u), "r"(c.kmask));
  uint32_t r;
  asm("{.reg .b32 t; shf.r.wrap.b32 t, %1, %2, 3; add.u32 %0, t, %3;}" : "=r"(r) : "r"(mu), "r"(c.seven), "r"(p));
  return r;
}
__device__ __forceinline__ float gadd(float x, float M, uint32_t g) {
  float r = x;
  asm("{.reg .pred p; setp.ne.b32 p, %2, -1; @p add.f32 %0, %0, %1;}" : "+f"(r) : "f"(M), "r"(g));
  return r;
}
__device__ __forceinline__ float gex2(float x, uint32_t g) {
  float r = x;
  asm("{.reg .pred p; setp.ne.b32 p, %1, -1; @p ex2.approx.ftz.f32 %0, %0;}" : "+f"(r) : "r"(g));
  return r;
}
template <int NPOLY, int NPAIR, int CH, int D, bool G0 = false>
__device__ __forceinline__ void exp_tile(const float (&s)[2 * NPAIR], uint32_t (&p)[NPAIR], const ExpC& c, uint32_t g0 = 0) {
#pragma unroll
  for (int i = 0; i < NPAIR; i++) {
    const bool isPoly = ((i + 1) * NPOLY / 32) != (i * NPOLY / 32);
    const int ch = i / CH;
    const bool gated = ch >= D || G0;
    int gi = (ch - D) * CH + CH - 1;
    if (ch >= D) {
      while (gi > (ch - D) * CH && !(((gi + 1) * NPOLY / 32) != (gi * NPOLY / 32))) gi--;
    }
    const uint32_t g = ch >= D ? p[gi] : g0;
    if (!isPoly) {
      if (gated && ATT_GM) p[i] = pack_bf16(gex2(s[2 * i], g), gex2(s[2 * i + 1], g));
      else p[i] = pack_bf16(ex2f(s[2 * i]), ex2f(s[2 * i + 1]));
    } else {
      if (gated) p[i] = exp2_poly_pair(gadd(s[2 * i], 12329.f, g), gadd(s[2 * i + 1], 12329.f, g), c);
      else p[i] = exp2_poly_pair(s[2 * i] + 12329.f, s[2 * i + 1] + 12329.f, c);
    }
  }
}

__device__ __forceinline__ void store_o(__nv_bfloat16* o, int row0, int head, int lane, const uint32_t (&r)[4]) {
  const int g = lane >> 2, t = lane & 3;
  uint32_t* p0 = reinterpret_cast<uint32_t*>(o + (size_t)(row0 + g) * DM + head * 16) + t;
  uint32_t* p1 = reinterpret_cast<uint32_t*>(o + (size_t)(row0 + g + 8) * DM + head * 16) + t;
  p0[0] = r[0];
  p1[0] = r[1];
  p0[4] = r[2];
  p1[4] = r[3];
}

__device__ __forceinline__ void kv_fetch_piece(uint32_t sbase, uint32_t bar, int piece) {
  const uint8_t* img = reinterpret_cast<const uint8_t*>(g_kv) + (size_t)(blockIdx.x >> 2) * KV_HEAD_BYTES;
  const int g = piece >> 1, isv = piece & 1;
  const int e0 = g == 0 ? 0 : (isv ? 256 : 320) + (g - 1) * 512;
  const int e1 = g == 3 ? 2048 : (isv ? 256 : 320) + g * 512;
  const int bytes = (e1 - e0) * (isv ? 48 : 32);
  const int off = isv ? KV_K_BYTES + e0 * 48 : e0 * 32;
  mbar_expect_tx(bar + 8 * g, bytes);
  bulk_load(sbase + off, img + off, bytes, bar + 8 * g);
}

__device__ __forceinline__ void safe_exp(const float (&s)[32], uint32_t (&p)[16], float (&o)[12], float& m0, float& m1) {
  float x0 = s[0], x1 = s[2];
#pragma unroll
  for (int i = 0; i < 8; i++) {
    x0 = fmaxf(x0, fmaxf(s[4 * i], s[4 * i + 1]));
    x1 = fmaxf(x1, fmaxf(s[4 * i + 2], s[4 * i + 3]));
  }
  x0 = fmaxf(x0, __shfl_xor_sync(0xffffffffu, x0, 1));
  x1 = fmaxf(x1, __shfl_xor_sync(0xffffffffu, x1, 1));
  x0 = fmaxf(x0, __shfl_xor_sync(0xffffffffu, x0, 2));
  x1 = fmaxf(x1, __shfl_xor_sync(0xffffffffu, x1, 2));
  const float n0 = fmaxf(m0, x0), n1 = fmaxf(m1, x1);
  const float c0 = ex2f(m0 - n0), c1 = ex2f(m1 - n1);
  m0 = n0;
  m1 = n1;
#pragma unroll
  for (int i = 0; i < 3; i++) {
    o[4 * i] *= c0;
    o[4 * i + 1] *= c0;
    o[4 * i + 2] *= c1;
    o[4 * i + 3] *= c1;
  }
#pragma unroll
  for (int i = 0; i < 8; i++) {
    p[2 * i] = pack_bf16(ex2f(s[4 * i] - n0), ex2f(s[4 * i + 1] - n0));
    p[2 * i + 1] = pack_bf16(ex2f(s[4 * i + 2] - n1), ex2f(s[4 * i + 3] - n1));
  }
}

__device__ __forceinline__ void attn_step(float (&sx)[32], float (&sy)[32], float (&o)[12], const uint4& qf, uint64_t dK, uint64_t dV,
                                          const ExpC& ec) {
  uint32_t pa[16], pb[16];
  wg_fence();
  wgmma_rs_n64_z(sy, qf.x, qf.y, qf.z, qf.w, dK + 128);
  wg_commit();
  exp_tile<ATT_NPOLY, 16, ATT_CH, ATT_D>(sx, pa, ec);
  wg_fence();
  wgmma_rs_n24_tb(o, pa[12], pa[13], pa[14], pa[15], dV + 3 * 48, 1);
  wg_commit();
  wg_wait<1>();
  fence_regs(sy);
  exp_tile<ATT_NPOLY, 16, ATT_CH, ATT_D>(sy, pb, ec);
  wg_fence();
#pragma unroll
  for (int k = 0; k < 3; k++) wgmma_rs_n24_tb(o, pa[4 * k], pa[4 * k + 1], pa[4 * k + 2], pa[4 * k + 3], dV + k * 48, 1);
#pragma unroll
  for (int k = 0; k < 4; k++) wgmma_rs_n24_tb(o, pb[4 * k], pb[4 * k + 1], pb[4 * k + 2], pb[4 * k + 3], dV + (4 + k) * 48, 1);
  wgmma_rs_n64_z(sy, qf.x, qf.y, qf.z, qf.w, dK + 256);
  wg_commit();
  wg_wait<0>();
  fence_regs(sy);
}

template <bool SAFE>
__device__ __forceinline__ void attn_tile(uint64_t dK, uint64_t dV, uint32_t bar, const uint4 qf, const ExpC& ec, uint32_t (&outp)[4],
                                          bool warm) {
  float o[12];
#pragma unroll
  for (int i = 0; i < 12; i++) asm volatile("mov.f32 %0, 0f00000000;" : "=f"(o[i]));
  if (!warm) mbar_wait(bar, 0);
  if (!SAFE) {
    float s0[32], s1[32];
    wg_fence();
    wgmma_rs_n64_z(s0, qf.x, qf.y, qf.z, qf.w, dK);
    wg_commit();
    wg_wait<0>();
    fence_regs(s0);
#pragma unroll 1
    for (int p = warm ? 7 : 0; p < 8; p++) {
      if ((p & 1) && !warm) mbar_wait(bar + 8 * min((p + 1) >> 1, 3), 0);
      attn_step(s0, s1, o, qf, dK, dV, ec);
      attn_step(s1, s0, o, qf, dK + 256, dV + 384, ec);
      dK += 512;
      dV += 768;
    }
  } else {
    float m0 = -INFINITY, m1 = -INFINITY;
#pragma unroll 1
    for (int j = 0; j < 32; j++) {
      if (j == 4) { mbar_wait(bar + 8, 0); mbar_wait(bar + 16, 0); mbar_wait(bar + 24, 0); }
      float s[32];
      uint32_t p[16];
      wg_fence();
      wgmma_rs_n64_z(s, qf.x, qf.y, qf.z, qf.w, dK);
      wg_commit();
      wg_wait<0>();
      fence_regs(s);
      safe_exp(s, p, o, m0, m1);
      wg_fence();
#pragma unroll
      for (int k = 0; k < 4; k++) wgmma_rs_n24_tb(o, p[4 * k], p[4 * k + 1], p[4 * k + 2], p[4 * k + 3], dV + k * 48, 1);
      wg_commit();
      wg_wait<0>();
      fence_regs(o);
      dK += 128;
      dV += 192;
    }
  }
  fence_regs(o);
  const float r0 = 1.0f / o[8], r1 = 1.0f / o[10];
  outp[0] = pack_bf16(o[0] * r0, o[1] * r0);
  outp[1] = pack_bf16(o[2] * r1, o[3] * r1);
  outp[2] = pack_bf16(o[4] * r0, o[5] * r0);
  outp[3] = pack_bf16(o[6] * r1, o[7] * r1);
}

__device__ __forceinline__ void linear_attn_cta(uint8_t* smem_raw, uint32_t sbase, const CUtensorMap* mo16, int cta) {
  const int warp = threadIdx.x >> 5, lane = threadIdx.x & 31;
  const int hg = warp & 1;
  const uint4* qp = g_qfrag + (size_t)(NH + cta * 8 + hg * 4) * 32 * 128 + lane;
  auto qaddr = [&](int i) {
    const int blk16 = i * 8 + (warp >> 1);
    return qp + (blk16 >> 2) * 128 + (blk16 & 3) * 32;
  };
  uint4 q[4];
#pragma unroll
  for (int h = 0; h < 4; h++) q[h] = qaddr(0)[h * 32 * 128];
  float* red = reinterpret_cast<float*>(smem_raw + (sbase - smem_u32(smem_raw)) + 131072);
  {
    const float* src = g_kvpart + (size_t)cta * 8 * 384;
    float sum[6];
#pragma unroll
    for (int i = 0; i < 6; i++) sum[i] = 0.f;
#pragma unroll
    for (int r = 0; r < 16; r++) {
#pragma unroll
      for (int i = 0; i < 6; i++) sum[i] += src[(size_t)r * NH * 384 + threadIdx.x + i * 512];
    }
#pragma unroll
    for (int i = 0; i < 6; i++) red[threadIdx.x + i * 512] = round_bf16(sum[i]);
  }
  __syncthreads();
  if (threadIdx.x == 0) PROF_T(1, 1);
  uint32_t bf[4][6];
  {
    const int g = lane >> 2, t = lane & 3;
#pragma unroll
    for (int h = 0; h < 4; h++) {
#pragma unroll
      for (int f = 0; f < 6; f++) {
        const int blk = f >> 1, half = f & 1;
        const int e = (blk == 2) ? 0 : g;
        const int d = 2 * t + 8 * half;
        const int base = (hg * 4 + h) * 384 + (blk * 4 + half * 2 + (e & 1)) * 32 + (e >> 1);
        bf[h][f] = pack_bf16(red[base + (d & 7) * 4], red[base + ((d + 1) & 7) * 4]);
      }
    }
  }
  if (threadIdx.x == 0) PROF_T(1, 2);
  const uint32_t stg = sbase + warp * 8192;
#pragma unroll 1
  for (int i = 0; i < 16; i++) {
    uint4 qc[4];
#pragma unroll
    for (int h = 0; h < 4; h++) qc[h] = q[h];
    if (i + 1 < 16) {
#pragma unroll
      for (int h = 0; h < 4; h++) q[h] = qaddr(i + 1)[h * 32 * 128];
    }
    const uint32_t buf = stg + (i & 3) * 2048;
    if (i >= 4) {
      if (lane == 0) asm volatile("cp.async.bulk.wait_group.read 3;" ::: "memory");
      __syncwarp();
    }
#pragma unroll
    for (int h = 0; h < 4; h++) {
      float n0[4] = {0, 0, 0, 0}, n1[4] = {0, 0, 0, 0}, dn[4] = {0, 0, 0, 0};
      hmma(n0, qc[h].x, qc[h].y, qc[h].z, qc[h].w, bf[h][0], bf[h][1]);
      hmma(n1, qc[h].x, qc[h].y, qc[h].z, qc[h].w, bf[h][2], bf[h][3]);
      hmma(dn, qc[h].x, qc[h].y, qc[h].z, qc[h].w, bf[h][4], bf[h][5]);
      const float d0 = __fdividef(1.0f, dn[0] + 1e-6f), d1 = __fdividef(1.0f, dn[2] + 1e-6f);
      const uint32_t r0 = pack_bf16(n0[0] * d0, n0[1] * d0);
      const uint32_t r1 = pack_bf16(n0[2] * d1, n0[3] * d1);
      const uint32_t r2 = pack_bf16(n1[0] * d0, n1[1] * d0);
      const uint32_t r3 = pack_bf16(n1[2] * d1, n1[3] * d1);
      const int row = lane & 15;
      const int chunk = h * 2 + (lane >> 4);
      const uint32_t addr = buf + row * 128 + ((chunk ^ (row & 7)) << 4);
      asm volatile("stmatrix.sync.aligned.m8n8.x4.shared.b16 [%0], {%1,%2,%3,%4};" ::"r"(addr), "r"(r0), "r"(r1), "r"(r2), "r"(r3)
                   : "memory");
    }
    fence_proxy_async();
    __syncwarp();
    if (lane == 0) {
      tma_store_2d(mo16, buf, cta * 128 + hg * 64, (i * 8 + (warp >> 1)) * 16);
      asm volatile("cp.async.bulk.commit_group;" ::: "memory");
    }
  }
  if (threadIdx.x == 0) PROF_T(1, 3);
  if (lane == 0) {
    asm volatile("cp.async.bulk.wait_group 0;" ::: "memory");
    fence_proxy_async_all();
  }
  __syncthreads();
  if (threadIdx.x == 0) flag_arrive(&g_sync[4]);
}

__device__ __forceinline__ uint32_t tail_stage(uint32_t sbase, int s) { return sbase + (s < 2 ? T_S0 + s * 16384 : T_S2 + (s - 2) * 16384); }

__device__ __forceinline__ void tail_consumer(uint32_t sbase, const CUtensorMap* mout, int rt, int ct) {
  const uint32_t tb = sbase + K2_BAR + 96;
  const int wg = threadIdx.x >> 7, warp = (threadIdx.x >> 5) & 3, lane = threadIdx.x & 31;
#pragma unroll 1
  for (int tile = 0; tile < 2; tile++) {
    float acc[32];
#pragma unroll 1
    for (int kb = 0; kb < 8; kb++) {
      const int g = tile * 8 + kb;
      const int s = g % 6;
      if (g == 0) mbar_wait(tb + 96, 0);
      if (g == 4) mbar_wait(tb + 104, 0);
      if (g == 8) mbar_wait(tb + 112, 0);
      mbar_wait(tb + 8 * s, (g / 6) & 1);
      if (threadIdx.x == 0) PROF_T(2, 1 + (g >> 1));
      const uint32_t wa = sbase + (tile ? T_WB + kb * 8192 : (kb < 4 ? T_WA0 + kb * 8192 : T_WA1 + (kb - 4) * 8192));
      const uint64_t dA = mkdesc(tail_stage(sbase, s) + wg * 8192, 16, 1024, 1);
      const uint64_t dB = mkdesc(wa, 8192, 1024, 1);
      wg_fence();
#pragma unroll
      for (int k = 0; k < 4; k++) wgmma_ss_n64_tb(acc, dA + k * 2, dB + k * 128, (kb | k) != 0);
      wg_commit();
      if (kb > 0) {
        wg_wait<1>();
        if ((threadIdx.x & 127) == 0) mbar_arrive(tb + 48 + 8 * ((g - 1) % 6));
      }
    }
    wg_wait<0>();
    if ((threadIdx.x & 127) == 0) mbar_arrive(tb + 48 + 8 * ((tile * 8 + 7) % 6));
    fence_regs(acc);
    if (tile == 0) asm volatile("bar.sync 3, 256;" ::: "memory");
    const uint32_t stg = sbase + T_WA0 + tile * 16384 + wg * 8192;
    const int rloc = warp * 16 + (lane & 15);
#pragma unroll
    for (int c16 = 0; c16 < 4; c16++) {
      const float* a = &acc[c16 * 8];
      const uint32_t r0 = pack_bf16(a[0], a[1]), r1 = pack_bf16(a[2], a[3]), r2 = pack_bf16(a[4], a[5]), r3 = pack_bf16(a[6], a[7]);
      const int chunk = c16 * 2 + (lane >> 4);
      const uint32_t addr = stg + rloc * 128 + ((chunk ^ (rloc & 7)) << 4);
      asm volatile("stmatrix.sync.aligned.m8n8.x4.shared.b16 [%0], {%1,%2,%3,%4};" ::"r"(addr), "r"(r0), "r"(r1), "r"(r2), "r"(r3)
                   : "memory");
    }
    fence_proxy_async();
    asm volatile("bar.sync %0, 128;" ::"r"(4 + wg) : "memory");
    if ((threadIdx.x & 127) == 0) {
      tma_store_2d(mout, stg, tile * DM + ct * 64, rt * 128 + wg * 64);
      asm volatile("cp.async.bulk.commit_group;" ::: "memory");
    }
  }
  if ((threadIdx.x & 127) == 0) asm volatile("cp.async.bulk.wait_group.read 0;" ::: "memory");
}

__device__ __forceinline__ void tail_producer_local(uint32_t sbase, const CUtensorMap* mo, const CUtensorMap* mwA, const CUtensorMap* mwB,
                                                    int rt, int ct) {
  const uint32_t tb = sbase + K2_BAR + 96;
  uint32_t fetched;
  asm volatile("ld.shared.u32 %0, [%1];" : "=r"(fetched) : "r"(sbase + K2_BAR + 80) : "memory");
  if (!fetched) {
    flag_wait(&g_sync[4], 4);
    fence_proxy_async_all();
  }
  for (int g = fetched ? 2 : 0; g < 6; g++) {
    if (g == 4) {
      mbar_expect_tx(tb + 104, 32768);
      for (int kb = 4; kb < 8; kb++) tma_load_2d(sbase + T_WA1 + (kb - 4) * 8192, mwA, ct * 64, kb * 64, tb + 104);
    }
    mbar_expect_tx(tb + 8 * g, 16384);
    tma_load_2d(tail_stage(sbase, g), mo, g * 64, rt * 128, tb + 8 * g);
  }
  mbar_expect_tx(tb + 112, 65536);
  for (int kb = 0; kb < 8; kb++) tma_load_2d(sbase + T_WB + kb * 8192, mwB, ct * 64, kb * 64, tb + 112);
  for (int g = 6; g < 8; g++) {
    mbar_wait(tb + 48 + 8 * (g % 6), 0);
    mbar_expect_tx(tb + 8 * (g % 6), 16384);
    tma_load_2d(tail_stage(sbase, g % 6), mo, g * 64, rt * 128, tb + 8 * (g % 6));
  }
}
__device__ __forceinline__ void tail_producer_grid(uint32_t sbase, const CUtensorMap* mo, int rt, int qb) {
  const uint32_t tb = sbase + K2_BAR + 96;
  flag_arrive(&g_sync[qb]);
  flag_wait(&g_sync[qb], 32);
  fence_proxy_async_all();
  for (int g = 8; g < 16; g++) {
    const int s = g % 6;
    mbar_wait(tb + 48 + 8 * s, ((g / 6) - 1) & 1);
    mbar_expect_tx(tb + 8 * s, 16384);
    tma_load_2d(tail_stage(sbase, s), mo, (g & 7) * 64, S_LEN + rt * 128, tb + 8 * s);
  }
}

__global__ void __launch_bounds__(512, 1)
attn_kernel(const __grid_constant__ CUtensorMap mo16, const __grid_constant__ CUtensorMap mo, const __grid_constant__ CUtensorMap mwA,
            const __grid_constant__ CUtensorMap mwB, const __grid_constant__ CUtensorMap mout, const uint8_t* __restrict__ woA,
            const uint8_t* __restrict__ woB) {
  extern __shared__ uint8_t smem_raw[];
  const uint32_t sbase = (smem_u32(smem_raw) + 1023) & ~1023u;
  const uint32_t bar = sbase + K2_BAR;
  if (threadIdx.x == 0) { PROF_G(1, 30); PROF_T(1, 0); PROF_T(2, 0); }
  if (threadIdx.x == 0) {
    for (int i = 0; i < 4; i++) mbar_init(bar + 8 * i, 2);
    for (int i = 0; i < 6; i++) {
      mbar_init(bar + 96 + 8 * i, 1);
      mbar_init(bar + 96 + 48 + 8 * i, 2);
    }
    for (int i = 0; i < 3; i++) mbar_init(bar + 96 + 96 + 8 * i, 1);
    asm volatile("st.shared.v4.u32 [%0], {%1, %2, %3, %4};" ::"r"(bar + 64), "r"(0x3C003C00u), "r"(0x00070000u), "r"(7u),
                 "r"(ATT_DEG == 3 ? 0x2cfd2cfdu : 0x35623562u)
                 : "memory");
    fence_barrier_init();
    fence_proxy_async();
  }
  __syncthreads();
  if (blockIdx.x >= 128) {
    if (threadIdx.x < 16) {
      const int i = (blockIdx.x - 128) * 16 + threadIdx.x;
      const uint8_t* p = (i < 32 ? woA : woB) + (size_t)(i & 31) * 16384;
      asm volatile("cp.async.bulk.prefetch.L2.global [%0], %1;" ::"l"(p), "r"(16384) : "memory");
    }
    pdl_wait();
    if (threadIdx.x == 0) PROF_T(1, 7);
    linear_attn_cta(smem_raw, sbase, &mo16, blockIdx.x - 128);
    if (threadIdx.x == 0) { PROF_T(1, 5); PROF_G(1, 31); }
    return;
  }
  const int head = blockIdx.x >> 2, qb = blockIdx.x & 3;
  const int lane = threadIdx.x & 31;
  const int wg = __shfl_sync(0xffffffffu, threadIdx.x >> 7, 0), warp = __shfl_sync(0xffffffffu, (threadIdx.x >> 5) & 3, 0);
  const int ort = qb * 4 + ((blockIdx.x >> 2) & 3), oct = blockIdx.x >> 4;
  ExpC ec;
  asm volatile("ld.volatile.shared.v4.u32 {%0, %1, %2, %3}, [%4];" : "=r"(ec.k3c00), "=r"(ec.kmask), "=r"(ec.seven), "=r"(ec.c3) : "r"(bar + 64));
  const uint64_t dK = mkdesc(sbase, 128, 256, 0);
  const uint64_t dV = mkdesc(sbase + KV_K_BYTES, 384, 128, 0);
  pdl_wait();
  if (threadIdx.x == 0) { PROF_T(1, 7); PROF_G(1, 29); }
  if (threadIdx.x == 0) {
#pragma unroll
    for (int piece = 0; piece < 8; piece++) kv_fetch_piece(sbase, bar, piece);
    mbar_expect_tx(bar + 96 + 96, 32768);
    for (int kb = 0; kb < 4; kb++) tma_load_2d(sbase + T_WA0 + kb * 8192, &mwA, oct * 64, kb * 64, bar + 96 + 96);
  }
  uint4 qnext = g_qfrag[(head * 32 + qb * 8 + wg * 2) * 128 + (threadIdx.x & 127)];
  bool safe_path;
  {
    float4 n = make_float4(0.f, 0.f, 0.f, 0.f);
    if (lane < 16) n = *reinterpret_cast<const float4*>(&g_nrm[(head * 16 + lane) * 4]);
    uint32_t qm = ((lane >> 2) == qb) ? __float_as_uint(n.x) : 0u;
    qm = __reduce_max_sync(0xffffffffu, qm);
    const uint32_t km = __reduce_max_sync(0xffffffffu, __float_as_uint(n.y));
    const uint32_t vm = __reduce_max_sync(0xffffffffu, __float_as_uint(n.z));
    const float b2 = __uint_as_float(qm) * (QSCALE * QSCALE) * __uint_as_float(km) * 1.02f;
    const float vmax = __uint_as_float(vm);
    const bool ok = (b2 <= 21.5f * 21.5f) && (vmax <= 1.0e24f) && (vmax >= 1.0e-18f || vmax == 0.f);
    safe_path = !ok;
  }
#pragma unroll 1
  for (int t = 0; t < 2; t++) {
    const int tile64 = qb * 8 + wg * 2 + t;
    const uint4 qf = qnext;
    if (t == 0) qnext = g_qfrag[(head * 32 + tile64 + 1) * 128 + (threadIdx.x & 127)];
    if (t == 1 && wg == 3 && warp == 0) {
      uint32_t done;
      asm volatile("ld.acquire.gpu.global.u32 %0, [%1];" : "=r"(done) : "l"(&g_sync[4]) : "memory");
      if (lane == 0) {
        if (done >= 4) {
          fence_proxy_async_all();
          for (int g = 0; g < 2; g++) {
            mbar_expect_tx(bar + 96 + 8 * g, 16384);
            tma_load_2d(tail_stage(sbase, g), &mo, g * 64, ort * 128, bar + 96 + 8 * g);
          }
        }
        asm volatile("st.shared.u32 [%0], %1;" ::"r"(bar + 80), "r"(done >= 4 ? 1u : 0u) : "memory");
      }
      __syncwarp();
    }
    uint32_t r[4];
    if (threadIdx.x == 0) PROF_T(1, 1 + t);
    if (!safe_path) attn_tile<false>(dK, dV, bar, qf, ec, r, false);
    else attn_tile<true>(dK, dV, bar, qf, ec, r, false);
    store_o(g_o + (size_t)S_LEN * DM, tile64 * 64 + warp * 16, head, lane, r);
  }
  if (threadIdx.x == 0) PROF_T(1, 5);
  if (threadIdx.x == 384) PROF_T(1, 10);
  fence_proxy_async_all();
  if (threadIdx.x == 384) PROF_T(1, 11);
  if (wg == 2 && warp < 2) {
    asm volatile("bar.sync 2, 512;" ::: "memory");
    if (threadIdx.x == 256) PROF_T(1, 12);
    if (lane == 0) {
      if (warp == 0) tail_producer_grid(sbase, &mo, ort, qb);
      else tail_producer_local(sbase, &mo, &mwA, &mwB, ort, oct);
    }
  } else {
    asm volatile("bar.arrive 2, 512;" ::: "memory");
    if (wg < 2) tail_consumer(sbase, &mout, ort, oct);
  }
  if (threadIdx.x == 0) { PROF_T(2, 12); PROF_G(1, 31); }
}

typedef CUresult (*EncodeFn)(CUtensorMap*, CUtensorMapDataType, cuuint32_t, void*, const cuuint64_t*, const cuuint64_t*,
                             const cuuint32_t*, const cuuint32_t*, CUtensorMapInterleave, CUtensorMapSwizzle,
                             CUtensorMapL2promotion, CUtensorMapFloatOOBfill);

void make_map(EncodeFn enc, CUtensorMap* m, const void* ptr, uint64_t inner, uint64_t outer, uint32_t box_inner, uint32_t box_outer) {
  cuuint64_t dims[2] = {inner, outer};
  cuuint64_t strides[1] = {inner * 2};
  cuuint32_t box[2] = {box_inner, box_outer};
  cuuint32_t es[2] = {1, 1};
  enc(m, CU_TENSOR_MAP_DATA_TYPE_BFLOAT16, 2, const_cast<void*>(ptr), dims, strides, box, es, CU_TENSOR_MAP_INTERLEAVE_NONE,
      CU_TENSOR_MAP_SWIZZLE_128B, CU_TENSOR_MAP_L2_PROMOTION_L2_256B, CU_TENSOR_MAP_FLOAT_OOB_FILL_NONE);
}

struct HostState {
  bool init;
  const void* key[7];
  CUtensorMap mxA, mxB, mwA, mwB, mo, mo16, mwoA, mwoB, mout;
};
HostState g_hs;

}

extern "C" void kernel_launch(void* const* d_in, const int* in_sizes, int n_in, void* d_out, int out_size) {
  (void)in_sizes; (void)n_in; (void)out_size;
  HostState& hs = g_hs;
  bool same = hs.init && hs.key[6] == d_out;
  for (int i = 0; i < 6 && same; i++) same = hs.key[i] == d_in[i];
  if (!same) {
    void* fn = nullptr;
    cudaDriverEntryPointQueryResult qr;
    cudaGetDriverEntryPoint("cuTensorMapEncodeTiled", &fn, cudaEnableDefault, &qr);
    EncodeFn enc = (EncodeFn)fn;
    void* go = nullptr;
    cudaGetSymbolAddress(&go, g_o);
    make_map(enc, &hs.mxA, d_in[0], 512, 2048, 64, 128);
    make_map(enc, &hs.mwA, d_in[1], 1536, 512, 64, 32);
    make_map(enc, &hs.mwoA, d_in[2], 512, 512, 64, 64);
    make_map(enc, &hs.mxB, d_in[3], 512, 2048, 64, 128);
    make_map(enc, &hs.mwB, d_in[4], 1536, 512, 64, 32);
    make_map(enc, &hs.mwoB, d_in[5], 512, 512, 64, 64);
    make_map(enc, &hs.mo, go, 512, 4096, 64, 128);
    make_map(enc, &hs.mo16, go, 512, 4096, 64, 16);
    make_map(enc, &hs.mout, d_out, 1024, 2048, 64, 64);
    cudaFuncSetAttribute(qkv_gemm_kernel, cudaFuncAttributeMaxDynamicSharedMemorySize, K1_SMEM);
    cudaFuncSetAttribute(attn_kernel, cudaFuncAttributeMaxDynamicSharedMemorySize, K2_SMEM);
    for (int i = 0; i < 6; i++) hs.key[i] = d_in[i];
    hs.key[6] = d_out;
    hs.init = true;
  }
  cudaStream_t st = cudaStreamPerThread;
  {
    cudaLaunchConfig_t cfg = {};
    cfg.gridDim = dim3(128);
    cfg.blockDim = dim3(384);
    cfg.dynamicSmemBytes = K1_SMEM;
    cfg.stream = st;
    cudaLaunchAttribute at[1];
    at[0].id = cudaLaunchAttributeClusterDimension;
    at[0].val.clusterDim.x = 2;
    at[0].val.clusterDim.y = 1;
    at[0].val.clusterDim.z = 1;
    cfg.attrs = at;
    cfg.numAttrs = 1;
    cudaLaunchKernelEx(&cfg, qkv_gemm_kernel, hs.mxA, hs.mxB, hs.mwA, hs.mwB);
  }
  {
    cudaLaunchConfig_t cfg = {};
    cfg.gridDim = dim3(132);
    cfg.blockDim = dim3(512);
    cfg.dynamicSmemBytes = K2_SMEM;
    cfg.stream = st;
    cudaLaunchAttribute at[1];
    at[0].id = cudaLaunchAttributeProgrammaticStreamSerialization;
    at[0].val.programmaticStreamSerializationAllowed = 1;
    cfg.attrs = at;
    cfg.numAttrs = 1;
    cudaLaunchKernelEx(&cfg, attn_kernel, hs.mo16, hs.mo, hs.mwoA, hs.mwoB, hs.mout, (const uint8_t*)d_in[2], (const uint8_t*)d_in[5]);
  }
}
```

```cpp
#include <cuda_runtime.h>
#include <cuda_bf16.h>
#include <cuda.h>
#include <stdint.h>

namespace {

constexpr int S_LEN = 2048;
constexpr int DM = 512;
constexpr int NH = 32;

constexpr int KV_K_BYTES = 65536;
constexpr int KV_HEAD_BYTES = KV_K_BYTES + 98304;
__device__ uint4 g_qfrag[2 * NH * 32 * 128];
__device__ uint4 g_kv[NH * KV_HEAD_BYTES / 16];
__device__ float g_kvpart[16 * NH * 384];
__device__ float g_nrm[NH * 16 * 4];
__device__ __nv_bfloat16 g_o[2 * S_LEN * DM];

#define g_prof_set(k, i, v)
#define g_prof_dummy(i) true
#define PROF_T(k, i) do {} while (0)
#define PROF_G(k, i) do {} while (0)
__device__ __forceinline__ uint32_t smem_u32(const void* p) { return (uint32_t)__cvta_generic_to_shared(p); }
__device__ __forceinline__ void mbar_init(uint32_t bar, int cnt) {
  asm volatile("mbarrier.init.shared::cta.b64 [%0], %1;" ::"r"(bar), "r"(cnt) : "memory");
}
__device__ __forceinline__ void mbar_expect_tx(uint32_t bar, uint32_t bytes) {
  asm volatile("mbarrier.arrive.expect_tx.shared::cta.b64 _, [%0], %1;" ::"r"(bar), "r"(bytes) : "memory");
}
__device__ __forceinline__ void mbar_arrive(uint32_t bar) {
  asm volatile("mbarrier.arrive.shared::cta.b64 _, [%0];" ::"r"(bar) : "memory");
}
__device__ __forceinline__ void mbar_arrive_cluster(uint32_t bar, uint32_t cta) {
  asm volatile(
      "{\n.reg .b32 ra;\nmapa.shared::cluster.u32 ra, %0, %1;\n"
      "mbarrier.arrive.shared::cluster.b64 _, [ra];\n}" ::"r"(bar), "r"(cta) : "memory");
}
__device__ __forceinline__ void mbar_wait(uint32_t bar, uint32_t parity) {
  asm volatile(
      "{\n.reg .pred p;\n.reg .u32 n;\n"
      "mov.u32 n, 0;\n"
      "WAIT_LOOP:\n"
      "mbarrier.try_wait.parity.shared::cta.b64 p, [%0], %1, 0x400000;\n"
      "@p bra WAIT_DONE;\n"
      "add.u32 n, n, 1;\n"
      "setp.lt.u32 p, n, 4000000;\n"
      "@p bra WAIT_LOOP;\n"
      "trap;\n"
      "WAIT_DONE:\n}" ::"r"(bar), "r"(parity) : "memory");
}
__device__ __forceinline__ void fence_barrier_init() {
  asm volatile("fence.mbarrier_init.release.cluster;" ::: "memory");
}
__device__ __forceinline__ void fence_proxy_async() { asm volatile("fence.proxy.async.shared::cta;" ::: "memory"); }
__device__ __forceinline__ void cluster_sync_relaxed() {
  asm volatile("barrier.cluster.arrive.relaxed.aligned;\nbarrier.cluster.wait.aligned;" ::: "memory");
}
__device__ __forceinline__ void tma_load_2d(uint32_t dst, const CUtensorMap* m, int x, int y, uint32_t bar) {
  asm volatile(
      "cp.async.bulk.tensor.2d.shared::cluster.global.mbarrier::complete_tx::bytes [%0], [%1, {%3, %4}], [%2];" ::"r"(dst),
      "l"(m), "r"(bar), "r"(x), "r"(y)
      : "memory");
}
__device__ __forceinline__ void tma_load_2d_mc(uint32_t dst, const CUtensorMap* m, int x, int y, uint32_t bar, uint16_t mask) {
  asm volatile(
      "cp.async.bulk.tensor.2d.shared::cluster.global.mbarrier::complete_tx::bytes.multicast::cluster [%0], [%1, {%3, %4}], "
      "[%2], %5;" ::"r"(dst),
      "l"(m), "r"(bar), "r"(x), "r"(y), "h"(mask)
      : "memory");
}
__device__ __forceinline__ void tma_store_2d(const CUtensorMap* m, uint32_t src, int x, int y) {
  asm volatile("cp.async.bulk.tensor.2d.global.shared::cta.bulk_group [%0, {%2, %3}], [%1];" ::"l"(m), "r"(src), "r"(x),
               "r"(y)
               : "memory");
}
__device__ __forceinline__ void bulk_load(uint32_t dst, const void* src, uint32_t bytes, uint32_t bar) {
  asm volatile("cp.async.bulk.shared::cluster.global.mbarrier::complete_tx::bytes [%0], [%1], %2, [%3];" ::"r"(dst),
               "l"(src), "r"(bytes), "r"(bar)
               : "memory");
}
__device__ __forceinline__ void bulk_load_mc(uint32_t dst, const void* src, uint32_t bytes, uint32_t bar, uint16_t mask) {
  asm volatile("cp.async.bulk.shared::cluster.global.mbarrier::complete_tx::bytes.multicast::cluster [%0], [%1], %2, [%3], %4;" ::"r"(dst),
               "l"(src), "r"(bytes), "r"(bar), "h"(mask)
               : "memory");
}
__device__ __forceinline__ void pdl_launch_dependents() { asm volatile("griddepcontrol.launch_dependents;" ::: "memory"); }
__device__ __forceinline__ void pdl_wait() { asm volatile("griddepcontrol.wait;" ::: "memory"); }
__device__ __forceinline__ void wg_fence() { asm volatile("wgmma.fence.sync.aligned;" ::: "memory"); }
__device__ __forceinline__ void wg_commit() { asm volatile("wgmma.commit_group.sync.aligned;" ::: "memory"); }
template <int N>
__device__ __forceinline__ void wg_wait() {
  asm volatile("wgmma.wait_group.sync.aligned %0;" ::"n"(N) : "memory");
}
template <int M>
__device__ __forceinline__ void fence_regs(float (&r)[M]) {
#pragma unroll
  for (int i = 0; i < M; i++) asm volatile("" : "+f"(r[i])::"memory");
}
__device__ __forceinline__ uint64_t mkdesc(uint32_t addr, uint32_t lbo, uint32_t sbo, uint32_t layout) {
  return (uint64_t)((addr & 0x3FFFF) >> 4) | ((uint64_t)(lbo >> 4) << 16) | ((uint64_t)(sbo >> 4) << 32) |
         ((uint64_t)layout << 62);
}
__device__ __forceinline__ uint32_t pack_bf16(float lo, float hi) {
  uint32_t r;
  asm("cvt.rn.bf16x2.f32 %0, %1, %2;" : "=r"(r) : "f"(hi), "f"(lo));
  return r;
}
__device__ __forceinline__ float bf_lo(uint32_t v) { return __uint_as_float(v << 16); }
__device__ __forceinline__ float bf_hi(uint32_t v) { return __uint_as_float(v & 0xFFFF0000u); }
__device__ __forceinline__ float round_bf16(float x) { return bf_lo(pack_bf16(x, 0.f)); }
__device__ __forceinline__ float ex2f(float x) {
  float y;
  asm("ex2.approx.ftz.f32 %0, %1;" : "=f"(y) : "f"(x));
  return y;
}

__device__ __forceinline__ void wgmma_rs_n24_tb(float (&d)[12], uint32_t a0, uint32_t a1, uint32_t a2, uint32_t a3, uint64_t descB, int scaleD) {
  asm volatile("{\n.reg .pred p;\nsetp.ne.b32 p, %17, 0;\n"
    "wgmma.mma_async.sync.aligned.m64n24k16.f32.bf16.bf16 "
    "{%0, %1, %2, %3, %4, %5, %6, %7, %8, %9, %10, %11}, {%12, %13, %14, %15}, %16, p, 1, 1, 1;\n}\n"
    : "+f"(d[0]), "+f"(d[1]), "+f"(d[2]), "+f"(d[3]), "+f"(d[4]), "+f"(d[5]), "+f"(d[6]), "+f"(d[7]),
      "+f"(d[8]), "+f"(d[9]), "+f"(d[10]), "+f"(d[11])
    : "r"(a0), "r"(a1), "r"(a2), "r"(a3), "l"(descB), "r"(scaleD));
}
__device__ __forceinline__ void wgmma_rs_n64_z(float (&d)[32], uint32_t a0, uint32_t a1, uint32_t a2, uint32_t a3, uint64_t descB) {
  asm volatile("{\n.reg .pred p;\nsetp.ne.b32 p, %37, 0;\n"
    "wgmma.mma_async.sync.aligned.m64n64k16.f32.bf16.bf16 "
    "{%0, %1, %2, %3, %4, %5, %6, %7, %8, %9, %10, %11, %12, %13, %14, %15, %16, %17, %18, %19, %20, %21, %22, %23, %24, %25, %26, %27, %28, %29, %30, %31}, {%32, %33, %34, %35}, %36, p, 1, 1, 0;\n}\n"
    : "=f"(d[0]), "=f"(d[1]), "=f"(d[2]), "=f"(d[3]), "=f"(d[4]), "=f"(d[5]), "=f"(d[6]), "=f"(d[7]),
      "=f"(d[8]), "=f"(d[9]), "=f"(d[10]), "=f"(d[11]), "=f"(d[12]), "=f"(d[13]), "=f"(d[14]), "=f"(d[15]),
      "=f"(d[16]), "=f"(d[17]), "=f"(d[18]), "=f"(d[19]), "=f"(d[20]), "=f"(d[21]), "=f"(d[22]), "=f"(d[23]),
      "=f"(d[24]), "=f"(d[25]), "=f"(d[26]), "=f"(d[27]), "=f"(d[28]), "=f"(d[29]), "=f"(d[30]), "=f"(d[31])
    : "r"(a0), "r"(a1), "r"(a2), "r"(a3), "l"(descB), "n"(0));
}
__device__ __forceinline__ void wgmma_ss_n128_tb(float (&d)[64], uint64_t descA, uint64_t descB, int scaleD) {
  asm volatile("{\n.reg .pred p;\nsetp.ne.b32 p, %66, 0;\n"
    "wgmma.mma_async.sync.aligned.m64n128k16.f32.bf16.bf16 "
    "{%0, %1, %2, %3, %4, %5, %6, %7, %8, %9, %10, %11, %12, %13, %14, %15, %16, %17, %18, %19, %20, %21, %22, %23, %24, %25, %26, %27, %28, %29, %30, %31, %32, %33, %34, %35, %36, %37, %38, %39, %40, %41, %42, %43, %44, %45, %46, %47, %48, %49, %50, %51, %52, %53, %54, %55, %56, %57, %58, %59, %60, %61, %62, %63}, %64, %65, p, 1, 1, 0, 1;\n}\n"
    : "+f"(d[0]), "+f"(d[1]), "+f"(d[2]), "+f"(d[3]), "+f"(d[4]), "+f"(d[5]), "+f"(d[6]), "+f"(d[7]),
      "+f"(d[8]), "+f"(d[9]), "+f"(d[10]), "+f"(d[11]), "+f"(d[12]), "+f"(d[13]), "+f"(d[14]), "+f"(d[15]),
      "+f"(d[16]), "+f"(d[17]), "+f"(d[18]), "+f"(d[19]), "+f"(d[20]), "+f"(d[21]), "+f"(d[22]), "+f"(d[23]),
      "+f"(d[24]), "+f"(d[25]), "+f"(d[26]), "+f"(d[27]), "+f"(d[28]), "+f"(d[29]), "+f"(d[30]), "+f"(d[31]),
      "+f"(d[32]), "+f"(d[33]), "+f"(d[34]), "+f"(d[35]), "+f"(d[36]), "+f"(d[37]), "+f"(d[38]), "+f"(d[39]),
      "+f"(d[40]), "+f"(d[41]), "+f"(d[42]), "+f"(d[43]), "+f"(d[44]), "+f"(d[45]), "+f"(d[46]), "+f"(d[47]),
      "+f"(d[48]), "+f"(d[49]), "+f"(d[50]), "+f"(d[51]), "+f"(d[52]), "+f"(d[53]), "+f"(d[54]), "+f"(d[55]),
      "+f"(d[56]), "+f"(d[57]), "+f"(d[58]), "+f"(d[59]), "+f"(d[60]), "+f"(d[61]), "+f"(d[62]), "+f"(d[63])
    : "l"(descA), "l"(descB), "r"(scaleD));
}
__device__ __forceinline__ void wgmma_ss_n192_tb(float (&d)[96], uint64_t descA, uint64_t descB, int scaleD) {
  asm volatile("{\n.reg .pred p;\nsetp.ne.b32 p, %98, 0;\n"
    "wgmma.mma_async.sync.aligned.m64n192k16.f32.bf16.bf16 "
    "{%0, %1, %2, %3, %4, %5, %6, %7, %8, %9, %10, %11, %12, %13, %14, %15, %16, %17, %18, %19, %20, %21, %22, %23, %24, %25, %26, %27, %28, %29, %30, %31, %32, %33, %34, %35, %36, %37, %38, %39, %40, %41, %42, %43, %44, %45, %46, %47, %48, %49, %50, %51, %52, %53, %54, %55, %56, %57, %58, %59, %60, %61, %62, %63, %64, %65, %66, %67, %68, %69, %70, %71, %72, %73, %74, %75, %76, %77, %78, %79, %80, %81, %82, %83, %84, %85, %86, %87, %88, %89, %90, %91, %92, %93, %94, %95}, %96, %97, p, 1, 1, 0, 1;\n}\n"
    : "+f"(d[0]), "+f"(d[1]), "+f"(d[2]), "+f"(d[3]), "+f"(d[4]), "+f"(d[5]), "+f"(d[6]), "+f"(d[7]),
      "+f"(d[8]), "+f"(d[9]), "+f"(d[10]), "+f"(d[11]), "+f"(d[12]), "+f"(d[13]), "+f"(d[14]), "+f"(d[15]),
      "+f"(d[16]), "+f"(d[17]), "+f"(d[18]), "+f"(d[19]), "+f"(d[20]), "+f"(d[21]), "+f"(d[22]), "+f"(d[23]),
      "+f"(d[24]), "+f"(d[25]), "+f"(d[26]), "+f"(d[27]), "+f"(d[28]), "+f"(d[29]), "+f"(d[30]), "+f"(d[31]),
      "+f"(d[32]), "+f"(d[33]), "+f"(d[34]), "+f"(d[35]), "+f"(d[36]), "+f"(d[37]), "+f"(d[38]), "+f"(d[39]),
      "+f"(d[40]), "+f"(d[41]), "+f"(d[42]), "+f"(d[43]), "+f"(d[44]), "+f"(d[45]), "+f"(d[46]), "+f"(d[47]),
      "+f"(d[48]), "+f"(d[49]), "+f"(d[50]), "+f"(d[51]), "+f"(d[52]), "+f"(d[53]), "+f"(d[54]), "+f"(d[55]),
      "+f"(d[56]), "+f"(d[57]), "+f"(d[58]), "+f"(d[59]), "+f"(d[60]), "+f"(d[61]), "+f"(d[62]), "+f"(d[63]),
      "+f"(d[64]), "+f"(d[65]), "+f"(d[66]), "+f"(d[67]), "+f"(d[68]), "+f"(d[69]), "+f"(d[70]), "+f"(d[71]),
      "+f"(d[72]), "+f"(d[73]), "+f"(d[74]), "+f"(d[75]), "+f"(d[76]), "+f"(d[77]), "+f"(d[78]), "+f"(d[79]),
      "+f"(d[80]), "+f"(d[81]), "+f"(d[82]), "+f"(d[83]), "+f"(d[84]), "+f"(d[85]), "+f"(d[86]), "+f"(d[87]),
      "+f"(d[88]), "+f"(d[89]), "+f"(d[90]), "+f"(d[91]), "+f"(d[92]), "+f"(d[93]), "+f"(d[94]), "+f"(d[95])
    : "l"(descA), "l"(descB), "r"(scaleD));
}

__device__ __forceinline__ void ldsm4t(uint32_t (&b)[4], uint32_t addr) {
  asm volatile("ldmatrix.sync.aligned.m8n8.x4.trans.shared.b16 {%0,%1,%2,%3}, [%4];"
               : "=r"(b[0]), "=r"(b[1]), "=r"(b[2]), "=r"(b[3])
               : "r"(addr));
}
__device__ __forceinline__ void hmma(float (&c)[4], uint32_t a0, uint32_t a1, uint32_t a2, uint32_t a3, uint32_t b0, uint32_t b1) {
  asm("mma.sync.aligned.m16n8k16.row.col.f32.bf16.bf16.f32 {%0,%1,%2,%3}, {%4,%5,%6,%7}, {%8,%9}, {%0,%1,%2,%3};"
      : "+f"(c[0]), "+f"(c[1]), "+f"(c[2]), "+f"(c[3])
      : "r"(a0), "r"(a1), "r"(a2), "r"(a3), "r"(b0), "r"(b1));
}

__device__ __forceinline__ uint32_t movm(uint32_t a) {
  uint32_t d;
  asm volatile("movmatrix.sync.aligned.m8n8.trans.b16 %0, %1;" : "=r"(d) : "r"(a));
  return d;
}

#define K1_WARM 0
constexpr int K1_STAGES = 4;
constexpr int K1_W_BYTES = 3 * 8192;
constexpr int K1_X_BYTES = 8 * 16384;
constexpr int K1_BAR_OFF = K1_X_BYTES + K1_STAGES * K1_W_BYTES;
constexpr int K1_SMEM = K1_BAR_OFF + 192 + 1024;
constexpr float QSCALE = 0.25f * 1.4426950408889634f;

__device__ __forceinline__ uint32_t phi2(uint32_t t2) {
  uint32_t a2, mask, r2, o2;
  asm("add.rn.bf16x2 %0, %1, %2;" : "=r"(a2) : "r"(t2), "r"(0x3F803F80u));
  const uint32_t e2 = pack_bf16(ex2f(bf_lo(t2) * 1.4426950408889634f), ex2f(bf_hi(t2) * 1.4426950408889634f));
  asm("set.gt.u32.bf16x2 %0, %1, %2;" : "=r"(mask) : "r"(t2), "r"(0u));
  r2 = (a2 & mask) | (e2 & ~mask);
  asm("add.rn.bf16x2 %0, %1, %2;" : "=r"(o2) : "r"(r2), "r"(0x35863586u));
  return o2;
}

#define K1_SLOT_KB(h) ((h) < 4 ? 2 * (h) : 2 * ((h) - 4) + 1)
struct EpiCtx {
  uint4* qf;
  uint32_t* kp;
  uint32_t* vp;
  uint32_t* s_red;
  float* red;
  int lane;
};

template <bool LINEAR, int HH, int PART>
__device__ __forceinline__ void epi_slice(const float (&acc)[96], const EpiCtx& c, uint32_t (&pk)[4], float& vmax, bool live) {
  const float* a = &acc[HH * 8];
  const float* k = &acc[32 + HH * 8];
  const float* v = &acc[64 + HH * 8];
  if (!LINEAR) {
    if (PART == 0) {
      uint32_t* kh = c.kp + HH * (KV_HEAD_BYTES / 4);
      if (live) {
        c.qf[HH * 32 * 128] = make_uint4(pack_bf16(a[0] * QSCALE, a[1] * QSCALE), pack_bf16(a[2] * QSCALE, a[3] * QSCALE),
                                         pack_bf16(a[4] * QSCALE, a[5] * QSCALE), pack_bf16(a[6] * QSCALE, a[7] * QSCALE));
        kh[0] = pack_bf16(k[0], k[1]);
        kh[64] = pack_bf16(k[2], k[3]);
        kh[32] = pack_bf16(k[4], k[5]);
        kh[96] = pack_bf16(k[6], k[7]);
      }
      float q0 = a[0] * a[0] + a[1] * a[1] + a[4] * a[4] + a[5] * a[5];
      float q1 = a[2] * a[2] + a[3] * a[3] + a[6] * a[6] + a[7] * a[7];
      float k0 = k[0] * k[0] + k[1] * k[1] + k[4] * k[4] + k[5] * k[5];
      float k1 = k[2] * k[2] + k[3] * k[3] + k[6] * k[6] + k[7] * k[7];
#pragma unroll
      for (int o = 1; o <= 2; o <<= 1) {
        q0 += __shfl_xor_sync(0xffffffffu, q0, o);
        q1 += __shfl_xor_sync(0xffffffffu, q1, o);
        k0 += __shfl_xor_sync(0xffffffffu, k0, o);
        k1 += __shfl_xor_sync(0xffffffffu, k1, o);
      }
      const uint32_t qm = __reduce_max_sync(0xffffffffu, max(__float_as_uint(q0) & 0x7FFFFFFFu, __float_as_uint(q1) & 0x7FFFFFFFu));
      const uint32_t km = __reduce_max_sync(0xffffffffu, max(__float_as_uint(k0) & 0x7FFFFFFFu, __float_as_uint(k1) & 0x7FFFFFFFu));
      if (c.lane == 0 && live) {
        atomicMax(&c.s_red[HH * 2 + 0], qm);
        atomicMax(&c.s_red[HH * 2 + 1], km);
      }
    } else {
      uint32_t* vh = c.vp + HH * (KV_HEAD_BYTES / 4);
      if (live) {
        vh[0] = pack_bf16(v[0], v[1]);
        vh[96] = pack_bf16(v[2], v[3]);
        vh[32] = pack_bf16(v[4], v[5]);
        vh[128] = pack_bf16(v[6], v[7]);
        vh[64] = 0x3F803F80u;
        vh[160] = 0x3F803F80u;
      }
#pragma unroll
      for (int i = 0; i < 8; i++) asm("max.NaN.f32 %0, %0, %1;" : "+f"(vmax) : "f"(fabsf(v[i])));
    }
  } else {
    if (PART == 0) {
      const uint4 pq = make_uint4(phi2(pack_bf16(a[0], a[1])), phi2(pack_bf16(a[2], a[3])), phi2(pack_bf16(a[4], a[5])),
                                  phi2(pack_bf16(a[6], a[7])));
      if (live) c.qf[HH * 32 * 128] = pq;
      pk[0] = movm(phi2(pack_bf16(k[0], k[1])));
      pk[2] = movm(phi2(pack_bf16(k[2], k[3])));
      pk[1] = movm(phi2(pack_bf16(k[4], k[5])));
      pk[3] = movm(phi2(pack_bf16(k[6], k[7])));
    } else {
      const uint32_t b0 = movm(pack_bf16(v[0], v[1]));
      const uint32_t b1 = movm(pack_bf16(v[2], v[3]));
      const uint32_t b2 = movm(pack_bf16(v[4], v[5]));
      const uint32_t b3 = movm(pack_bf16(v[6], v[7]));
      float c0[4] = {0, 0, 0, 0}, c1[4] = {0, 0, 0, 0}, c2[4] = {0, 0, 0, 0};
      hmma(c0, pk[0], pk[1], pk[2], pk[3], b0, b1);
      hmma(c1, pk[0], pk[1], pk[2], pk[3], b2, b3);
      hmma(c2, pk[0], pk[1], pk[2], pk[3], 0x3F803F80u, 0x3F803F80u);
      float* slot = c.red + HH * 2 * 4096;
      if (live) {
#pragma unroll
        for (int i = 0; i < 4; i++) {
          slot[i * 32] = c0[i];
          slot[(4 + i) * 32] = c1[i];
          slot[(8 + i) * 32] = c2[i];
        }
      }
    }
  }
}

template <bool LINEAR>
__device__ __forceinline__ void qkv_consumer(uint32_t sbase, uint8_t* smem_gen, uint32_t* s_red, int cp, int rt) {
  const uint32_t bar_full = sbase + K1_BAR_OFF;
  const uint32_t bar_empty = bar_full + 8 * K1_STAGES;
  const int warp = threadIdx.x >> 5;
  const int wg = warp >> 2;
  const int lane = threadIdx.x & 31;
  float accN[96], accP[96];
  EpiCtx c;
  {
    const int row0 = rt * 128 + wg * 64 + (warp & 3) * 16;
    c.qf = g_qfrag + ((size_t)((LINEAR ? NH : 0) + cp * 8) * 32 + (rt * 2 + wg)) * 128 + (threadIdx.x & 127);
    uint32_t* img = reinterpret_cast<uint32_t*>(reinterpret_cast<uint8_t*>(g_kv) + (size_t)(cp * 8) * KV_HEAD_BYTES);
    c.kp = img + (row0 >> 3) * 64 + lane;
    c.vp = img + KV_K_BYTES / 4 + (row0 >> 3) * 96 + lane;
    c.s_red = s_red;
    c.red = reinterpret_cast<float*>(smem_gen + wg * 8192) + (warp & 3) * 384 + lane;
    c.lane = lane;
  }
  uint32_t pk[4] = {0, 0, 0, 0};
  float vmax = 0.f;
#pragma unroll
  for (int i = 0; i < 96; i++) asm volatile("mov.f32 %0, 0f00000000;" : "=f"(accN[i]));
  int npass;
  asm volatile("mov.u32 %0, 2;" : "=r"(npass));
#pragma unroll 1
  for (int pass = K1_WARM ? 0 : 1; pass < npass; pass++) {
    const bool live = K1_WARM ? pass != 0 : true;
    if (live) {
#pragma unroll 1
      for (int kb = 0; kb < 8; kb++) {
        const int s = kb % K1_STAGES;
        mbar_wait(bar_full + 8 * s, (kb / K1_STAGES) & 1);
        if (threadIdx.x == 0) PROF_T(0, 2 + (kb >> 1));
        const uint64_t dA = mkdesc(sbase + kb * 16384 + wg * 8192, 16, 1024, 1);
        const uint64_t dB = mkdesc(sbase + K1_X_BYTES + s * K1_W_BYTES, 8192, 1024, 1);
        wg_fence();
#pragma unroll
        for (int k = 0; k < 4; k++) wgmma_ss_n192_tb(accP, dA + k * 2, dB + k * 128, (kb | k) != 0);
        wg_commit();
        if (kb > 0) {
          wg_wait<1>();
          if ((threadIdx.x & 127) == 0) {
            const int sp = (kb - 1) % K1_STAGES;
            mbar_arrive_cluster(bar_empty + 8 * sp, 0);
            mbar_arrive_cluster(bar_empty + 8 * sp, 1);
          }
        }
      }
      wg_wait<0>();
      fence_regs(accP);
      if ((threadIdx.x & 127) == 0) {
        mbar_arrive_cluster(bar_empty + 8 * (7 % K1_STAGES), 0);
        mbar_arrive_cluster(bar_empty + 8 * (7 % K1_STAGES), 1);
      }
      if (threadIdx.x == 0) PROF_T(0, 6);
#define K1_T1_STEP(KB)                                                                           \
  {                                                                                              \
    constexpr int g = 8 + KB;                                                                    \
    constexpr int s = g % K1_STAGES;                                                             \
    mbar_wait(bar_full + 8 * s, (g / K1_STAGES) & 1);                                            \
    const uint64_t dA = mkdesc(sbase + KB * 16384 + wg * 8192, 16, 1024, 1);                     \
    const uint64_t dB = mkdesc(sbase + K1_X_BYTES + s * K1_W_BYTES, 8192, 1024, 1);              \
    wg_fence();                                                                                  \
    _Pragma("unroll") for (int k = 0; k < 4; k++) wgmma_ss_n192_tb(accN, dA + k * 2, dB + k * 128, (KB | k) != 0); \
    wg_commit();                                                                                 \
    epi_slice<LINEAR, KB / 2, KB & 1>(accP, c, pk, vmax, true);                                  \
    wg_wait<0>();                                                                                \
    if (KB + K1_STAGES < 8 && (threadIdx.x & 127) == 0) {                                        \
      mbar_arrive_cluster(bar_empty + 8 * s, 0);                                                 \
      mbar_arrive_cluster(bar_empty + 8 * s, 1);                                                 \
    }                                                                                            \
  }
      K1_T1_STEP(0) K1_T1_STEP(1) K1_T1_STEP(2) K1_T1_STEP(3) K1_T1_STEP(4) K1_T1_STEP(5) K1_T1_STEP(6) K1_T1_STEP(7)
#undef K1_T1_STEP
      fence_regs(accN);
      if (threadIdx.x == 0) PROF_T(0, 10);
      c.qf += 4 * 32 * 128;
      c.kp += 4 * (KV_HEAD_BYTES / 4);
      c.vp += 4 * (KV_HEAD_BYTES / 4);
      c.s_red += 8;
      c.red += 4096;
    }
    float vm1 = 0.f;
    epi_slice<LINEAR, 0, 0>(accN, c, pk, vm1, live);
    epi_slice<LINEAR, 0, 1>(accN, c, pk, vm1, live);
    epi_slice<LINEAR, 1, 0>(accN, c, pk, vm1, live);
    epi_slice<LINEAR, 1, 1>(accN, c, pk, vm1, live);
    epi_slice<LINEAR, 2, 0>(accN, c, pk, vm1, live);
    epi_slice<LINEAR, 2, 1>(accN, c, pk, vm1, live);
    epi_slice<LINEAR, 3, 0>(accN, c, pk, vm1, live);
    epi_slice<LINEAR, 3, 1>(accN, c, pk, vm1, live);
    if (live) asm("max.NaN.f32 %0, %0, %1;" : "+f"(vmax) : "f"(vm1));
  }
  if (!LINEAR) {
    const uint32_t vm = __reduce_max_sync(0xffffffffu, __float_as_uint(vmax) & 0x7FFFFFFFu);
    if (lane == 0) atomicMax(&s_red[16], vm);
    asm volatile("bar.sync 1, 256;" ::: "memory");
    if (threadIdx.x < 8) {
      *reinterpret_cast<float4*>(&g_nrm[((cp * 8 + threadIdx.x) * 16 + rt) * 4]) =
          make_float4(__uint_as_float(s_red[threadIdx.x * 2]), __uint_as_float(s_red[threadIdx.x * 2 + 1]), __uint_as_float(s_red[16]), 0.f);
    }
  } else {
    asm volatile("bar.sync 1, 256;" ::: "memory");
    float* dst = g_kvpart + ((size_t)rt * NH + cp * 8) * 384;
#pragma unroll
    for (int i = 0; i < 12; i++) {
      const int o = threadIdx.x + i * 256;
      const int h = o / 384, e = o - h * 384;
      const float* src = reinterpret_cast<const float*>(smem_gen) + K1_SLOT_KB(h) * 4096 + e;
      float sum = 0.f;
#pragma unroll
      for (int w = 0; w < 8; w++) sum += src[(w >> 2) * 2048 + (w & 3) * 384];
      dst[o] = sum;
    }
  }
}

__global__ void __launch_bounds__(384, 1)
qkv_gemm_kernel(const __grid_constant__ CUtensorMap mxA, const __grid_constant__ CUtensorMap mxB,
                const __grid_constant__ CUtensorMap mwA, const __grid_constant__ CUtensorMap mwB) {
  extern __shared__ uint8_t smem_raw[];
  const uint32_t sbase = (smem_u32(smem_raw) + 1023) & ~1023u;
  uint8_t* smem_gen = smem_raw + (sbase - smem_u32(smem_raw));
  const uint32_t bar_full = sbase + K1_BAR_OFF;
  const uint32_t bar_empty = bar_full + 8 * K1_STAGES;
  uint32_t* s_red = reinterpret_cast<uint32_t*>(smem_gen + K1_BAR_OFF + 64);

  const int rank = blockIdx.x & 1;
  const int pair = blockIdx.x >> 1;
  const int branch = pair >> 5;
  const int rp = (pair & 31) >> 2;
  const int cp = pair & 3;
  const int rt = rp * 2 + rank;
  const int warp = threadIdx.x >> 5;
  if (threadIdx.x == 0) { PROF_G(0, 30); PROF_T(0, 0); }
  const CUtensorMap* mx = branch ? &mxA : &mxB;
  const CUtensorMap* mw = branch ? &mwA : &mwB;

  if (threadIdx.x == 256) {
    asm volatile("prefetch.tensormap [%0];" ::"l"(mx) : "memory");
    asm volatile("prefetch.tensormap [%0];" ::"l"(mw) : "memory");
    for (int i = 0; i < K1_STAGES; i++) {
      mbar_init(bar_full + 8 * i, 1);
      mbar_init(bar_empty + 8 * i, 4);
    }
    fence_barrier_init();
    fence_proxy_async();
    for (int kb = 0; kb < K1_STAGES; kb++) mbar_expect_tx(bar_full + 8 * kb, 16384 + K1_W_BYTES);
    tma_load_2d(sbase, mx, 0, rt * 128, bar_full);
  }
  pdl_launch_dependents();
  if (threadIdx.x < 32) s_red[threadIdx.x] = 0;
  __syncthreads();
  cluster_sync_relaxed();
  if (threadIdx.x == 0) PROF_T(0, 1);

  if (warp >= 8) {
    asm volatile("setmaxnreg.dec.sync.aligned.u32 40;");
    if (threadIdx.x == 256) {
      for (int g = 0; g < 16; g++) {
        const int s = g % K1_STAGES;
        const int kb = g & 7;
        if (g >= K1_STAGES) {
          mbar_wait(bar_empty + 8 * s, ((g / K1_STAGES) - 1) & 1);
          mbar_expect_tx(bar_full + 8 * s, (g < 8 ? 16384 : 0) + K1_W_BYTES);
        }
        if (g > 0 && g < 8) tma_load_2d(sbase + kb * 16384, mx, kb * 64, rt * 128, bar_full + 8 * s);
        const int h0 = cp * 8 + (g >> 3) * 4;
        const uint32_t st = sbase + K1_X_BYTES + s * K1_W_BYTES + rank * 4096;
#pragma unroll
        for (int p = 0; p < 3; p++)
          tma_load_2d_mc(st + p * 8192, mw, p * 512 + h0 * 16, kb * 64 + rank * 32, bar_full + 8 * s, (uint16_t)3);
      }
    }
    __syncwarp();
    cluster_sync_relaxed();
  } else {
    asm volatile("setmaxnreg.inc.sync.aligned.u32 232;");
    if (branch == 0) qkv_consumer<false>(sbase, smem_gen, s_red, cp, rt);
    else qkv_consumer<true>(sbase, smem_gen, s_red, cp, rt);
    if (threadIdx.x == 0) PROF_T(0, 11);
    __syncwarp();
    cluster_sync_relaxed();
    if (threadIdx.x == 0) { PROF_T(0, 12); PROF_G(0, 31); }
  }
}

constexpr int K2_SMEM = KV_HEAD_BYTES + 1024 + 256;

#define ATT_NPOLY 18
#define ATT_CH 8
#define ATT_D 1
#define PRO_MODE 1
#define STAGGER 0
#define K2_WARM 0
#define K2_FIRST 2
#define CONST_SMID 0
#define ATT_STRUCT 1
#define ATT_PIN 0
#define ATT_GM 1
#define ATT_DEG 2
struct ExpC {
  uint32_t k3c00, kmask, seven, c3;
};
__device__ __forceinline__ uint32_t hfma2(uint32_t a, uint32_t b, uint32_t c) {
  uint32_t r;
  asm("fma.rn.f16x2 %0, %1, %2, %3;" : "=r"(r) : "r"(a), "r"(b), "r"(c));
  return r;
}
__device__ __forceinline__ uint32_t exp2_poly_pair(float t0, float t1, const ExpC& c) {
  uint32_t u;
  asm("prmt.b32 %0, %1, %2, 0x5410;" : "=r"(u) : "r"(__float_as_uint(t0)), "r"(__float_as_uint(t1)));
  uint32_t m;
  asm("lop3.b32 %0, %1, 0x03FF03FF, %2, 0xEA;" : "=r"(m) : "r"(u), "r"(c.k3c00));
  uint32_t p = hfma2(m, c.c3, 0xa385a385u);
  p = hfma2(p, m, 0x4ad64ad7u);
  uint32_t mu;
  asm("lop3.b32 %0, %1, 0xFC00FC00, %2, 0xEA;" : "=r"(mu) : "r"(u), "r"(c.kmask));
  uint32_t r;
  asm("{.reg .b32 t; shf.r.wrap.b32 t, %1, %2, 3; add.u32 %0, t, %3;}" : "=r"(r) : "r"(mu), "r"(c.seven), "r"(p));
  return r;
}
__device__ __forceinline__ float gadd(float x, float M, uint32_t g) {
  float r = x;
  asm("{.reg .pred p; setp.ne.b32 p, %2, -1; @p add.f32 %0, %0, %1;}" : "+f"(r) : "f"(M), "r"(g));
  return r;
}
__device__ __forceinline__ float gex2(float x, uint32_t g) {
  float r = x;
  asm("{.reg .pred p; setp.ne.b32 p, %1, -1; @p ex2.approx.ftz.f32 %0, %0;}" : "+f"(r) : "r"(g));
  return r;
}
template <int NPOLY, int NPAIR, int CH, int D, bool G0 = false>
__device__ __forceinline__ void exp_tile(const float (&s)[2 * NPAIR], uint32_t (&p)[NPAIR], const ExpC& c, uint32_t g0 = 0) {
#pragma unroll
  for (int i = 0; i < NPAIR; i++) {
    const bool isPoly = ((i + 1) * NPOLY / 32) != (i * NPOLY / 32);
    const int ch = i / CH;
    const bool gated = ch >= D || G0;
    int gi = (ch - D) * CH + CH - 1;
    if (ch >= D) {
      while (gi > (ch - D) * CH && !(((gi + 1) * NPOLY / 32) != (gi * NPOLY / 32))) gi--;
    }
    const uint32_t g = ch >= D ? p[gi] : g0;
    if (!isPoly) {
      if (gated && ATT_GM) p[i] = pack_bf16(gex2(s[2 * i], g), gex2(s[2 * i + 1], g));
      else p[i] = pack_bf16(ex2f(s[2 * i]), ex2f(s[2 * i + 1]));
    } else {
      if (gated) p[i] = exp2_poly_pair(gadd(s[2 * i], 12329.f, g), gadd(s[2 * i + 1], 12329.f, g), c);
      else p[i] = exp2_poly_pair(s[2 * i] + 12329.f, s[2 * i + 1] + 12329.f, c);
    }
  }
}

__device__ __forceinline__ void store_o(__nv_bfloat16* o, int row0, int head, int lane, const uint32_t (&r)[4]) {
  const int g = lane >> 2, t = lane & 3;
  uint32_t* p0 = reinterpret_cast<uint32_t*>(o + (size_t)(row0 + g) * DM + head * 16) + t;
  uint32_t* p1 = reinterpret_cast<uint32_t*>(o + (size_t)(row0 + g + 8) * DM + head * 16) + t;
  p0[0] = r[0];
  p1[0] = r[1];
  p0[4] = r[2];
  p1[4] = r[3];
}

__device__ __forceinline__ void kv_fetch_piece(uint32_t sbase, uint32_t bar, int piece) {
  const uint8_t* img = reinterpret_cast<const uint8_t*>(g_kv) + (size_t)(blockIdx.x >> 2) * KV_HEAD_BYTES;
  const int g = piece >> 1, isv = piece & 1;
  const int e0 = g == 0 ? 0 : (isv ? 256 : 320) + (g - 1) * 512;
  const int e1 = g == 3 ? 2048 : (isv ? 256 : 320) + g * 512;
  const int bytes = (e1 - e0) * (isv ? 48 : 32);
  const int off = isv ? KV_K_BYTES + e0 * 48 : e0 * 32;
  mbar_expect_tx(bar + 8 * g, bytes);
  bulk_load(sbase + off, img + off, bytes, bar + 8 * g);
}

__device__ __forceinline__ void safe_exp(const float (&s)[32], uint32_t (&p)[16], float (&o)[12], float& m0, float& m1) {
  float x0 = s[0], x1 = s[2];
#pragma unroll
  for (int i = 0; i < 8; i++) {
    x0 = fmaxf(x0, fmaxf(s[4 * i], s[4 * i + 1]));
    x1 = fmaxf(x1, fmaxf(s[4 * i + 2], s[4 * i + 3]));
  }
  x0 = fmaxf(x0, __shfl_xor_sync(0xffffffffu, x0, 1));
  x1 = fmaxf(x1, __shfl_xor_sync(0xffffffffu, x1, 1));
  x0 = fmaxf(x0, __shfl_xor_sync(0xffffffffu, x0, 2));
  x1 = fmaxf(x1, __shfl_xor_sync(0xffffffffu, x1, 2));
  const float n0 = fmaxf(m0, x0), n1 = fmaxf(m1, x1);
  const float c0 = ex2f(m0 - n0), c1 = ex2f(m1 - n1);
  m0 = n0;
  m1 = n1;
#pragma unroll
  for (int i = 0; i < 3; i++) {
    o[4 * i] *= c0;
    o[4 * i + 1] *= c0;
    o[4 * i + 2] *= c1;
    o[4 * i + 3] *= c1;
  }
#pragma unroll
  for (int i = 0; i < 8; i++) {
    p[2 * i] = pack_bf16(ex2f(s[4 * i] - n0), ex2f(s[4 * i + 1] - n0));
    p[2 * i + 1] = pack_bf16(ex2f(s[4 * i + 2] - n1), ex2f(s[4 * i + 3] - n1));
  }
}

__device__ __forceinline__ void attn_step(float (&sx)[32], float (&sy)[32], float (&o)[12], const uint4& qf, uint64_t dK, uint64_t dV,
                                          const ExpC& ec) {
  uint32_t pa[16], pb[16];
  wg_fence();
  wgmma_rs_n64_z(sy, qf.x, qf.y, qf.z, qf.w, dK + 128);
  wg_commit();
  exp_tile<ATT_NPOLY, 16, ATT_CH, ATT_D>(sx, pa, ec);
  wg_fence();
  wgmma_rs_n24_tb(o, pa[12], pa[13], pa[14], pa[15], dV + 3 * 48, 1);
  wg_commit();
  wg_wait<1>();
  fence_regs(sy);
  exp_tile<ATT_NPOLY, 16, ATT_CH, ATT_D>(sy, pb, ec);
  wg_fence();
#pragma unroll
  for (int k = 0; k < 3; k++) wgmma_rs_n24_tb(o, pa[4 * k], pa[4 * k + 1], pa[4 * k + 2], pa[4 * k + 3], dV + k * 48, 1);
#pragma unroll
  for (int k = 0; k < 4; k++) wgmma_rs_n24_tb(o, pb[4 * k], pb[4 * k + 1], pb[4 * k + 2], pb[4 * k + 3], dV + (4 + k) * 48, 1);
  wgmma_rs_n64_z(sy, qf.x, qf.y, qf.z, qf.w, dK + 256);
  wg_commit();
  wg_wait<0>();
  fence_regs(sy);
}

template <bool SAFE>
__device__ __forceinline__ void attn_tile(uint64_t dK, uint64_t dV, uint32_t bar, const uint4 qf, const ExpC& ec, uint32_t (&outp)[4],
                                          bool warm) {
  float o[12];
#pragma unroll
  for (int i = 0; i < 12; i++) asm volatile("mov.f32 %0, 0f00000000;" : "=f"(o[i]));
  if (!warm) mbar_wait(bar, 0);
  if (!SAFE) {
    float s0[32], s1[32];
    wg_fence();
    wgmma_rs_n64_z(s0, qf.x, qf.y, qf.z, qf.w, dK);
    wg_commit();
    wg_wait<0>();
    fence_regs(s0);
#pragma unroll 1
    for (int p = warm ? 7 : 0; p < 8; p++) {
      if ((p & 1) && !warm) mbar_wait(bar + 8 * min((p + 1) >> 1, 3), 0);
      attn_step(s0, s1, o, qf, dK, dV, ec);
      attn_step(s1, s0, o, qf, dK + 256, dV + 384, ec);
      dK += 512;
      dV += 768;
    }
  } else {
    float m0 = -INFINITY, m1 = -INFINITY;
#pragma unroll 1
    for (int j = 0; j < 32; j++) {
      if (j == 4) { mbar_wait(bar + 8, 0); mbar_wait(bar + 16, 0); mbar_wait(bar + 24, 0); }
      float s[32];
      uint32_t p[16];
      wg_fence();
      wgmma_rs_n64_z(s, qf.x, qf.y, qf.z, qf.w, dK);
      wg_commit();
      wg_wait<0>();
      fence_regs(s);
      safe_exp(s, p, o, m0, m1);
      wg_fence();
#pragma unroll
      for (int k = 0; k < 4; k++) wgmma_rs_n24_tb(o, p[4 * k], p[4 * k + 1], p[4 * k + 2], p[4 * k + 3], dV + k * 48, 1);
      wg_commit();
      wg_wait<0>();
      fence_regs(o);
      dK += 128;
      dV += 192;
    }
  }
  fence_regs(o);
  const float r0 = 1.0f / o[8], r1 = 1.0f / o[10];
  outp[0] = pack_bf16(o[0] * r0, o[1] * r0);
  outp[1] = pack_bf16(o[2] * r1, o[3] * r1);
  outp[2] = pack_bf16(o[4] * r0, o[5] * r0);
  outp[3] = pack_bf16(o[6] * r1, o[7] * r1);
}

__device__ __forceinline__ void linear_attn_cta(uint8_t* smem_raw, uint32_t sbase, const CUtensorMap* mo16, int cta) {
  const int warp = threadIdx.x >> 5, lane = threadIdx.x & 31;
  const int hg = warp & 1;
  const uint4* qp = g_qfrag + (size_t)(NH + cta * 8 + hg * 4) * 32 * 128 + lane;
  auto qaddr = [&](int i) {
    const int blk16 = i * 8 + (warp >> 1);
    return qp + (blk16 >> 2) * 128 + (blk16 & 3) * 32;
  };
  uint4 q[4];
#pragma unroll
  for (int h = 0; h < 4; h++) q[h] = qaddr(0)[h * 32 * 128];
  float* red = reinterpret_cast<float*>(smem_raw + (sbase - smem_u32(smem_raw)) + 131072);
  {
    const float* src = g_kvpart + (size_t)cta * 8 * 384;
    float sum[6];
#pragma unroll
    for (int i = 0; i < 6; i++) sum[i] = 0.f;
#pragma unroll
    for (int r = 0; r < 16; r++) {
#pragma unroll
      for (int i = 0; i < 6; i++) sum[i] += src[(size_t)r * NH * 384 + threadIdx.x + i * 512];
    }
#pragma unroll
    for (int i = 0; i < 6; i++) red[threadIdx.x + i * 512] = round_bf16(sum[i]);
  }
  __syncthreads();
  if (threadIdx.x == 0) PROF_T(1, 1);
  uint32_t bf[4][6];
  {
    const int g = lane >> 2, t = lane & 3;
#pragma unroll
    for (int h = 0; h < 4; h++) {
#pragma unroll
      for (int f = 0; f < 6; f++) {
        const int blk = f >> 1, half = f & 1;
        const int e = (blk == 2) ? 0 : g;
        const int d = 2 * t + 8 * half;
        const int base = (hg * 4 + h) * 384 + (blk * 4 + half * 2 + (e & 1)) * 32 + (e >> 1);
        bf[h][f] = pack_bf16(red[base + (d & 7) * 4], red[base + ((d + 1) & 7) * 4]);
      }
    }
  }
  if (threadIdx.x == 0) PROF_T(1, 2);
  const uint32_t stg = sbase + warp * 8192;
#pragma unroll 1
  for (int i = 0; i < 16; i++) {
    uint4 qc[4];
#pragma unroll
    for (int h = 0; h < 4; h++) qc[h] = q[h];
    if (i + 1 < 16) {
#pragma unroll
      for (int h = 0; h < 4; h++) q[h] = qaddr(i + 1)[h * 32 * 128];
    }
    const uint32_t buf = stg + (i & 3) * 2048;
    if (i >= 4) {
      if (lane == 0) asm volatile("cp.async.bulk.wait_group.read 3;" ::: "memory");
      __syncwarp();
    }
#pragma unroll
    for (int h = 0; h < 4; h++) {
      float n0[4] = {0, 0, 0, 0}, n1[4] = {0, 0, 0, 0}, dn[4] = {0, 0, 0, 0};
      hmma(n0, qc[h].x, qc[h].y, qc[h].z, qc[h].w, bf[h][0], bf[h][1]);
      hmma(n1, qc[h].x, qc[h].y, qc[h].z, qc[h].w, bf[h][2], bf[h][3]);
      hmma(dn, qc[h].x, qc[h].y, qc[h].z, qc[h].w, bf[h][4], bf[h][5]);
      const float d0 = __fdividef(1.0f, dn[0] + 1e-6f), d1 = __fdividef(1.0f, dn[2] + 1e-6f);
      const uint32_t r0 = pack_bf16(n0[0] * d0, n0[1] * d0);
      const uint32_t r1 = pack_bf16(n0[2] * d1, n0[3] * d1);
      const uint32_t r2 = pack_bf16(n1[0] * d0, n1[1] * d0);
      const uint32_t r3 = pack_bf16(n1[2] * d1, n1[3] * d1);
      const int row = lane & 15;
      const int chunk = h * 2 + (lane >> 4);
      const uint32_t addr = buf + row * 128 + ((chunk ^ (row & 7)) << 4);
      asm volatile("stmatrix.sync.aligned.m8n8.x4.shared.b16 [%0], {%1,%2,%3,%4};" ::"r"(addr), "r"(r0), "r"(r1), "r"(r2), "r"(r3)
                   : "memory");
    }
    fence_proxy_async();
    __syncwarp();
    if (lane == 0) {
      tma_store_2d(mo16, buf, cta * 128 + hg * 64, (i * 8 + (warp >> 1)) * 16);
      asm volatile("cp.async.bulk.commit_group;" ::: "memory");
    }
  }
  if (threadIdx.x == 0) PROF_T(1, 3);
  if (lane == 0) asm volatile("cp.async.bulk.wait_group 0;" ::: "memory");
}

__global__ void __launch_bounds__(512, 1)
attn_kernel(const __grid_constant__ CUtensorMap mo16, const uint8_t* __restrict__ woA, const uint8_t* __restrict__ woB) {
  extern __shared__ uint8_t smem_raw[];
  const uint32_t sbase = (smem_u32(smem_raw) + 1023) & ~1023u;
  const uint32_t bar = sbase + KV_HEAD_BYTES;
  if (threadIdx.x == 0) { PROF_G(1, 30); PROF_T(1, 0); }
  if (threadIdx.x == 0) {
    for (int i = 0; i < 4; i++) mbar_init(bar + 8 * i, 2);
    asm volatile("st.shared.v4.u32 [%0], {%1, %2, %3, %4};" ::"r"(bar + 64), "r"(0x3C003C00u), "r"(0x00070000u), "r"(7u),
                 "r"(ATT_DEG == 3 ? 0x2cfd2cfdu : 0x35623562u)
                 : "memory");
    fence_barrier_init();
    fence_proxy_async();
  }
  __syncthreads();
  pdl_launch_dependents();
  if (blockIdx.x >= 128 && threadIdx.x < 16) {
    const int i = (blockIdx.x - 128) * 16 + threadIdx.x;
    const uint8_t* p = (i < 32 ? woA : woB) + (size_t)(i & 31) * 16384;
    asm volatile("cp.async.bulk.prefetch.L2.global [%0], %1;" ::"l"(p), "r"(16384) : "memory");
  }
  if (blockIdx.x >= 128) {
    pdl_wait();
    linear_attn_cta(smem_raw, sbase, &mo16, blockIdx.x - 128);
    if (threadIdx.x == 0) { PROF_T(1, 5); PROF_G(1, 31); }
    return;
  }
  const int head = blockIdx.x >> 2, qb = blockIdx.x & 3;
  const int lane = threadIdx.x & 31;
  const int wg = __shfl_sync(0xffffffffu, threadIdx.x >> 7, 0), warp = __shfl_sync(0xffffffffu, (threadIdx.x >> 5) & 3, 0);
  ExpC ec;
  asm volatile("ld.volatile.shared.v4.u32 {%0, %1, %2, %3}, [%4];" : "=r"(ec.k3c00), "=r"(ec.kmask), "=r"(ec.seven), "=r"(ec.c3) : "r"(bar + 64));
  const uint64_t dK = mkdesc(sbase, 128, 256, 0);
  const uint64_t dV = mkdesc(sbase + KV_K_BYTES, 384, 128, 0);
  uint4 qnext = make_uint4(0, 0, 0, 0);
  bool safe_path = false;
#pragma unroll 1
  for (int t = (K2_WARM && blockIdx.x < 4) ? -1 : 0; t < 2; t++) {
    if (t == 0) {
      pdl_wait();
      if (threadIdx.x == 0) { PROF_T(1, 7); PROF_G(1, 29); }
      if (threadIdx.x == 0) {
#pragma unroll
        for (int piece = 0; piece < K2_FIRST; piece++) kv_fetch_piece(sbase, bar, piece);
      }
      qnext = g_qfrag[(head * 32 + qb * 8 + wg * 2) * 128 + (threadIdx.x & 127)];
      float4 n = make_float4(0.f, 0.f, 0.f, 0.f);
      if (lane < 16) n = *reinterpret_cast<const float4*>(&g_nrm[(head * 16 + lane) * 4]);
      uint32_t qm = ((lane >> 2) == qb) ? __float_as_uint(n.x) : 0u;
      qm = __reduce_max_sync(0xffffffffu, qm);
      const uint32_t km = __reduce_max_sync(0xffffffffu, __float_as_uint(n.y));
      const uint32_t vm = __reduce_max_sync(0xffffffffu, __float_as_uint(n.z));
      const float b2 = __uint_as_float(qm) * (QSCALE * QSCALE) * __uint_as_float(km) * 1.02f;
      const float vmax = __uint_as_float(vm);
      const bool ok = (b2 <= 21.5f * 21.5f) && (vmax <= 1.0e24f) && (vmax >= 1.0e-18f || vmax == 0.f);
      safe_path = !ok;
      if (K2_FIRST < 8) {
        mbar_wait(bar, 0);
        if (threadIdx.x == 0) {
#pragma unroll
          for (int piece = K2_FIRST; piece < 8; piece++) kv_fetch_piece(sbase, bar, piece);
        }
      }
    }
    const int tile64 = qb * 8 + wg * 2 + t;
    const uint4 qf = qnext;
    if (t == 0) qnext = g_qfrag[(head * 32 + tile64 + 1) * 128 + (threadIdx.x & 127)];
    uint32_t r[4];
    if (threadIdx.x == 0 && t >= 0) PROF_T(1, 1 + t);
    if (!safe_path) attn_tile<false>(dK, dV, bar, qf, ec, r, t < 0);
    else attn_tile<true>(dK, dV, bar, qf, ec, r, false);
    if (t >= 0) store_o(g_o + (size_t)S_LEN * DM, tile64 * 64 + warp * 16, head, lane, r);
  }
  if (threadIdx.x == 0) { PROF_T(1, 5); PROF_G(1, 31); }
}

#define K3_WPRE 2
constexpr int K3_STAGES = 5;
constexpr int K3_W_BYTES = 8 * 16384;
constexpr int K3_BAR_OFF = K3_W_BYTES + K3_STAGES * 16384;
constexpr int K3_SMEM = K3_BAR_OFF + 256 + 1024;

__global__ void __launch_bounds__(288, 1)
out_gemm_kernel(const __grid_constant__ CUtensorMap mo, const __grid_constant__ CUtensorMap mwA,
                const __grid_constant__ CUtensorMap mwB, const __grid_constant__ CUtensorMap mout) {
  extern __shared__ uint8_t smem_raw[];
  const uint32_t sbase = (smem_u32(smem_raw) + 1023) & ~1023u;
  const uint32_t bar_full = sbase + K3_BAR_OFF;
  const uint32_t bar_empty = bar_full + 8 * K3_STAGES;
  const uint32_t bar_w = bar_empty + 8 * K3_STAGES;
  const int branch = blockIdx.x >> 6;
  const int rt = (blockIdx.x & 63) >> 2;
  const int ct = blockIdx.x & 3;
  const int warp = threadIdx.x >> 5;
  if (threadIdx.x == 0) { PROF_G(2, 30); PROF_T(2, 0); }
  if (threadIdx.x == 256) {
    const CUtensorMap* mw = branch ? &mwB : &mwA;
    asm volatile("prefetch.tensormap [%0];" ::"l"(mw) : "memory");
    asm volatile("prefetch.tensormap [%0];" ::"l"(&mo) : "memory");
    asm volatile("prefetch.tensormap [%0];" ::"l"(&mout) : "memory");
    for (int i = 0; i < K3_STAGES; i++) {
      mbar_init(bar_full + 8 * i, 1);
      mbar_init(bar_empty + 8 * i, 2);
    }
    for (int i = 0; i < 8; i++) mbar_init(bar_w + 8 * i, 1);
    fence_barrier_init();
    fence_proxy_async();
    for (int kb = 0; kb < K3_WPRE; kb++) {
      mbar_expect_tx(bar_w + 8 * kb, 16384);
      tma_load_2d(sbase + kb * 16384, mw, ct * 128, kb * 64, bar_w + 8 * kb);
      tma_load_2d(sbase + kb * 16384 + 8192, mw, ct * 128 + 64, kb * 64, bar_w + 8 * kb);
    }
  }
  __syncthreads();
  if (warp == 8) {
    if ((threadIdx.x & 31) == 0) {
      const CUtensorMap* mw = branch ? &mwB : &mwA;
      pdl_wait();
      PROF_T(2, 1);
      for (int kb = 0; kb < 8; kb++) {
        const int s = kb % K3_STAGES;
        if (kb >= K3_STAGES) mbar_wait(bar_empty + 8 * s, ((kb / K3_STAGES) - 1) & 1);
        mbar_expect_tx(bar_full + 8 * s, 16384);
        tma_load_2d(sbase + K3_W_BYTES + s * 16384, &mo, kb * 64, branch * S_LEN + rt * 128, bar_full + 8 * s);
        const int kw = kb + K3_WPRE;
        if (kw < 8) {
          mbar_expect_tx(bar_w + 8 * kw, 16384);
          tma_load_2d(sbase + kw * 16384, mw, ct * 128, kw * 64, bar_w + 8 * kw);
          tma_load_2d(sbase + kw * 16384 + 8192, mw, ct * 128 + 64, kw * 64, bar_w + 8 * kw);
        }
      }
    }
  } else {
    const int wg = warp >> 2;
    float acc[64];
    for (int kb = 0; kb < 8; kb++) {
      const int s = kb % K3_STAGES;
      mbar_wait(bar_w + 8 * kb, 0);
      mbar_wait(bar_full + 8 * s, (kb / K3_STAGES) & 1);
      if (threadIdx.x == 0) PROF_T(2, 2 + kb);
      const uint64_t dA = mkdesc(sbase + K3_W_BYTES + s * 16384 + wg * 8192, 16, 1024, 1);
      const uint64_t dB = mkdesc(sbase + kb * 16384, 8192, 1024, 1);
      wg_fence();
#pragma unroll
      for (int k = 0; k < 4; k++) wgmma_ss_n128_tb(acc, dA + k * 2, dB + k * 128, (kb | k) != 0);
      wg_commit();
      if (kb > 0) {
        wg_wait<1>();
        if ((threadIdx.x & 127) == 0) mbar_arrive(bar_empty + 8 * ((kb - 1) % K3_STAGES));
      }
    }
    wg_wait<0>();
    fence_regs(acc);
    if (threadIdx.x == 0) PROF_T(2, 10);
    const uint32_t stg = sbase + K3_W_BYTES + wg * 8192;
    const int lane = threadIdx.x & 31;
    const int rloc = (warp & 3) * 16 + (lane & 15);
#pragma unroll
    for (int c16 = 0; c16 < 8; c16++) {
      const float* a = &acc[c16 * 8];
      const uint32_t r0 = pack_bf16(a[0], a[1]), r1 = pack_bf16(a[2], a[3]), r2 = pack_bf16(a[4], a[5]), r3 = pack_bf16(a[6], a[7]);
      const int chunk = (c16 & 3) * 2 + (lane >> 4);
      const uint32_t addr = stg + (c16 >> 2) * 16384 + rloc * 128 + ((chunk ^ (rloc & 7)) << 4);
      asm volatile("stmatrix.sync.aligned.m8n8.x4.shared.b16 [%0], {%1,%2,%3,%4};" ::"r"(addr), "r"(r0), "r"(r1), "r"(r2), "r"(r3)
                   : "memory");
    }
    fence_proxy_async();
    asm volatile("bar.sync %0, 128;" ::"r"(2 + wg) : "memory");
    if ((threadIdx.x & 127) == 0) {
      tma_store_2d(&mout, stg, branch * DM + ct * 128, rt * 128 + wg * 64);
      tma_store_2d(&mout, stg + 16384, branch * DM + ct * 128 + 64, rt * 128 + wg * 64);
      asm volatile("cp.async.bulk.commit_group;" ::: "memory");
      asm volatile("cp.async.bulk.wait_group.read 0;" ::: "memory");
      if (threadIdx.x == 0) { PROF_T(2, 12); PROF_G(2, 31); }
    }
  }
}

typedef CUresult (*EncodeFn)(CUtensorMap*, CUtensorMapDataType, cuuint32_t, void*, const cuuint64_t*, const cuuint64_t*,
                             const cuuint32_t*, const cuuint32_t*, CUtensorMapInterleave, CUtensorMapSwizzle,
                             CUtensorMapL2promotion, CUtensorMapFloatOOBfill);

void make_map(EncodeFn enc, CUtensorMap* m, const void* ptr, uint64_t inner, uint64_t outer, uint32_t box_inner, uint32_t box_outer) {
  cuuint64_t dims[2] = {inner, outer};
  cuuint64_t strides[1] = {inner * 2};
  cuuint32_t box[2] = {box_inner, box_outer};
  cuuint32_t es[2] = {1, 1};
  enc(m, CU_TENSOR_MAP_DATA_TYPE_BFLOAT16, 2, const_cast<void*>(ptr), dims, strides, box, es, CU_TENSOR_MAP_INTERLEAVE_NONE,
      CU_TENSOR_MAP_SWIZZLE_128B, CU_TENSOR_MAP_L2_PROMOTION_L2_256B, CU_TENSOR_MAP_FLOAT_OOB_FILL_NONE);
}

struct HostState {
  bool init;
  const void* key[7];
  CUtensorMap mxA, mxB, mwA, mwB, mo, mo16, mwoA, mwoB, mout;
};
HostState g_hs;

}

extern "C" void kernel_launch(void* const* d_in, const int* in_sizes, int n_in, void* d_out, int out_size) {
  (void)in_sizes; (void)n_in; (void)out_size;
  HostState& hs = g_hs;
  bool same = hs.init && hs.key[6] == d_out;
  for (int i = 0; i < 6 && same; i++) same = hs.key[i] == d_in[i];
  if (!same) {
    void* fn = nullptr;
    cudaDriverEntryPointQueryResult qr;
    cudaGetDriverEntryPoint("cuTensorMapEncodeTiled", &fn, cudaEnableDefault, &qr);
    EncodeFn enc = (EncodeFn)fn;
    void* go = nullptr;
    cudaGetSymbolAddress(&go, g_o);
    make_map(enc, &hs.mxA, d_in[0], 512, 2048, 64, 128);
    make_map(enc, &hs.mwA, d_in[1], 1536, 512, 64, 32);
    make_map(enc, &hs.mwoA, d_in[2], 512, 512, 64, 64);
    make_map(enc, &hs.mxB, d_in[3], 512, 2048, 64, 128);
    make_map(enc, &hs.mwB, d_in[4], 1536, 512, 64, 32);
    make_map(enc, &hs.mwoB, d_in[5], 512, 512, 64, 64);
    make_map(enc, &hs.mo, go, 512, 4096, 64, 128);
    make_map(enc, &hs.mo16, go, 512, 4096, 64, 16);
    make_map(enc, &hs.mout, d_out, 1024, 2048, 64, 64);
    cudaFuncSetAttribute(qkv_gemm_kernel, cudaFuncAttributeMaxDynamicSharedMemorySize, K1_SMEM);
    cudaFuncSetAttribute(attn_kernel, cudaFuncAttributeMaxDynamicSharedMemorySize, K2_SMEM);
    cudaFuncSetAttribute(out_gemm_kernel, cudaFuncAttributeMaxDynamicSharedMemorySize, K3_SMEM);
    for (int i = 0; i < 6; i++) hs.key[i] = d_in[i];
    hs.key[6] = d_out;
    hs.init = true;
  }
  cudaStream_t st = cudaStreamPerThread;
  {
    cudaLaunchConfig_t cfg = {};
    cfg.gridDim = dim3(128);
    cfg.blockDim = dim3(384);
    cfg.dynamicSmemBytes = K1_SMEM;
    cfg.stream = st;
    cudaLaunchAttribute at[1];
    at[0].id = cudaLaunchAttributeClusterDimension;
    at[0].val.clusterDim.x = 2;
    at[0].val.clusterDim.y = 1;
    at[0].val.clusterDim.z = 1;
    cfg.attrs = at;
    cfg.numAttrs = 1;
    cudaLaunchKernelEx(&cfg, qkv_gemm_kernel, hs.mxA, hs.mxB, hs.mwA, hs.mwB);
  }
  {
    cudaLaunchConfig_t cfg = {};
    cfg.gridDim = dim3(132);
    cfg.blockDim = dim3(512);
    cfg.dynamicSmemBytes = K2_SMEM;
    cfg.stream = st;
    cudaLaunchAttribute at[1];
    at[0].id = cudaLaunchAttributeProgrammaticStreamSerialization;
    at[0].val.programmaticStreamSerializationAllowed = 1;
    cfg.attrs = at;
    cfg.numAttrs = 1;
    cudaLaunchKernelEx(&cfg, attn_kernel, hs.mo16, (const uint8_t*)d_in[2], (const uint8_t*)d_in[5]);
    cfg.gridDim = dim3(128);
    cfg.blockDim = dim3(288);
    cfg.dynamicSmemBytes = K3_SMEM;
    cudaLaunchKernelEx(&cfg, out_gemm_kernel, hs.mo, hs.mwoA, hs.mwoB, hs.mout);
  }
}
```

```cpp
#include <cuda_runtime.h>
#include <cuda_bf16.h>
#include <cuda.h>
#include <stdint.h>

namespace {

constexpr int S_LEN = 2048;
constexpr int DM = 512;
constexpr int NH = 32;

constexpr int KV_K_BYTES = 65536;
constexpr int KV_HEAD_BYTES = KV_K_BYTES + 98304;
__device__ uint4 g_qfrag[2 * NH * 32 * 128];
__device__ uint4 g_kv[NH * KV_HEAD_BYTES / 16];
__device__ float g_kvpart[16 * NH * 384];
__device__ float g_nrm[NH * 16 * 4];
__device__ __nv_bfloat16 g_o[2 * S_LEN * DM];

#define g_prof_set(k, i, v)
#define g_prof_dummy(i) true
#define PROF_T(k, i) do {} while (0)
#define PROF_G(k, i) do {} while (0)
__device__ __forceinline__ uint32_t smem_u32(const void* p) { return (uint32_t)__cvta_generic_to_shared(p); }
__device__ __forceinline__ void mbar_init(uint32_t bar, int cnt) {
  asm volatile("mbarrier.init.shared::cta.b64 [%0], %1;" ::"r"(bar), "r"(cnt) : "memory");
}
__device__ __forceinline__ void mbar_expect_tx(uint32_t bar, uint32_t bytes) {
  asm volatile("mbarrier.arrive.expect_tx.shared::cta.b64 _, [%0], %1;" ::"r"(bar), "r"(bytes) : "memory");
}
__device__ __forceinline__ void mbar_arrive(uint32_t bar) {
  asm volatile("mbarrier.arrive.shared::cta.b64 _, [%0];" ::"r"(bar) : "memory");
}
__device__ __forceinline__ void mbar_arrive_cluster(uint32_t bar, uint32_t cta) {
  asm volatile(
      "{\n.reg .b32 ra;\nmapa.shared::cluster.u32 ra, %0, %1;\n"
      "mbarrier.arrive.shared::cluster.b64 _, [ra];\n}" ::"r"(bar), "r"(cta) : "memory");
}
__device__ __forceinline__ void mbar_wait(uint32_t bar, uint32_t parity) {
  asm volatile(
      "{\n.reg .pred p;\n.reg .u32 n;\n"
      "mov.u32 n, 0;\n"
      "WAIT_LOOP:\n"
      "mbarrier.try_wait.parity.shared::cta.b64 p, [%0], %1, 0x400000;\n"
      "@p bra WAIT_DONE;\n"
      "add.u32 n, n, 1;\n"
      "setp.lt.u32 p, n, 4000000;\n"
      "@p bra WAIT_LOOP;\n"
      "trap;\n"
      "WAIT_DONE:\n}" ::"r"(bar), "r"(parity) : "memory");
}
__device__ __forceinline__ void fence_barrier_init() {
  asm volatile("fence.mbarrier_init.release.cluster;" ::: "memory");
}
__device__ __forceinline__ void fence_proxy_async() { asm volatile("fence.proxy.async.shared::cta;" ::: "memory"); }
__device__ __forceinline__ void cluster_sync_relaxed() {
  asm volatile("barrier.cluster.arrive.relaxed.aligned;\nbarrier.cluster.wait.aligned;" ::: "memory");
}
__device__ __forceinline__ void tma_load_2d(uint32_t dst, const CUtensorMap* m, int x, int y, uint32_t bar) {
  asm volatile(
      "cp.async.bulk.tensor.2d.shared::cluster.global.mbarrier::complete_tx::bytes [%0], [%1, {%3, %4}], [%2];" ::"r"(dst),
      "l"(m), "r"(bar), "r"(x), "r"(y)
      : "memory");
}
__device__ __forceinline__ void tma_load_2d_mc(uint32_t dst, const CUtensorMap* m, int x, int y, uint32_t bar, uint16_t mask) {
  asm volatile(
      "cp.async.bulk.tensor.2d.shared::cluster.global.mbarrier::complete_tx::bytes.multicast::cluster [%0], [%1, {%3, %4}], "
      "[%2], %5;" ::"r"(dst),
      "l"(m), "r"(bar), "r"(x), "r"(y), "h"(mask)
      : "memory");
}
__device__ __forceinline__ void tma_store_2d(const CUtensorMap* m, uint32_t src, int x, int y) {
  asm volatile("cp.async.bulk.tensor.2d.global.shared::cta.bulk_group [%0, {%2, %3}], [%1];" ::"l"(m), "r"(src), "r"(x),
               "r"(y)
               : "memory");
}
__device__ __forceinline__ void bulk_load(uint32_t dst, const void* src, uint32_t bytes, uint32_t bar) {
  asm volatile("cp.async.bulk.shared::cluster.global.mbarrier::complete_tx::bytes [%0], [%1], %2, [%3];" ::"r"(dst),
               "l"(src), "r"(bytes), "r"(bar)
               : "memory");
}
__device__ __forceinline__ void bulk_load_mc(uint32_t dst, const void* src, uint32_t bytes, uint32_t bar, uint16_t mask) {
  asm volatile("cp.async.bulk.shared::cluster.global.mbarrier::complete_tx::bytes.multicast::cluster [%0], [%1], %2, [%3], %4;" ::"r"(dst),
               "l"(src), "r"(bytes), "r"(bar), "h"(mask)
               : "memory");
}
__device__ __forceinline__ void pdl_launch_dependents() { asm volatile("griddepcontrol.launch_dependents;" ::: "memory"); }
__device__ __forceinline__ void pdl_wait() { asm volatile("griddepcontrol.wait;" ::: "memory"); }
__device__ __forceinline__ void wg_fence() { asm volatile("wgmma.fence.sync.aligned;" ::: "memory"); }
__device__ __forceinline__ void wg_commit() { asm volatile("wgmma.commit_group.sync.aligned;" ::: "memory"); }
template <int N>
__device__ __forceinline__ void wg_wait() {
  asm volatile("wgmma.wait_group.sync.aligned %0;" ::"n"(N) : "memory");
}
template <int M>
__device__ __forceinline__ void fence_regs(float (&r)[M]) {
#pragma unroll
  for (int i = 0; i < M; i++) asm volatile("" : "+f"(r[i])::"memory");
}
__device__ __forceinline__ uint64_t mkdesc(uint32_t addr, uint32_t lbo, uint32_t sbo, uint32_t layout) {
  return (uint64_t)((addr & 0x3FFFF) >> 4) | ((uint64_t)(lbo >> 4) << 16) | ((uint64_t)(sbo >> 4) << 32) |
         ((uint64_t)layout << 62);
}
__device__ __forceinline__ uint32_t pack_bf16(float lo, float hi) {
  uint32_t r;
  asm("cvt.rn.bf16x2.f32 %0, %1, %2;" : "=r"(r) : "f"(hi), "f"(lo));
  return r;
}
__device__ __forceinline__ float bf_lo(uint32_t v) { return __uint_as_float(v << 16); }
__device__ __forceinline__ float bf_hi(uint32_t v) { return __uint_as_float(v & 0xFFFF0000u); }
__device__ __forceinline__ float round_bf16(float x) { return bf_lo(pack_bf16(x, 0.f)); }
__device__ __forceinline__ float ex2f(float x) {
  float y;
  asm("ex2.approx.ftz.f32 %0, %1;" : "=f"(y) : "f"(x));
  return y;
}

__device__ __forceinline__ void wgmma_rs_n24_tb(float (&d)[12], uint32_t a0, uint32_t a1, uint32_t a2, uint32_t a3, uint64_t descB, int scaleD) {
  asm volatile("{\n.reg .pred p;\nsetp.ne.b32 p, %17, 0;\n"
    "wgmma.mma_async.sync.aligned.m64n24k16.f32.bf16.bf16 "
    "{%0, %1, %2, %3, %4, %5, %6, %7, %8, %9, %10, %11}, {%12, %13, %14, %15}, %16, p, 1, 1, 1;\n}\n"
    : "+f"(d[0]), "+f"(d[1]), "+f"(d[2]), "+f"(d[3]), "+f"(d[4]), "+f"(d[5]), "+f"(d[6]), "+f"(d[7]),
      "+f"(d[8]), "+f"(d[9]), "+f"(d[10]), "+f"(d[11])
    : "r"(a0), "r"(a1), "r"(a2), "r"(a3), "l"(descB), "r"(scaleD));
}
__device__ __forceinline__ void wgmma_rs_n64_z(float (&d)[32], uint32_t a0, uint32_t a1, uint32_t a2, uint32_t a3, uint64_t descB) {
  asm volatile("{\n.reg .pred p;\nsetp.ne.b32 p, %37, 0;\n"
    "wgmma.mma_async.sync.aligned.m64n64k16.f32.bf16.bf16 "
    "{%0, %1, %2, %3, %4, %5, %6, %7, %8, %9, %10, %11, %12, %13, %14, %15, %16, %17, %18, %19, %20, %21, %22, %23, %24, %25, %26, %27, %28, %29, %30, %31}, {%32, %33, %34, %35}, %36, p, 1, 1, 0;\n}\n"
    : "=f"(d[0]), "=f"(d[1]), "=f"(d[2]), "=f"(d[3]), "=f"(d[4]), "=f"(d[5]), "=f"(d[6]), "=f"(d[7]),
      "=f"(d[8]), "=f"(d[9]), "=f"(d[10]), "=f"(d[11]), "=f"(d[12]), "=f"(d[13]), "=f"(d[14]), "=f"(d[15]),
      "=f"(d[16]), "=f"(d[17]), "=f"(d[18]), "=f"(d[19]), "=f"(d[20]), "=f"(d[21]), "=f"(d[22]), "=f"(d[23]),
      "=f"(d[24]), "=f"(d[25]), "=f"(d[26]), "=f"(d[27]), "=f"(d[28]), "=f"(d[29]), "=f"(d[30]), "=f"(d[31])
    : "r"(a0), "r"(a1), "r"(a2), "r"(a3), "l"(descB), "n"(0));
}
__device__ __forceinline__ void wgmma_ss_n128_tb(float (&d)[64], uint64_t descA, uint64_t descB, int scaleD) {
  asm volatile("{\n.reg .pred p;\nsetp.ne.b32 p, %66, 0;\n"
    "wgmma.mma_async.sync.aligned.m64n128k16.f32.bf16.bf16 "
    "{%0, %1, %2, %3, %4, %5, %6, %7, %8, %9, %10, %11, %12, %13, %14, %15, %16, %17, %18, %19, %20, %21, %22, %23, %24, %25, %26, %27, %28, %29, %30, %31, %32, %33, %34, %35, %36, %37, %38, %39, %40, %41, %42, %43, %44, %45, %46, %47, %48, %49, %50, %51, %52, %53, %54, %55, %56, %57, %58, %59, %60, %61, %62, %63}, %64, %65, p, 1, 1, 0, 1;\n}\n"
    : "+f"(d[0]), "+f"(d[1]), "+f"(d[2]), "+f"(d[3]), "+f"(d[4]), "+f"(d[5]), "+f"(d[6]), "+f"(d[7]),
      "+f"(d[8]), "+f"(d[9]), "+f"(d[10]), "+f"(d[11]), "+f"(d[12]), "+f"(d[13]), "+f"(d[14]), "+f"(d[15]),
      "+f"(d[16]), "+f"(d[17]), "+f"(d[18]), "+f"(d[19]), "+f"(d[20]), "+f"(d[21]), "+f"(d[22]), "+f"(d[23]),
      "+f"(d[24]), "+f"(d[25]), "+f"(d[26]), "+f"(d[27]), "+f"(d[28]), "+f"(d[29]), "+f"(d[30]), "+f"(d[31]),
      "+f"(d[32]), "+f"(d[33]), "+f"(d[34]), "+f"(d[35]), "+f"(d[36]), "+f"(d[37]), "+f"(d[38]), "+f"(d[39]),
      "+f"(d[40]), "+f"(d[41]), "+f"(d[42]), "+f"(d[43]), "+f"(d[44]), "+f"(d[45]), "+f"(d[46]), "+f"(d[47]),
      "+f"(d[48]), "+f"(d[49]), "+f"(d[50]), "+f"(d[51]), "+f"(d[52]), "+f"(d[53]), "+f"(d[54]), "+f"(d[55]),
      "+f"(d[56]), "+f"(d[57]), "+f"(d[58]), "+f"(d[59]), "+f"(d[60]), "+f"(d[61]), "+f"(d[62]), "+f"(d[63])
    : "l"(descA), "l"(descB), "r"(scaleD));
}
__device__ __forceinline__ void wgmma_ss_n192_tb(float (&d)[96], uint64_t descA, uint64_t descB, int scaleD) {
  asm volatile("{\n.reg .pred p;\nsetp.ne.b32 p, %98, 0;\n"
    "wgmma.mma_async.sync.aligned.m64n192k16.f32.bf16.bf16 "
    "{%0, %1, %2, %3, %4, %5, %6, %7, %8, %9, %10, %11, %12, %13, %14, %15, %16, %17, %18, %19, %20, %21, %22, %23, %24, %25, %26, %27, %28, %29, %30, %31, %32, %33, %34, %35, %36, %37, %38, %39, %40, %41, %42, %43, %44, %45, %46, %47, %48, %49, %50, %51, %52, %53, %54, %55, %56, %57, %58, %59, %60, %61, %62, %63, %64, %65, %66, %67, %68, %69, %70, %71, %72, %73, %74, %75, %76, %77, %78, %79, %80, %81, %82, %83, %84, %85, %86, %87, %88, %89, %90, %91, %92, %93, %94, %95}, %96, %97, p, 1, 1, 0, 1;\n}\n"
    : "+f"(d[0]), "+f"(d[1]), "+f"(d[2]), "+f"(d[3]), "+f"(d[4]), "+f"(d[5]), "+f"(d[6]), "+f"(d[7]),
      "+f"(d[8]), "+f"(d[9]), "+f"(d[10]), "+f"(d[11]), "+f"(d[12]), "+f"(d[13]), "+f"(d[14]), "+f"(d[15]),
      "+f"(d[16]), "+f"(d[17]), "+f"(d[18]), "+f"(d[19]), "+f"(d[20]), "+f"(d[21]), "+f"(d[22]), "+f"(d[23]),
      "+f"(d[24]), "+f"(d[25]), "+f"(d[26]), "+f"(d[27]), "+f"(d[28]), "+f"(d[29]), "+f"(d[30]), "+f"(d[31]),
      "+f"(d[32]), "+f"(d[33]), "+f"(d[34]), "+f"(d[35]), "+f"(d[36]), "+f"(d[37]), "+f"(d[38]), "+f"(d[39]),
      "+f"(d[40]), "+f"(d[41]), "+f"(d[42]), "+f"(d[43]), "+f"(d[44]), "+f"(d[45]), "+f"(d[46]), "+f"(d[47]),
      "+f"(d[48]), "+f"(d[49]), "+f"(d[50]), "+f"(d[51]), "+f"(d[52]), "+f"(d[53]), "+f"(d[54]), "+f"(d[55]),
      "+f"(d[56]), "+f"(d[57]), "+f"(d[58]), "+f"(d[59]), "+f"(d[60]), "+f"(d[61]), "+f"(d[62]), "+f"(d[63]),
      "+f"(d[64]), "+f"(d[65]), "+f"(d[66]), "+f"(d[67]), "+f"(d[68]), "+f"(d[69]), "+f"(d[70]), "+f"(d[71]),
      "+f"(d[72]), "+f"(d[73]), "+f"(d[74]), "+f"(d[75]), "+f"(d[76]), "+f"(d[77]), "+f"(d[78]), "+f"(d[79]),
      "+f"(d[80]), "+f"(d[81]), "+f"(d[82]), "+f"(d[83]), "+f"(d[84]), "+f"(d[85]), "+f"(d[86]), "+f"(d[87]),
      "+f"(d[88]), "+f"(d[89]), "+f"(d[90]), "+f"(d[91]), "+f"(d[92]), "+f"(d[93]), "+f"(d[94]), "+f"(d[95])
    : "l"(descA), "l"(descB), "r"(scaleD));
}

__device__ __forceinline__ void ldsm4t(uint32_t (&b)[4], uint32_t addr) {
  asm volatile("ldmatrix.sync.aligned.m8n8.x4.trans.shared.b16 {%0,%1,%2,%3}, [%4];"
               : "=r"(b[0]), "=r"(b[1]), "=r"(b[2]), "=r"(b[3])
               : "r"(addr));
}
__device__ __forceinline__ void hmma(float (&c)[4], uint32_t a0, uint32_t a1, uint32_t a2, uint32_t a3, uint32_t b0, uint32_t b1) {
  asm("mma.sync.aligned.m16n8k16.row.col.f32.bf16.bf16.f32 {%0,%1,%2,%3}, {%4,%5,%6,%7}, {%8,%9}, {%0,%1,%2,%3};"
      : "+f"(c[0]), "+f"(c[1]), "+f"(c[2]), "+f"(c[3])
      : "r"(a0), "r"(a1), "r"(a2), "r"(a3), "r"(b0), "r"(b1));
}

__device__ __forceinline__ uint32_t movm(uint32_t a) {
  uint32_t d;
  asm volatile("movmatrix.sync.aligned.m8n8.trans.b16 %0, %1;" : "=r"(d) : "r"(a));
  return d;
}

#define K1_WARM 0
constexpr int K1_STAGES = 4;
constexpr int K1_W_BYTES = 3 * 8192;
constexpr int K1_X_BYTES = 8 * 16384;
constexpr int K1_BAR_OFF = K1_X_BYTES + K1_STAGES * K1_W_BYTES;
constexpr int K1_SMEM = K1_BAR_OFF + 192 + 1024;
constexpr float QSCALE = 0.25f * 1.4426950408889634f;

__device__ __forceinline__ uint32_t phi2(uint32_t t2) {
  uint32_t a2, mask, r2, o2;
  asm("add.rn.bf16x2 %0, %1, %2;" : "=r"(a2) : "r"(t2), "r"(0x3F803F80u));
  const uint32_t e2 = pack_bf16(ex2f(bf_lo(t2) * 1.4426950408889634f), ex2f(bf_hi(t2) * 1.4426950408889634f));
  asm("set.gt.u32.bf16x2 %0, %1, %2;" : "=r"(mask) : "r"(t2), "r"(0u));
  r2 = (a2 & mask) | (e2 & ~mask);
  asm("add.rn.bf16x2 %0, %1, %2;" : "=r"(o2) : "r"(r2), "r"(0x35863586u));
  return o2;
}

#define K1_SLOT_KB(h) ((h) < 4 ? 2 * (h) : 2 * ((h) - 4) + 1)
struct EpiCtx {
  uint4* qf;
  uint32_t* kp;
  uint32_t* vp;
  uint32_t s_red_addr;
  float* red;
  int lane;
};

template <bool LINEAR, int HH, int PART>
__device__ __forceinline__ void epi_slice(const float (&acc)[96], const EpiCtx& c, uint32_t (&pk)[4], float& vmax, bool live) {
  const float* a = &acc[HH * 8];
  const float* k = &acc[32 + HH * 8];
  const float* v = &acc[64 + HH * 8];
  if (!LINEAR) {
    if (PART == 0) {
      uint32_t* kh = c.kp + HH * (KV_HEAD_BYTES / 4);
      if (live) {
        c.qf[HH * 32 * 128] = make_uint4(pack_bf16(a[0] * QSCALE, a[1] * QSCALE), pack_bf16(a[2] * QSCALE, a[3] * QSCALE),
                                         pack_bf16(a[4] * QSCALE, a[5] * QSCALE), pack_bf16(a[6] * QSCALE, a[7] * QSCALE));
        kh[0] = pack_bf16(k[0], k[1]);
        kh[64] = pack_bf16(k[2], k[3]);
        kh[32] = pack_bf16(k[4], k[5]);
        kh[96] = pack_bf16(k[6], k[7]);
      }
      float q0 = a[0] * a[0] + a[1] * a[1] + a[4] * a[4] + a[5] * a[5];
      float q1 = a[2] * a[2] + a[3] * a[3] + a[6] * a[6] + a[7] * a[7];
      float k0 = k[0] * k[0] + k[1] * k[1] + k[4] * k[4] + k[5] * k[5];
      float k1 = k[2] * k[2] + k[3] * k[3] + k[6] * k[6] + k[7] * k[7];
#pragma unroll
      for (int o = 1; o <= 2; o <<= 1) {
        q0 += __shfl_xor_sync(0xffffffffu, q0, o);
        q1 += __shfl_xor_sync(0xffffffffu, q1, o);
        k0 += __shfl_xor_sync(0xffffffffu, k0, o);
        k1 += __shfl_xor_sync(0xffffffffu, k1, o);
      }
      const uint32_t qm = __reduce_max_sync(0xffffffffu, max(__float_as_uint(q0) & 0x7FFFFFFFu, __float_as_uint(q1) & 0x7FFFFFFFu));
      const uint32_t km = __reduce_max_sync(0xffffffffu, max(__float_as_uint(k0) & 0x7FFFFFFFu, __float_as_uint(k1) & 0x7FFFFFFFu));
      asm volatile(
          "{\n.reg .pred p;\nsetp.ne.b32 p, %3, 0;\n"
          "@p red.shared.max.u32 [%0], %1;\n@p red.shared.max.u32 [%0+4], %2;\n}" ::"r"(c.s_red_addr + HH * 8),
          "r"(qm), "r"(km), "r"((c.lane == 0 && live) ? 1 : 0)
          : "memory");
    } else {
      uint32_t* vh = c.vp + HH * (KV_HEAD_BYTES / 4);
      if (live) {
        vh[0] = pack_bf16(v[0], v[1]);
        vh[96] = pack_bf16(v[2], v[3]);
        vh[32] = pack_bf16(v[4], v[5]);
        vh[128] = pack_bf16(v[6], v[7]);
        vh[64] = 0x3F803F80u;
        vh[160] = 0x3F803F80u;
      }
#pragma unroll
      for (int i = 0; i < 8; i++) asm("max.NaN.f32 %0, %0, %1;" : "+f"(vmax) : "f"(fabsf(v[i])));
    }
  } else {
    if (PART == 0) {
      const uint4 pq = make_uint4(phi2(pack_bf16(a[0], a[1])), phi2(pack_bf16(a[2], a[3])), phi2(pack_bf16(a[4], a[5])),
                                  phi2(pack_bf16(a[6], a[7])));
      if (live) c.qf[HH * 32 * 128] = pq;
      pk[0] = movm(phi2(pack_bf16(k[0], k[1])));
      pk[2] = movm(phi2(pack_bf16(k[2], k[3])));
      pk[1] = movm(phi2(pack_bf16(k[4], k[5])));
      pk[3] = movm(phi2(pack_bf16(k[6], k[7])));
    } else {
      const uint32_t b0 = movm(pack_bf16(v[0], v[1]));
      const uint32_t b1 = movm(pack_bf16(v[2], v[3]));
      const uint32_t b2 = movm(pack_bf16(v[4], v[5]));
      const uint32_t b3 = movm(pack_bf16(v[6], v[7]));
      float c0[4] = {0, 0, 0, 0}, c1[4] = {0, 0, 0, 0}, c2[4] = {0, 0, 0, 0};
      hmma(c0, pk[0], pk[1], pk[2], pk[3], b0, b1);
      hmma(c1, pk[0], pk[1], pk[2], pk[3], b2, b3);
      hmma(c2, pk[0], pk[1], pk[2], pk[3], 0x3F803F80u, 0x3F803F80u);
      float* slot = c.red + HH * 2 * 4096;
      if (live) {
#pragma unroll
        for (int i = 0; i < 4; i++) {
          slot[i * 32] = c0[i];
          slot[(4 + i) * 32] = c1[i];
          slot[(8 + i) * 32] = c2[i];
        }
      }
    }
  }
}

template <bool LINEAR>
__device__ __forceinline__ void qkv_consumer(uint32_t sbase, uint8_t* smem_gen, uint32_t* s_red, int cp, int rt) {
  const uint32_t bar_full = sbase + K1_BAR_OFF;
  const uint32_t bar_empty = bar_full + 8 * K1_STAGES;
  const int warp = threadIdx.x >> 5;
  const int wg = warp >> 2;
  const int lane = threadIdx.x & 31;
  float accN[96], accP[96];
  EpiCtx c;
  {
    const int row0 = rt * 128 + wg * 64 + (warp & 3) * 16;
    c.qf = g_qfrag + ((size_t)((LINEAR ? NH : 0) + cp * 8) * 32 + (rt * 2 + wg)) * 128 + (threadIdx.x & 127);
    uint32_t* img = reinterpret_cast<uint32_t*>(reinterpret_cast<uint8_t*>(g_kv) + (size_t)(cp * 8) * KV_HEAD_BYTES);
    c.kp = img + (row0 >> 3) * 64 + lane;
    c.vp = img + KV_K_BYTES / 4 + (row0 >> 3) * 96 + lane;
    c.s_red_addr = smem_u32(s_red);
    c.red = reinterpret_cast<float*>(smem_gen + wg * 8192) + (warp & 3) * 384 + lane;
    c.lane = lane;
  }
  uint32_t pk[4] = {0, 0, 0, 0};
  float vmax = 0.f;
#pragma unroll
  for (int i = 0; i < 96; i++) asm volatile("mov.f32 %0, 0f00000000;" : "=f"(accN[i]));
  int npass;
  asm volatile("mov.u32 %0, 2;" : "=r"(npass));
#pragma unroll 1
  for (int pass = K1_WARM ? 0 : 1; pass < npass; pass++) {
    const bool live = K1_WARM ? pass != 0 : true;
    if (live) {
#pragma unroll 1
      for (int kb = 0; kb < 8; kb++) {
        const int s = kb % K1_STAGES;
        mbar_wait(bar_full + 8 * s, (kb / K1_STAGES) & 1);
        if (threadIdx.x == 0) PROF_T(0, 2 + (kb >> 1));
        const uint64_t dA = mkdesc(sbase + kb * 16384 + wg * 8192, 16, 1024, 1);
        const uint64_t dB = mkdesc(sbase + K1_X_BYTES + s * K1_W_BYTES, 8192, 1024, 1);
        wg_fence();
#pragma unroll
        for (int k = 0; k < 4; k++) wgmma_ss_n192_tb(accP, dA + k * 2, dB + k * 128, (kb | k) != 0);
        wg_commit();
        if (kb > 0) {
          wg_wait<1>();
          if ((threadIdx.x & 127) == 0) {
            const int sp = (kb - 1) % K1_STAGES;
            mbar_arrive_cluster(bar_empty + 8 * sp, 0);
            mbar_arrive_cluster(bar_empty + 8 * sp, 1);
          }
        }
      }
      wg_wait<0>();
      fence_regs(accP);
      if ((threadIdx.x & 127) == 0) {
        mbar_arrive_cluster(bar_empty + 8 * (7 % K1_STAGES), 0);
        mbar_arrive_cluster(bar_empty + 8 * (7 % K1_STAGES), 1);
      }
      if (threadIdx.x == 0) PROF_T(0, 6);
#define K1_T1_STEP(KB)                                                                           \
  {                                                                                              \
    constexpr int g = 8 + KB;                                                                    \
    constexpr int s = g % K1_STAGES;                                                             \
    mbar_wait(bar_full + 8 * s, (g / K1_STAGES) & 1);                                            \
    const uint64_t dA = mkdesc(sbase + KB * 16384 + wg * 8192, 16, 1024, 1);                     \
    const uint64_t dB = mkdesc(sbase + K1_X_BYTES + s * K1_W_BYTES, 8192, 1024, 1);              \
    wg_fence();                                                                                  \
    _Pragma("unroll") for (int k = 0; k < 4; k++) wgmma_ss_n192_tb(accN, dA + k * 2, dB + k * 128, (KB | k) != 0); \
    wg_commit();                                                                                 \
    epi_slice<LINEAR, KB / 2, KB & 1>(accP, c, pk, vmax, true);                                  \
    wg_wait<0>();                                                                                \
    if (KB + K1_STAGES < 8 && (threadIdx.x & 127) == 0) {                                        \
      mbar_arrive_cluster(bar_empty + 8 * s, 0);                                                 \
      mbar_arrive_cluster(bar_empty + 8 * s, 1);                                                 \
    }                                                                                            \
  }
      K1_T1_STEP(0) K1_T1_STEP(1) K1_T1_STEP(2) K1_T1_STEP(3) K1_T1_STEP(4) K1_T1_STEP(5) K1_T1_STEP(6) K1_T1_STEP(7)
#undef K1_T1_STEP
      fence_regs(accN);
      if (threadIdx.x == 0) PROF_T(0, 10);
      c.qf += 4 * 32 * 128;
      c.kp += 4 * (KV_HEAD_BYTES / 4);
      c.vp += 4 * (KV_HEAD_BYTES / 4);
      c.s_red_addr += 32;
      c.red += 4096;
    }
    float vm1 = 0.f;
    epi_slice<LINEAR, 0, 0>(accN, c, pk, vm1, live);
    epi_slice<LINEAR, 0, 1>(accN, c, pk, vm1, live);
    epi_slice<LINEAR, 1, 0>(accN, c, pk, vm1, live);
    epi_slice<LINEAR, 1, 1>(accN, c, pk, vm1, live);
    epi_slice<LINEAR, 2, 0>(accN, c, pk, vm1, live);
    epi_slice<LINEAR, 2, 1>(accN, c, pk, vm1, live);
    epi_slice<LINEAR, 3, 0>(accN, c, pk, vm1, live);
    epi_slice<LINEAR, 3, 1>(accN, c, pk, vm1, live);
    if (live) asm("max.NaN.f32 %0, %0, %1;" : "+f"(vmax) : "f"(vm1));
  }
  if (!LINEAR) {
    const uint32_t vm = __reduce_max_sync(0xffffffffu, __float_as_uint(vmax) & 0x7FFFFFFFu);
    if (lane == 0) atomicMax(&s_red[16], vm);
    asm volatile("bar.sync 1, 256;" ::: "memory");
    if (threadIdx.x < 8) {
      *reinterpret_cast<float4*>(&g_nrm[((cp * 8 + threadIdx.x) * 16 + rt) * 4]) =
          make_float4(__uint_as_float(s_red[threadIdx.x * 2]), __uint_as_float(s_red[threadIdx.x * 2 + 1]), __uint_as_float(s_red[16]), 0.f);
    }
  } else {
    asm volatile("bar.sync 1, 256;" ::: "memory");
    float* dst = g_kvpart + ((size_t)rt * NH + cp * 8) * 384 + threadIdx.x;
    const float* base = reinterpret_cast<const float*>(smem_gen);
#pragma unroll
    for (int i = 0; i < 12; i++) {
      const int h0 = (i / 3) * 2, r = i % 3;
      const bool second = r == 2 || (r == 1 && threadIdx.x >= 128);
      const int e = (int)threadIdx.x + r * 256 - (second ? 384 : 0);
      const float* src = base + (second ? K1_SLOT_KB(h0 + 1) : K1_SLOT_KB(h0)) * 4096 + e;
      float sum = 0.f;
#pragma unroll
      for (int w = 0; w < 8; w++) sum += src[(w >> 2) * 2048 + (w & 3) * 384];
      dst[i * 256] = sum;
    }
  }
}

__global__ void __launch_bounds__(384, 1)
qkv_gemm_kernel(const __grid_constant__ CUtensorMap mxA, const __grid_constant__ CUtensorMap mxB,
                const __grid_constant__ CUtensorMap mwA, const __grid_constant__ CUtensorMap mwB) {
  extern __shared__ uint8_t smem_raw[];
  const uint32_t sbase = (smem_u32(smem_raw) + 1023) & ~1023u;
  uint8_t* smem_gen = smem_raw + (sbase - smem_u32(smem_raw));
  const uint32_t bar_full = sbase + K1_BAR_OFF;
  const uint32_t bar_empty = bar_full + 8 * K1_STAGES;
  uint32_t* s_red = reinterpret_cast<uint32_t*>(smem_gen + K1_BAR_OFF + 64);

  const int rank = blockIdx.x & 1;
  const int pair = blockIdx.x >> 1;
  const int branch = pair >> 5;
  const int rp = (pair & 31) >> 2;
  const int cp = pair & 3;
  const int rt = rp * 2 + rank;
  const int warp = threadIdx.x >> 5;
  if (threadIdx.x == 0) { PROF_G(0, 30); PROF_T(0, 0); }
  const CUtensorMap* mx = branch ? &mxA : &mxB;
  const CUtensorMap* mw = branch ? &mwA : &mwB;

  if (threadIdx.x == 256) {
    asm volatile("prefetch.tensormap [%0];" ::"l"(mx) : "memory");
    asm volatile("prefetch.tensormap [%0];" ::"l"(mw) : "memory");
    for (int i = 0; i < K1_STAGES; i++) {
      mbar_init(bar_full + 8 * i, 1);
      mbar_init(bar_empty + 8 * i, 4);
    }
    fence_barrier_init();
    fence_proxy_async();
    for (int kb = 0; kb < K1_STAGES; kb++) mbar_expect_tx(bar_full + 8 * kb, 16384 + K1_W_BYTES);
    tma_load_2d(sbase, mx, 0, rt * 128, bar_full);
  }
  pdl_launch_dependents();
  if (threadIdx.x < 32) s_red[threadIdx.x] = 0;
  __syncthreads();
  cluster_sync_relaxed();
  if (threadIdx.x == 0) PROF_T(0, 1);

  if (warp >= 8) {
    asm volatile("setmaxnreg.dec.sync.aligned.u32 40;");
    if (threadIdx.x == 256) {
      for (int g = 0; g < 16; g++) {
        const int s = g % K1_STAGES;
        const int kb = g & 7;
        if (g >= K1_STAGES) {
          mbar_wait(bar_empty + 8 * s, ((g / K1_STAGES) - 1) & 1);
          mbar_expect_tx(bar_full + 8 * s, (g < 8 ? 16384 : 0) + K1_W_BYTES);
        }
        if (g > 0 && g < 8) tma_load_2d(sbase + kb * 16384, mx, kb * 64, rt * 128, bar_full + 8 * s);
        const int h0 = cp * 8 + (g >> 3) * 4;
        const uint32_t st = sbase + K1_X_BYTES + s * K1_W_BYTES + rank * 4096;
#pragma unroll
        for (int p = 0; p < 3; p++)
          tma_load_2d_mc(st + p * 8192, mw, p * 512 + h0 * 16, kb * 64 + rank * 32, bar_full + 8 * s, (uint16_t)3);
      }
    }
    __syncwarp();
    cluster_sync_relaxed();
  } else {
    asm volatile("setmaxnreg.inc.sync.aligned.u32 232;");
    if (branch == 0) qkv_consumer<false>(sbase, smem_gen, s_red, cp, rt);
    else qkv_consumer<true>(sbase, smem_gen, s_red, cp, rt);
    if (threadIdx.x == 0) PROF_T(0, 11);
    __syncwarp();
    cluster_sync_relaxed();
    if (threadIdx.x == 0) { PROF_T(0, 12); PROF_G(0, 31); }
  }
}

constexpr int K2_SMEM = KV_HEAD_BYTES + 1024 + 256;

#define ATT_NPOLY 19
#define ATT_CH 8
#define ATT_D 1
#define PRO_MODE 1
#define STAGGER 0
#define K2_WARM 0
#define K2_FIRST 2
#define CONST_SMID 0
#define ATT_STRUCT 1
#define ATT_PIN 0
#define ATT_GM 1
#define ATT_DEG 2
struct ExpC {
  uint32_t k3c00, kmask, seven, c3;
};
__device__ __forceinline__ uint32_t hfma2(uint32_t a, uint32_t b, uint32_t c) {
  uint32_t r;
  asm("fma.rn.f16x2 %0, %1, %2, %3;" : "=r"(r) : "r"(a), "r"(b), "r"(c));
  return r;
}
__device__ __forceinline__ uint32_t exp2_poly_pair(float t0, float t1, const ExpC& c) {
  uint32_t u;
  asm("prmt.b32 %0, %1, %2, 0x5410;" : "=r"(u) : "r"(__float_as_uint(t0)), "r"(__float_as_uint(t1)));
  uint32_t m;
  asm("lop3.b32 %0, %1, 0x03FF03FF, %2, 0xEA;" : "=r"(m) : "r"(u), "r"(c.k3c00));
  uint32_t p = hfma2(m, c.c3, 0xa385a385u);
  p = hfma2(p, m, 0x4ad64ad7u);
  uint32_t mu;
  asm("lop3.b32 %0, %1, 0xFC00FC00, %2, 0xEA;" : "=r"(mu) : "r"(u), "r"(c.kmask));
  uint32_t r;
  asm("{.reg .b32 t; shf.r.wrap.b32 t, %1, %2, 3; add.u32 %0, t, %3;}" : "=r"(r) : "r"(mu), "r"(c.seven), "r"(p));
  return r;
}
__device__ __forceinline__ float gadd(float x, float M, uint32_t g) {
  float r = x;
  asm("{.reg .pred p; setp.ne.b32 p, %2, -1; @p add.f32 %0, %0, %1;}" : "+f"(r) : "f"(M), "r"(g));
  return r;
}
__device__ __forceinline__ float gex2(float x, uint32_t g) {
  float r = x;
  asm("{.reg .pred p; setp.ne.b32 p, %1, -1; @p ex2.approx.ftz.f32 %0, %0;}" : "+f"(r) : "r"(g));
  return r;
}
template <int NPOLY, int NPAIR, int CH, int D, bool G0 = false>
__device__ __forceinline__ void exp_tile(const float (&s)[2 * NPAIR], uint32_t (&p)[NPAIR], const ExpC& c, uint32_t g0 = 0) {
#pragma unroll
  for (int i = 0; i < NPAIR; i++) {
    const bool isPoly = ((i + 1) * NPOLY / 32) != (i * NPOLY / 32);
    const int ch = i / CH;
    const bool gated = ch >= D || G0;
    int gi = (ch - D) * CH + CH - 1;
    if (ch >= D) {
      while (gi > (ch - D) * CH && !(((gi + 1) * NPOLY / 32) != (gi * NPOLY / 32))) gi--;
    }
    const uint32_t g = ch >= D ? p[gi] : g0;
    if (!isPoly) {
      if (gated && ATT_GM) p[i] = pack_bf16(gex2(s[2 * i], g), gex2(s[2 * i + 1], g));
      else p[i] = pack_bf16(ex2f(s[2 * i]), ex2f(s[2 * i + 1]));
    } else {
      if (gated) p[i] = exp2_poly_pair(gadd(s[2 * i], 12329.f, g), gadd(s[2 * i + 1], 12329.f, g), c);
      else p[i] = exp2_poly_pair(s[2 * i] + 12329.f, s[2 * i + 1] + 12329.f, c);
    }
  }
}

__device__ __forceinline__ void store_o(__nv_bfloat16* o, int row0, int head, int lane, const uint32_t (&r)[4]) {
  const int g = lane >> 2, t = lane & 3;
  uint32_t* p0 = reinterpret_cast<uint32_t*>(o + (size_t)(row0 + g) * DM + head * 16) + t;
  uint32_t* p1 = reinterpret_cast<uint32_t*>(o + (size_t)(row0 + g + 8) * DM + head * 16) + t;
  p0[0] = r[0];
  p1[0] = r[1];
  p0[4] = r[2];
  p1[4] = r[3];
}

__device__ __forceinline__ void kv_fetch_piece(uint32_t sbase, uint32_t bar, int piece) {
  const uint8_t* img = reinterpret_cast<const uint8_t*>(g_kv) + (size_t)(blockIdx.x >> 2) * KV_HEAD_BYTES;
  const int g = piece >> 1, isv = piece & 1;
  const int e0 = g == 0 ? 0 : (isv ? 256 : 320) + (g - 1) * 512;
  const int e1 = g == 3 ? 2048 : (isv ? 256 : 320) + g * 512;
  const int bytes = (e1 - e0) * (isv ? 48 : 32);
  const int off = isv ? KV_K_BYTES + e0 * 48 : e0 * 32;
  mbar_expect_tx(bar + 8 * g, bytes);
  bulk_load(sbase + off, img + off, bytes, bar + 8 * g);
}

__device__ __forceinline__ void safe_exp(const float (&s)[32], uint32_t (&p)[16], float (&o)[12], float& m0, float& m1) {
  float x0 = s[0], x1 = s[2];
#pragma unroll
  for (int i = 0; i < 8; i++) {
    x0 = fmaxf(x0, fmaxf(s[4 * i], s[4 * i + 1]));
    x1 = fmaxf(x1, fmaxf(s[4 * i + 2], s[4 * i + 3]));
  }
  x0 = fmaxf(x0, __shfl_xor_sync(0xffffffffu, x0, 1));
  x1 = fmaxf(x1, __shfl_xor_sync(0xffffffffu, x1, 1));
  x0 = fmaxf(x0, __shfl_xor_sync(0xffffffffu, x0, 2));
  x1 = fmaxf(x1, __shfl_xor_sync(0xffffffffu, x1, 2));
  const float n0 = fmaxf(m0, x0), n1 = fmaxf(m1, x1);
  const float c0 = ex2f(m0 - n0), c1 = ex2f(m1 - n1);
  m0 = n0;
  m1 = n1;
#pragma unroll
  for (int i = 0; i < 3; i++) {
    o[4 * i] *= c0;
    o[4 * i + 1] *= c0;
    o[4 * i + 2] *= c1;
    o[4 * i + 3] *= c1;
  }
#pragma unroll
  for (int i = 0; i < 8; i++) {
    p[2 * i] = pack_bf16(ex2f(s[4 * i] - n0), ex2f(s[4 * i + 1] - n0));
    p[2 * i + 1] = pack_bf16(ex2f(s[4 * i + 2] - n1), ex2f(s[4 * i + 3] - n1));
  }
}

__device__ __forceinline__ void attn_step(float (&sx)[32], float (&sy)[32], float (&o)[12], const uint4& qf, uint64_t dK, uint64_t dV,
                                          const ExpC& ec) {
  uint32_t pa[16], pb[16];
  wg_fence();
  wgmma_rs_n64_z(sy, qf.x, qf.y, qf.z, qf.w, dK + 128);
  wg_commit();
  exp_tile<ATT_NPOLY, 16, ATT_CH, ATT_D>(sx, pa, ec);
  wg_fence();
  wgmma_rs_n24_tb(o, pa[12], pa[13], pa[14], pa[15], dV + 3 * 48, 1);
  wg_commit();
  wg_wait<1>();
  fence_regs(sy);
  exp_tile<ATT_NPOLY, 16, ATT_CH, ATT_D>(sy, pb, ec);
  wg_fence();
#pragma unroll
  for (int k = 0; k < 3; k++) wgmma_rs_n24_tb(o, pa[4 * k], pa[4 * k + 1], pa[4 * k + 2], pa[4 * k + 3], dV + k * 48, 1);
#pragma unroll
  for (int k = 0; k < 4; k++) wgmma_rs_n24_tb(o, pb[4 * k], pb[4 * k + 1], pb[4 * k + 2], pb[4 * k + 3], dV + (4 + k) * 48, 1);
  wgmma_rs_n64_z(sy, qf.x, qf.y, qf.z, qf.w, dK + 256);
  wg_commit();
  wg_wait<0>();
  fence_regs(sy);
}

template <bool SAFE>
__device__ __forceinline__ void attn_tile(uint64_t dK, uint64_t dV, uint32_t bar, const uint4 qf, const ExpC& ec, uint32_t (&outp)[4],
                                          bool warm) {
  float o[12];
#pragma unroll
  for (int i = 0; i < 12; i++) asm volatile("mov.f32 %0, 0f00000000;" : "=f"(o[i]));
  if (!warm) mbar_wait(bar, 0);
  if (!SAFE) {
    float s0[32], s1[32];
    wg_fence();
    wgmma_rs_n64_z(s0, qf.x, qf.y, qf.z, qf.w, dK);
    wg_commit();
    wg_wait<0>();
    fence_regs(s0);
#pragma unroll 1
    for (int p = warm ? 7 : 0; p < 8; p++) {
      if ((p & 1) && !warm) mbar_wait(bar + 8 * min((p + 1) >> 1, 3), 0);
      attn_step(s0, s1, o, qf, dK, dV, ec);
      attn_step(s1, s0, o, qf, dK + 256, dV + 384, ec);
      dK += 512;
      dV += 768;
    }
  } else {
    float m0 = -INFINITY, m1 = -INFINITY;
#pragma unroll 1
    for (int j = 0; j < 32; j++) {
      if (j == 4) { mbar_wait(bar + 8, 0); mbar_wait(bar + 16, 0); mbar_wait(bar + 24, 0); }
      float s[32];
      uint32_t p[16];
      wg_fence();
      wgmma_rs_n64_z(s, qf.x, qf.y, qf.z, qf.w, dK);
      wg_commit();
      wg_wait<0>();
      fence_regs(s);
      safe_exp(s, p, o, m0, m1);
      wg_fence();
#pragma unroll
      for (int k = 0; k < 4; k++) wgmma_rs_n24_tb(o, p[4 * k], p[4 * k + 1], p[4 * k + 2], p[4 * k + 3], dV + k * 48, 1);
      wg_commit();
      wg_wait<0>();
      fence_regs(o);
      dK += 128;
      dV += 192;
    }
  }
  fence_regs(o);
  const float r0 = 1.0f / o[8], r1 = 1.0f / o[10];
  outp[0] = pack_bf16(o[0] * r0, o[1] * r0);
  outp[1] = pack_bf16(o[2] * r1, o[3] * r1);
  outp[2] = pack_bf16(o[4] * r0, o[5] * r0);
  outp[3] = pack_bf16(o[6] * r1, o[7] * r1);
}

__device__ __forceinline__ void linear_attn_cta(uint8_t* smem_raw, uint32_t sbase, const CUtensorMap* mo16, int cta) {
  const int warp = threadIdx.x >> 5, lane = threadIdx.x & 31;
  const int hg = warp & 1;
  const uint4* qp = g_qfrag + (size_t)(NH + cta * 8 + hg * 4) * 32 * 128 + lane;
  auto qaddr = [&](int i) {
    const int blk16 = i * 8 + (warp >> 1);
    return qp + (blk16 >> 2) * 128 + (blk16 & 3) * 32;
  };
  uint4 q[4];
#pragma unroll
  for (int h = 0; h < 4; h++) q[h] = qaddr(0)[h * 32 * 128];
  float* red = reinterpret_cast<float*>(smem_raw + (sbase - smem_u32(smem_raw)) + 131072);
  {
    const float* src = g_kvpart + (size_t)cta * 8 * 384;
    float sum[6];
#pragma unroll
    for (int i = 0; i < 6; i++) sum[i] = 0.f;
#pragma unroll
    for (int r = 0; r < 16; r++) {
#pragma unroll
      for (int i = 0; i < 6; i++) sum[i] += src[(size_t)r * NH * 384 + threadIdx.x + i * 512];
    }
#pragma unroll
    for (int i = 0; i < 6; i++) red[threadIdx.x + i * 512] = round_bf16(sum[i]);
  }
  __syncthreads();
  if (threadIdx.x == 0) PROF_T(1, 1);
  uint32_t bf[4][6];
  {
    const int g = lane >> 2, t = lane & 3;
#pragma unroll
    for (int h = 0; h < 4; h++) {
#pragma unroll
      for (int f = 0; f < 6; f++) {
        const int blk = f >> 1, half = f & 1;
        const int e = (blk == 2) ? 0 : g;
        const int d = 2 * t + 8 * half;
        const int base = (hg * 4 + h) * 384 + (blk * 4 + half * 2 + (e & 1)) * 32 + (e >> 1);
        bf[h][f] = pack_bf16(red[base + (d & 7) * 4], red[base + ((d + 1) & 7) * 4]);
      }
    }
  }
  if (threadIdx.x == 0) PROF_T(1, 2);
  const uint32_t stg = sbase + warp * 8192;
#pragma unroll 1
  for (int i = 0; i < 16; i++) {
    uint4 qc[4];
#pragma unroll
    for (int h = 0; h < 4; h++) qc[h] = q[h];
    if (i + 1 < 16) {
#pragma unroll
      for (int h = 0; h < 4; h++) q[h] = qaddr(i + 1)[h * 32 * 128];
    }
    const uint32_t buf = stg + (i & 3) * 2048;
    if (i >= 4) {
      if (lane == 0) asm volatile("cp.async.bulk.wait_group.read 3;" ::: "memory");
      __syncwarp();
    }
#pragma unroll
    for (int h = 0; h < 4; h++) {
      float n0[4] = {0, 0, 0, 0}, n1[4] = {0, 0, 0, 0}, dn[4] = {0, 0, 0, 0};
      hmma(n0, qc[h].x, qc[h].y, qc[h].z, qc[h].w, bf[h][0], bf[h][1]);
      hmma(n1, qc[h].x, qc[h].y, qc[h].z, qc[h].w, bf[h][2], bf[h][3]);
      hmma(dn, qc[h].x, qc[h].y, qc[h].z, qc[h].w, bf[h][4], bf[h][5]);
      const float d0 = __fdividef(1.0f, dn[0] + 1e-6f), d1 = __fdividef(1.0f, dn[2] + 1e-6f);
      const uint32_t r0 = pack_bf16(n0[0] * d0, n0[1] * d0);
      const uint32_t r1 = pack_bf16(n0[2] * d1, n0[3] * d1);
      const uint32_t r2 = pack_bf16(n1[0] * d0, n1[1] * d0);
      const uint32_t r3 = pack_bf16(n1[2] * d1, n1[3] * d1);
      const int row = lane & 15;
      const int chunk = h * 2 + (lane >> 4);
      const uint32_t addr = buf + row * 128 + ((chunk ^ (row & 7)) << 4);
      asm volatile("stmatrix.sync.aligned.m8n8.x4.shared.b16 [%0], {%1,%2,%3,%4};" ::"r"(addr), "r"(r0), "r"(r1), "r"(r2), "r"(r3)
                   : "memory");
    }
    fence_proxy_async();
    __syncwarp();
    if (lane == 0) {
      tma_store_2d(mo16, buf, cta * 128 + hg * 64, (i * 8 + (warp >> 1)) * 16);
      asm volatile("cp.async.bulk.commit_group;" ::: "memory");
    }
  }
  if (threadIdx.x == 0) PROF_T(1, 3);
  if (lane == 0) asm volatile("cp.async.bulk.wait_group 0;" ::: "memory");
}

__global__ void __launch_bounds__(512, 1)
attn_kernel(const __grid_constant__ CUtensorMap mo16, const uint8_t* __restrict__ woA, const uint8_t* __restrict__ woB) {
  extern __shared__ uint8_t smem_raw[];
  const uint32_t sbase = (smem_u32(smem_raw) + 1023) & ~1023u;
  const uint32_t bar = sbase + KV_HEAD_BYTES;
  if (threadIdx.x == 0) { PROF_G(1, 30); PROF_T(1, 0); }
  if (threadIdx.x == 0) {
    for (int i = 0; i < 4; i++) mbar_init(bar + 8 * i, 2);
    asm volatile("st.shared.v4.u32 [%0], {%1, %2, %3, %4};" ::"r"(bar + 64), "r"(0x3C003C00u), "r"(0x00070000u), "r"(7u),
                 "r"(ATT_DEG == 3 ? 0x2cfd2cfdu : 0x35623562u)
                 : "memory");
    fence_barrier_init();
    fence_proxy_async();
  }
  __syncthreads();
  pdl_launch_dependents();
  if (blockIdx.x >= 128 && threadIdx.x < 16) {
    const int i = (blockIdx.x - 128) * 16 + threadIdx.x;
    const uint8_t* p = (i < 32 ? woA : woB) + (size_t)(i & 31) * 16384;
    asm volatile("cp.async.bulk.prefetch.L2.global [%0], %1;" ::"l"(p), "r"(16384) : "memory");
  }
  if (blockIdx.x >= 128) {
    pdl_wait();
    linear_attn_cta(smem_raw, sbase, &mo16, blockIdx.x - 128);
    if (threadIdx.x == 0) { PROF_T(1, 5); PROF_G(1, 31); }
    return;
  }
  const int head = blockIdx.x >> 2, qb = blockIdx.x & 3;
  const int lane = threadIdx.x & 31;
  const int wg = __shfl_sync(0xffffffffu, threadIdx.x >> 7, 0), warp = __shfl_sync(0xffffffffu, (threadIdx.x >> 5) & 3, 0);
  ExpC ec;
  asm volatile("ld.volatile.shared.v4.u32 {%0, %1, %2, %3}, [%4];" : "=r"(ec.k3c00), "=r"(ec.kmask), "=r"(ec.seven), "=r"(ec.c3) : "r"(bar + 64));
  const uint64_t dK = mkdesc(sbase, 128, 256, 0);
  const uint64_t dV = mkdesc(sbase + KV_K_BYTES, 384, 128, 0);
  uint4 qnext = make_uint4(0, 0, 0, 0);
  bool safe_path = false;
#pragma unroll 1
  for (int t = (K2_WARM && blockIdx.x < 4) ? -1 : 0; t < 2; t++) {
    if (t == 0) {
      pdl_wait();
      if (threadIdx.x == 0) { PROF_T(1, 7); PROF_G(1, 29); }
      if (threadIdx.x == 0) {
#pragma unroll
        for (int piece = 0; piece < K2_FIRST; piece++) kv_fetch_piece(sbase, bar, piece);
      }
      qnext = g_qfrag[(head * 32 + qb * 8 + wg * 2) * 128 + (threadIdx.x & 127)];
      float4 n = make_float4(0.f, 0.f, 0.f, 0.f);
      if (lane < 16) n = *reinterpret_cast<const float4*>(&g_nrm[(head * 16 + lane) * 4]);
      uint32_t qm = ((lane >> 2) == qb) ? __float_as_uint(n.x) : 0u;
      qm = __reduce_max_sync(0xffffffffu, qm);
      const uint32_t km = __reduce_max_sync(0xffffffffu, __float_as_uint(n.y));
      const uint32_t vm = __reduce_max_sync(0xffffffffu, __float_as_uint(n.z));
      const float b2 = __uint_as_float(qm) * (QSCALE * QSCALE) * __uint_as_float(km) * 1.02f;
      const float vmax = __uint_as_float(vm);
      const bool ok = (b2 <= 21.5f * 21.5f) && (vmax <= 1.0e24f) && (vmax >= 1.0e-18f || vmax == 0.f);
      safe_path = !ok;
      if (K2_FIRST < 8) {
        mbar_wait(bar, 0);
        if (threadIdx.x == 0) {
#pragma unroll
          for (int piece = K2_FIRST; piece < 8; piece++) kv_fetch_piece(sbase, bar, piece);
        }
      }
    }
    const int tile64 = qb * 8 + wg * 2 + t;
    const uint4 qf = qnext;
    if (t == 0) qnext = g_qfrag[(head * 32 + tile64 + 1) * 128 + (threadIdx.x & 127)];
    uint32_t r[4];
    if (threadIdx.x == 0 && t >= 0) PROF_T(1, 1 + t);
    if (!safe_path) attn_tile<false>(dK, dV, bar, qf, ec, r, t < 0);
    else attn_tile<true>(dK, dV, bar, qf, ec, r, false);
    if (t >= 0) store_o(g_o + (size_t)S_LEN * DM, tile64 * 64 + warp * 16, head, lane, r);
  }
  if (threadIdx.x == 0) { PROF_T(1, 5); PROF_G(1, 31); }
}

#define K3_WPRE 2
constexpr int K3_STAGES = 5;
constexpr int K3_W_BYTES = 8 * 16384;
constexpr int K3_BAR_OFF = K3_W_BYTES + K3_STAGES * 16384;
constexpr int K3_SMEM = K3_BAR_OFF + 256 + 1024;

__global__ void __launch_bounds__(288, 1)
out_gemm_kernel(const __grid_constant__ CUtensorMap mo, const __grid_constant__ CUtensorMap mwA,
                const __grid_constant__ CUtensorMap mwB, const __grid_constant__ CUtensorMap mout) {
  extern __shared__ uint8_t smem_raw[];
  const uint32_t sbase = (smem_u32(smem_raw) + 1023) & ~1023u;
  const uint32_t bar_full = sbase + K3_BAR_OFF;
  const uint32_t bar_empty = bar_full + 8 * K3_STAGES;
  const uint32_t bar_w = bar_empty + 8 * K3_STAGES;
  const int branch = blockIdx.x >> 6;
  const int rt = (blockIdx.x & 63) >> 2;
  const int ct = blockIdx.x & 3;
  const int warp = threadIdx.x >> 5;
  if (threadIdx.x == 0) { PROF_G(2, 30); PROF_T(2, 0); }
  if (threadIdx.x == 256) {
    const CUtensorMap* mw = branch ? &mwB : &mwA;
    asm volatile("prefetch.tensormap [%0];" ::"l"(mw) : "memory");
    asm volatile("prefetch.tensormap [%0];" ::"l"(&mo) : "memory");
    asm volatile("prefetch.tensormap [%0];" ::"l"(&mout) : "memory");
    for (int i = 0; i < K3_STAGES; i++) {
      mbar_init(bar_full + 8 * i, 1);
      mbar_init(bar_empty + 8 * i, 2);
    }
    for (int i = 0; i < 8; i++) mbar_init(bar_w + 8 * i, 1);
    fence_barrier_init();
    fence_proxy_async();
    for (int kb = 0; kb < K3_WPRE; kb++) {
      mbar_expect_tx(bar_w + 8 * kb, 16384);
      tma_load_2d(sbase + kb * 16384, mw, ct * 128, kb * 64, bar_w + 8 * kb);
      tma_load_2d(sbase + kb * 16384 + 8192, mw, ct * 128 + 64, kb * 64, bar_w + 8 * kb);
    }
  }
  __syncthreads();
  if (warp == 8) {
    if ((threadIdx.x & 31) == 0) {
      const CUtensorMap* mw = branch ? &mwB : &mwA;
      pdl_wait();
      PROF_T(2, 1);
      for (int kb = 0; kb < 8; kb++) {
        const int s = kb % K3_STAGES;
        if (kb >= K3_STAGES) mbar_wait(bar_empty + 8 * s, ((kb / K3_STAGES) - 1) & 1);
        mbar_expect_tx(bar_full + 8 * s, 16384);
        tma_load_2d(sbase + K3_W_BYTES + s * 16384, &mo, kb * 64, branch * S_LEN + rt * 128, bar_full + 8 * s);
        const int kw = kb + K3_WPRE;
        if (kw < 8) {
          mbar_expect_tx(bar_w + 8 * kw, 16384);
          tma_load_2d(sbase + kw * 16384, mw, ct * 128, kw * 64, bar_w + 8 * kw);
          tma_load_2d(sbase + kw * 16384 + 8192, mw, ct * 128 + 64, kw * 64, bar_w + 8 * kw);
        }
      }
    }
  } else {
    const int wg = warp >> 2;
    float acc[64];
    for (int kb = 0; kb < 8; kb++) {
      const int s = kb % K3_STAGES;
      mbar_wait(bar_w + 8 * kb, 0);
      mbar_wait(bar_full + 8 * s, (kb / K3_STAGES) & 1);
      if (threadIdx.x == 0) PROF_T(2, 2 + kb);
      const uint64_t dA = mkdesc(sbase + K3_W_BYTES + s * 16384 + wg * 8192, 16, 1024, 1);
      const uint64_t dB = mkdesc(sbase + kb * 16384, 8192, 1024, 1);
      wg_fence();
#pragma unroll
      for (int k = 0; k < 4; k++) wgmma_ss_n128_tb(acc, dA + k * 2, dB + k * 128, (kb | k) != 0);
      wg_commit();
      if (kb > 0) {
        wg_wait<1>();
        if ((threadIdx.x & 127) == 0) mbar_arrive(bar_empty + 8 * ((kb - 1) % K3_STAGES));
      }
    }
    wg_wait<0>();
    fence_regs(acc);
    if (threadIdx.x == 0) PROF_T(2, 10);
    const uint32_t stg = sbase + K3_W_BYTES + wg * 8192;
    const int lane = threadIdx.x & 31;
    const int rloc = (warp & 3) * 16 + (lane & 15);
#pragma unroll
    for (int c16 = 0; c16 < 8; c16++) {
      const float* a = &acc[c16 * 8];
      const uint32_t r0 = pack_bf16(a[0], a[1]), r1 = pack_bf16(a[2], a[3]), r2 = pack_bf16(a[4], a[5]), r3 = pack_bf16(a[6], a[7]);
      const int chunk = (c16 & 3) * 2 + (lane >> 4);
      const uint32_t addr = stg + (c16 >> 2) * 16384 + rloc * 128 + ((chunk ^ (rloc & 7)) << 4);
      asm volatile("stmatrix.sync.aligned.m8n8.x4.shared.b16 [%0], {%1,%2,%3,%4};" ::"r"(addr), "r"(r0), "r"(r1), "r"(r2), "r"(r3)
                   : "memory");
    }
    fence_proxy_async();
    asm volatile("bar.sync %0, 128;" ::"r"(2 + wg) : "memory");
    if ((threadIdx.x & 127) == 0) {
      tma_store_2d(&mout, stg, branch * DM + ct * 128, rt * 128 + wg * 64);
      tma_store_2d(&mout, stg + 16384, branch * DM + ct * 128 + 64, rt * 128 + wg * 64);
      asm volatile("cp.async.bulk.commit_group;" ::: "memory");
      asm volatile("cp.async.bulk.wait_group.read 0;" ::: "memory");
      if (threadIdx.x == 0) { PROF_T(2, 12); PROF_G(2, 31); }
    }
  }
}

typedef CUresult (*EncodeFn)(CUtensorMap*, CUtensorMapDataType, cuuint32_t, void*, const cuuint64_t*, const cuuint64_t*,
                             const cuuint32_t*, const cuuint32_t*, CUtensorMapInterleave, CUtensorMapSwizzle,
                             CUtensorMapL2promotion, CUtensorMapFloatOOBfill);

void make_map(EncodeFn enc, CUtensorMap* m, const void* ptr, uint64_t inner, uint64_t outer, uint32_t box_inner, uint32_t box_outer) {
  cuuint64_t dims[2] = {inner, outer};
  cuuint64_t strides[1] = {inner * 2};
  cuuint32_t box[2] = {box_inner, box_outer};
  cuuint32_t es[2] = {1, 1};
  enc(m, CU_TENSOR_MAP_DATA_TYPE_BFLOAT16, 2, const_cast<void*>(ptr), dims, strides, box, es, CU_TENSOR_MAP_INTERLEAVE_NONE,
      CU_TENSOR_MAP_SWIZZLE_128B, CU_TENSOR_MAP_L2_PROMOTION_L2_256B, CU_TENSOR_MAP_FLOAT_OOB_FILL_NONE);
}

struct HostState {
  bool init;
  const void* key[7];
  CUtensorMap mxA, mxB, mwA, mwB, mo, mo16, mwoA, mwoB, mout;
};
HostState g_hs;

}

extern "C" void kernel_launch(void* const* d_in, const int* in_sizes, int n_in, void* d_out, int out_size) {
  (void)in_sizes; (void)n_in; (void)out_size;
  HostState& hs = g_hs;
  bool same = hs.init && hs.key[6] == d_out;
  for (int i = 0; i < 6 && same; i++) same = hs.key[i] == d_in[i];
  if (!same) {
    void* fn = nullptr;
    cudaDriverEntryPointQueryResult qr;
    cudaGetDriverEntryPoint("cuTensorMapEncodeTiled", &fn, cudaEnableDefault, &qr);
    EncodeFn enc = (EncodeFn)fn;
    void* go = nullptr;
    cudaGetSymbolAddress(&go, g_o);
    make_map(enc, &hs.mxA, d_in[0], 512, 2048, 64, 128);
    make_map(enc, &hs.mwA, d_in[1], 1536, 512, 64, 32);
    make_map(enc, &hs.mwoA, d_in[2], 512, 512, 64, 64);
    make_map(enc, &hs.mxB, d_in[3], 512, 2048, 64, 128);
    make_map(enc, &hs.mwB, d_in[4], 1536, 512, 64, 32);
    make_map(enc, &hs.mwoB, d_in[5], 512, 512, 64, 64);
    make_map(enc, &hs.mo, go, 512, 4096, 64, 128);
    make_map(enc, &hs.mo16, go, 512, 4096, 64, 16);
    make_map(enc, &hs.mout, d_out, 1024, 2048, 64, 64);
    cudaFuncSetAttribute(qkv_gemm_kernel, cudaFuncAttributeMaxDynamicSharedMemorySize, K1_SMEM);
    cudaFuncSetAttribute(attn_kernel, cudaFuncAttributeMaxDynamicSharedMemorySize, K2_SMEM);
    cudaFuncSetAttribute(out_gemm_kernel, cudaFuncAttributeMaxDynamicSharedMemorySize, K3_SMEM);
    for (int i = 0; i < 6; i++) hs.key[i] = d_in[i];
    hs.key[6] = d_out;
    hs.init = true;
  }
  cudaStream_t st = cudaStreamPerThread;
  {
    cudaLaunchConfig_t cfg = {};
    cfg.gridDim = dim3(128);
    cfg.blockDim = dim3(384);
    cfg.dynamicSmemBytes = K1_SMEM;
    cfg.stream = st;
    cudaLaunchAttribute at[1];
    at[0].id = cudaLaunchAttributeClusterDimension;
    at[0].val.clusterDim.x = 2;
    at[0].val.clusterDim.y = 1;
    at[0].val.clusterDim.z = 1;
    cfg.attrs = at;
    cfg.numAttrs = 1;
    cudaLaunchKernelEx(&cfg, qkv_gemm_kernel, hs.mxA, hs.mxB, hs.mwA, hs.mwB);
  }
  {
    cudaLaunchConfig_t cfg = {};
    cfg.gridDim = dim3(132);
    cfg.blockDim = dim3(512);
    cfg.dynamicSmemBytes = K2_SMEM;
    cfg.stream = st;
    cudaLaunchAttribute at[1];
    at[0].id = cudaLaunchAttributeProgrammaticStreamSerialization;
    at[0].val.programmaticStreamSerializationAllowed = 1;
    cfg.attrs = at;
    cfg.numAttrs = 1;
    cudaLaunchKernelEx(&cfg, attn_kernel, hs.mo16, (const uint8_t*)d_in[2], (const uint8_t*)d_in[5]);
    cfg.gridDim = dim3(128);
    cfg.blockDim = dim3(288);
    cfg.dynamicSmemBytes = K3_SMEM;
    cudaLaunchKernelEx(&cfg, out_gemm_kernel, hs.mo, hs.mwoA, hs.mwoB, hs.mout);
  }
}
```

```cpp
#include <cuda_runtime.h>
#include <cuda_bf16.h>
#include <cuda.h>
#include <stdint.h>

namespace {

constexpr int S_LEN = 2048;
constexpr int DM = 512;
constexpr int NH = 32;

constexpr int KV_K_BYTES = 65536;
constexpr int KV_HEAD_BYTES = KV_K_BYTES + 98304;
__device__ uint4 g_qfrag[2 * NH * 32 * 128];
__device__ uint4 g_kv[NH * KV_HEAD_BYTES / 16];
__device__ float g_kvpart[16 * NH * 384];
__device__ float g_nrm[NH * 16 * 4];
__device__ __nv_bfloat16 g_o[2 * S_LEN * DM];

#define g_prof_set(k, i, v)
#define g_prof_dummy(i) true
#define PROF_T(k, i) do {} while (0)
#define PROF_G(k, i) do {} while (0)
__device__ __forceinline__ uint32_t smem_u32(const void* p) { return (uint32_t)__cvta_generic_to_shared(p); }
__device__ __forceinline__ void mbar_init(uint32_t bar, int cnt) {
  asm volatile("mbarrier.init.shared::cta.b64 [%0], %1;" ::"r"(bar), "r"(cnt) : "memory");
}
__device__ __forceinline__ void mbar_expect_tx(uint32_t bar, uint32_t bytes) {
  asm volatile("mbarrier.arrive.expect_tx.shared::cta.b64 _, [%0], %1;" ::"r"(bar), "r"(bytes) : "memory");
}
__device__ __forceinline__ void mbar_arrive(uint32_t bar) {
  asm volatile("mbarrier.arrive.shared::cta.b64 _, [%0];" ::"r"(bar) : "memory");
}
__device__ __forceinline__ void mbar_arrive_cluster(uint32_t bar, uint32_t cta) {
  asm volatile(
      "{\n.reg .b32 ra;\nmapa.shared::cluster.u32 ra, %0, %1;\n"
      "mbarrier.arrive.shared::cluster.b64 _, [ra];\n}" ::"r"(bar), "r"(cta) : "memory");
}
__device__ __forceinline__ void mbar_wait(uint32_t bar, uint32_t parity) {
  asm volatile(
      "{\n.reg .pred p;\n.reg .u32 n;\n"
      "mov.u32 n, 0;\n"
      "WAIT_LOOP:\n"
      "mbarrier.try_wait.parity.shared::cta.b64 p, [%0], %1, 0x400000;\n"
      "@p bra WAIT_DONE;\n"
      "add.u32 n, n, 1;\n"
      "setp.lt.u32 p, n, 4000000;\n"
      "@p bra WAIT_LOOP;\n"
      "trap;\n"
      "WAIT_DONE:\n}" ::"r"(bar), "r"(parity) : "memory");
}
__device__ __forceinline__ void fence_barrier_init() {
  asm volatile("fence.mbarrier_init.release.cluster;" ::: "memory");
}
__device__ __forceinline__ void fence_proxy_async() { asm volatile("fence.proxy.async.shared::cta;" ::: "memory"); }
__device__ __forceinline__ void cluster_sync_relaxed() {
  asm volatile("barrier.cluster.arrive.relaxed.aligned;\nbarrier.cluster.wait.aligned;" ::: "memory");
}
__device__ __forceinline__ void tma_load_2d(uint32_t dst, const CUtensorMap* m, int x, int y, uint32_t bar) {
  asm volatile(
      "cp.async.bulk.tensor.2d.shared::cluster.global.mbarrier::complete_tx::bytes [%0], [%1, {%3, %4}], [%2];" ::"r"(dst),
      "l"(m), "r"(bar), "r"(x), "r"(y)
      : "memory");
}
__device__ __forceinline__ void tma_load_2d_mc(uint32_t dst, const CUtensorMap* m, int x, int y, uint32_t bar, uint16_t mask) {
  asm volatile(
      "cp.async.bulk.tensor.2d.shared::cluster.global.mbarrier::complete_tx::bytes.multicast::cluster [%0], [%1, {%3, %4}], "
      "[%2], %5;" ::"r"(dst),
      "l"(m), "r"(bar), "r"(x), "r"(y), "h"(mask)
      : "memory");
}
__device__ __forceinline__ void tma_store_2d(const CUtensorMap* m, uint32_t src, int x, int y) {
  asm volatile("cp.async.bulk.tensor.2d.global.shared::cta.bulk_group [%0, {%2, %3}], [%1];" ::"l"(m), "r"(src), "r"(x),
               "r"(y)
               : "memory");
}
__device__ __forceinline__ void bulk_load(uint32_t dst, const void* src, uint32_t bytes, uint32_t bar) {
  asm volatile("cp.async.bulk.shared::cluster.global.mbarrier::complete_tx::bytes [%0], [%1], %2, [%3];" ::"r"(dst),
               "l"(src), "r"(bytes), "r"(bar)
               : "memory");
}
__device__ __forceinline__ void bulk_load_mc(uint32_t dst, const void* src, uint32_t bytes, uint32_t bar, uint16_t mask) {
  asm volatile("cp.async.bulk.shared::cluster.global.mbarrier::complete_tx::bytes.multicast::cluster [%0], [%1], %2, [%3], %4;" ::"r"(dst),
               "l"(src), "r"(bytes), "r"(bar), "h"(mask)
               : "memory");
}
__device__ __forceinline__ void pdl_launch_dependents() { asm volatile("griddepcontrol.launch_dependents;" ::: "memory"); }
__device__ __forceinline__ void pdl_wait() { asm volatile("griddepcontrol.wait;" ::: "memory"); }
__device__ __forceinline__ void wg_fence() { asm volatile("wgmma.fence.sync.aligned;" ::: "memory"); }
__device__ __forceinline__ void wg_commit() { asm volatile("wgmma.commit_group.sync.aligned;" ::: "memory"); }
template <int N>
__device__ __forceinline__ void wg_wait() {
  asm volatile("wgmma.wait_group.sync.aligned %0;" ::"n"(N) : "memory");
}
template <int M>
__device__ __forceinline__ void fence_regs(float (&r)[M]) {
#pragma unroll
  for (int i = 0; i < M; i++) asm volatile("" : "+f"(r[i])::"memory");
}
__device__ __forceinline__ uint64_t mkdesc(uint32_t addr, uint32_t lbo, uint32_t sbo, uint32_t layout) {
  return (uint64_t)((addr & 0x3FFFF) >> 4) | ((uint64_t)(lbo >> 4) << 16) | ((uint64_t)(sbo >> 4) << 32) |
         ((uint64_t)layout << 62);
}
__device__ __forceinline__ uint32_t pack_bf16(float lo, float hi) {
  uint32_t r;
  asm("cvt.rn.bf16x2.f32 %0, %1, %2;" : "=r"(r) : "f"(hi), "f"(lo));
  return r;
}
__device__ __forceinline__ float bf_lo(uint32_t v) { return __uint_as_float(v << 16); }
__device__ __forceinline__ float bf_hi(uint32_t v) { return __uint_as_float(v & 0xFFFF0000u); }
__device__ __forceinline__ float round_bf16(float x) { return bf_lo(pack_bf16(x, 0.f)); }
__device__ __forceinline__ float ex2f(float x) {
  float y;
  asm("ex2.approx.ftz.f32 %0, %1;" : "=f"(y) : "f"(x));
  return y;
}

__device__ __forceinline__ void wgmma_rs_n24_tb(float (&d)[12], uint32_t a0, uint32_t a1, uint32_t a2, uint32_t a3, uint64_t descB, int scaleD) {
  asm volatile("{\n.reg .pred p;\nsetp.ne.b32 p, %17, 0;\n"
    "wgmma.mma_async.sync.aligned.m64n24k16.f32.bf16.bf16 "
    "{%0, %1, %2, %3, %4, %5, %6, %7, %8, %9, %10, %11}, {%12, %13, %14, %15}, %16, p, 1, 1, 1;\n}\n"
    : "+f"(d[0]), "+f"(d[1]), "+f"(d[2]), "+f"(d[3]), "+f"(d[4]), "+f"(d[5]), "+f"(d[6]), "+f"(d[7]),
      "+f"(d[8]), "+f"(d[9]), "+f"(d[10]), "+f"(d[11])
    : "r"(a0), "r"(a1), "r"(a2), "r"(a3), "l"(descB), "r"(scaleD));
}
__device__ __forceinline__ void wgmma_rs_n64_z(float (&d)[32], uint32_t a0, uint32_t a1, uint32_t a2, uint32_t a3, uint64_t descB) {
  asm volatile("{\n.reg .pred p;\nsetp.ne.b32 p, %37, 0;\n"
    "wgmma.mma_async.sync.aligned.m64n64k16.f32.bf16.bf16 "
    "{%0, %1, %2, %3, %4, %5, %6, %7, %8, %9, %10, %11, %12, %13, %14, %15, %16, %17, %18, %19, %20, %21, %22, %23, %24, %25, %26, %27, %28, %29, %30, %31}, {%32, %33, %34, %35}, %36, p, 1, 1, 0;\n}\n"
    : "=f"(d[0]), "=f"(d[1]), "=f"(d[2]), "=f"(d[3]), "=f"(d[4]), "=f"(d[5]), "=f"(d[6]), "=f"(d[7]),
      "=f"(d[8]), "=f"(d[9]), "=f"(d[10]), "=f"(d[11]), "=f"(d[12]), "=f"(d[13]), "=f"(d[14]), "=f"(d[15]),
      "=f"(d[16]), "=f"(d[17]), "=f"(d[18]), "=f"(d[19]), "=f"(d[20]), "=f"(d[21]), "=f"(d[22]), "=f"(d[23]),
      "=f"(d[24]), "=f"(d[25]), "=f"(d[26]), "=f"(d[27]), "=f"(d[28]), "=f"(d[29]), "=f"(d[30]), "=f"(d[31])
    : "r"(a0), "r"(a1), "r"(a2), "r"(a3), "l"(descB), "n"(0));
}
__device__ __forceinline__ void wgmma_ss_n128_tb(float (&d)[64], uint64_t descA, uint64_t descB, int scaleD) {
  asm volatile("{\n.reg .pred p;\nsetp.ne.b32 p, %66, 0;\n"
    "wgmma.mma_async.sync.aligned.m64n128k16.f32.bf16.bf16 "
    "{%0, %1, %2, %3, %4, %5, %6, %7, %8, %9, %10, %11, %12, %13, %14, %15, %16, %17, %18, %19, %20, %21, %22, %23, %24, %25, %26, %27, %28, %29, %30, %31, %32, %33, %34, %35, %36, %37, %38, %39, %40, %41, %42, %43, %44, %45, %46, %47, %48, %49, %50, %51, %52, %53, %54, %55, %56, %57, %58, %59, %60, %61, %62, %63}, %64, %65, p, 1, 1, 0, 1;\n}\n"
    : "+f"(d[0]), "+f"(d[1]), "+f"(d[2]), "+f"(d[3]), "+f"(d[4]), "+f"(d[5]), "+f"(d[6]), "+f"(d[7]),
      "+f"(d[8]), "+f"(d[9]), "+f"(d[10]), "+f"(d[11]), "+f"(d[12]), "+f"(d[13]), "+f"(d[14]), "+f"(d[15]),
      "+f"(d[16]), "+f"(d[17]), "+f"(d[18]), "+f"(d[19]), "+f"(d[20]), "+f"(d[21]), "+f"(d[22]), "+f"(d[23]),
      "+f"(d[24]), "+f"(d[25]), "+f"(d[26]), "+f"(d[27]), "+f"(d[28]), "+f"(d[29]), "+f"(d[30]), "+f"(d[31]),
      "+f"(d[32]), "+f"(d[33]), "+f"(d[34]), "+f"(d[35]), "+f"(d[36]), "+f"(d[37]), "+f"(d[38]), "+f"(d[39]),
      "+f"(d[40]), "+f"(d[41]), "+f"(d[42]), "+f"(d[43]), "+f"(d[44]), "+f"(d[45]), "+f"(d[46]), "+f"(d[47]),
      "+f"(d[48]), "+f"(d[49]), "+f"(d[50]), "+f"(d[51]), "+f"(d[52]), "+f"(d[53]), "+f"(d[54]), "+f"(d[55]),
      "+f"(d[56]), "+f"(d[57]), "+f"(d[58]), "+f"(d[59]), "+f"(d[60]), "+f"(d[61]), "+f"(d[62]), "+f"(d[63])
    : "l"(descA), "l"(descB), "r"(scaleD));
}
__device__ __forceinline__ void wgmma_ss_n192_tb(float (&d)[96], uint64_t descA, uint64_t descB, int scaleD) {
  asm volatile("{\n.reg .pred p;\nsetp.ne.b32 p, %98, 0;\n"
    "wgmma.mma_async.sync.aligned.m64n192k16.f32.bf16.bf16 "
    "{%0, %1, %2, %3, %4, %5, %6, %7, %8, %9, %10, %11, %12, %13, %14, %15, %16, %17, %18, %19, %20, %21, %22, %23, %24, %25, %26, %27, %28, %29, %30, %31, %32, %33, %34, %35, %36, %37, %38, %39, %40, %41, %42, %43, %44, %45, %46, %47, %48, %49, %50, %51, %52, %53, %54, %55, %56, %57, %58, %59, %60, %61, %62, %63, %64, %65, %66, %67, %68, %69, %70, %71, %72, %73, %74, %75, %76, %77, %78, %79, %80, %81, %82, %83, %84, %85, %86, %87, %88, %89, %90, %91, %92, %93, %94, %95}, %96, %97, p, 1, 1, 0, 1;\n}\n"
    : "+f"(d[0]), "+f"(d[1]), "+f"(d[2]), "+f"(d[3]), "+f"(d[4]), "+f"(d[5]), "+f"(d[6]), "+f"(d[7]),
      "+f"(d[8]), "+f"(d[9]), "+f"(d[10]), "+f"(d[11]), "+f"(d[12]), "+f"(d[13]), "+f"(d[14]), "+f"(d[15]),
      "+f"(d[16]), "+f"(d[17]), "+f"(d[18]), "+f"(d[19]), "+f"(d[20]), "+f"(d[21]), "+f"(d[22]), "+f"(d[23]),
      "+f"(d[24]), "+f"(d[25]), "+f"(d[26]), "+f"(d[27]), "+f"(d[28]), "+f"(d[29]), "+f"(d[30]), "+f"(d[31]),
      "+f"(d[32]), "+f"(d[33]), "+f"(d[34]), "+f"(d[35]), "+f"(d[36]), "+f"(d[37]), "+f"(d[38]), "+f"(d[39]),
      "+f"(d[40]), "+f"(d[41]), "+f"(d[42]), "+f"(d[43]), "+f"(d[44]), "+f"(d[45]), "+f"(d[46]), "+f"(d[47]),
      "+f"(d[48]), "+f"(d[49]), "+f"(d[50]), "+f"(d[51]), "+f"(d[52]), "+f"(d[53]), "+f"(d[54]), "+f"(d[55]),
      "+f"(d[56]), "+f"(d[57]), "+f"(d[58]), "+f"(d[59]), "+f"(d[60]), "+f"(d[61]), "+f"(d[62]), "+f"(d[63]),
      "+f"(d[64]), "+f"(d[65]), "+f"(d[66]), "+f"(d[67]), "+f"(d[68]), "+f"(d[69]), "+f"(d[70]), "+f"(d[71]),
      "+f"(d[72]), "+f"(d[73]), "+f"(d[74]), "+f"(d[75]), "+f"(d[76]), "+f"(d[77]), "+f"(d[78]), "+f"(d[79]),
      "+f"(d[80]), "+f"(d[81]), "+f"(d[82]), "+f"(d[83]), "+f"(d[84]), "+f"(d[85]), "+f"(d[86]), "+f"(d[87]),
      "+f"(d[88]), "+f"(d[89]), "+f"(d[90]), "+f"(d[91]), "+f"(d[92]), "+f"(d[93]), "+f"(d[94]), "+f"(d[95])
    : "l"(descA), "l"(descB), "r"(scaleD));
}

__device__ __forceinline__ void ldsm4t(uint32_t (&b)[4], uint32_t addr) {
  asm volatile("ldmatrix.sync.aligned.m8n8.x4.trans.shared.b16 {%0,%1,%2,%3}, [%4];"
               : "=r"(b[0]), "=r"(b[1]), "=r"(b[2]), "=r"(b[3])
               : "r"(addr));
}
__device__ __forceinline__ void hmma(float (&c)[4], uint32_t a0, uint32_t a1, uint32_t a2, uint32_t a3, uint32_t b0, uint32_t b1) {
  asm("mma.sync.aligned.m16n8k16.row.col.f32.bf16.bf16.f32 {%0,%1,%2,%3}, {%4,%5,%6,%7}, {%8,%9}, {%0,%1,%2,%3};"
      : "+f"(c[0]), "+f"(c[1]), "+f"(c[2]), "+f"(c[3])
      : "r"(a0), "r"(a1), "r"(a2), "r"(a3), "r"(b0), "r"(b1));
}

__device__ __forceinline__ uint32_t movm(uint32_t a) {
  uint32_t d;
  asm volatile("movmatrix.sync.aligned.m8n8.trans.b16 %0, %1;" : "=r"(d) : "r"(a));
  return d;
}

#define K1_WARM 0
constexpr int K1_STAGES = 4;
constexpr int K1_W_BYTES = 3 * 8192;
constexpr int K1_X_BYTES = 8 * 16384;
constexpr int K1_BAR_OFF = K1_X_BYTES + K1_STAGES * K1_W_BYTES;
constexpr int K1_SMEM = K1_BAR_OFF + 192 + 1024;
constexpr float QSCALE = 0.25f * 1.4426950408889634f;

__device__ __forceinline__ uint32_t phi2(uint32_t t2) {
  uint32_t a2, mask, r2, o2;
  asm("add.rn.bf16x2 %0, %1, %2;" : "=r"(a2) : "r"(t2), "r"(0x3F803F80u));
  const uint32_t e2 = pack_bf16(ex2f(bf_lo(t2) * 1.4426950408889634f), ex2f(bf_hi(t2) * 1.4426950408889634f));
  asm("set.gt.u32.bf16x2 %0, %1, %2;" : "=r"(mask) : "r"(t2), "r"(0u));
  r2 = (a2 & mask) | (e2 & ~mask);
  asm("add.rn.bf16x2 %0, %1, %2;" : "=r"(o2) : "r"(r2), "r"(0x35863586u));
  return o2;
}

#define K1_SLOT_KB(h) ((h) < 4 ? 2 * (h) : 2 * ((h) - 4) + 1)
struct EpiCtx {
  uint4* qf;
  uint32_t* kp;
  uint32_t* vp;
  uint32_t s_red_addr;
  float* red;
  int lane;
};

template <bool LINEAR, int HH, int PART>
__device__ __forceinline__ void epi_slice(const float (&acc)[96], const EpiCtx& c, uint32_t (&pk)[4], float& vmax, bool live) {
  const float* a = &acc[HH * 8];
  const float* k = &acc[32 + HH * 8];
  const float* v = &acc[64 + HH * 8];
  if (!LINEAR) {
    if (PART == 0) {
      uint32_t* kh = c.kp + HH * (KV_HEAD_BYTES / 4);
      if (live) {
        c.qf[HH * 32 * 128] = make_uint4(pack_bf16(a[0], a[1]), pack_bf16(a[2], a[3]), pack_bf16(a[4], a[5]), pack_bf16(a[6], a[7]));
        kh[0] = pack_bf16(k[0], k[1]);
        kh[64] = pack_bf16(k[2], k[3]);
        kh[32] = pack_bf16(k[4], k[5]);
        kh[96] = pack_bf16(k[6], k[7]);
      }
      float q0 = a[0] * a[0] + a[1] * a[1] + a[4] * a[4] + a[5] * a[5];
      float q1 = a[2] * a[2] + a[3] * a[3] + a[6] * a[6] + a[7] * a[7];
      float k0 = k[0] * k[0] + k[1] * k[1] + k[4] * k[4] + k[5] * k[5];
      float k1 = k[2] * k[2] + k[3] * k[3] + k[6] * k[6] + k[7] * k[7];
#pragma unroll
      for (int o = 1; o <= 2; o <<= 1) {
        q0 += __shfl_xor_sync(0xffffffffu, q0, o);
        q1 += __shfl_xor_sync(0xffffffffu, q1, o);
        k0 += __shfl_xor_sync(0xffffffffu, k0, o);
        k1 += __shfl_xor_sync(0xffffffffu, k1, o);
      }
      const uint32_t qm = __reduce_max_sync(0xffffffffu, max(__float_as_uint(q0) & 0x7FFFFFFFu, __float_as_uint(q1) & 0x7FFFFFFFu));
      const uint32_t km = __reduce_max_sync(0xffffffffu, max(__float_as_uint(k0) & 0x7FFFFFFFu, __float_as_uint(k1) & 0x7FFFFFFFu));
      asm volatile(
          "{\n.reg .pred p;\nsetp.ne.b32 p, %3, 0;\n"
          "@p red.shared.max.u32 [%0], %1;\n@p red.shared.max.u32 [%0+4], %2;\n}" ::"r"(c.s_red_addr + HH * 8),
          "r"(qm), "r"(km), "r"((c.lane == 0 && live) ? 1 : 0)
          : "memory");
    } else {
      uint32_t* vh = c.vp + HH * (KV_HEAD_BYTES / 4);
      if (live) {
        vh[0] = pack_bf16(v[0], v[1]);
        vh[96] = pack_bf16(v[2], v[3]);
        vh[32] = pack_bf16(v[4], v[5]);
        vh[128] = pack_bf16(v[6], v[7]);
        vh[64] = 0x3F803F80u;
        vh[160] = 0x3F803F80u;
      }
#pragma unroll
      for (int i = 0; i < 8; i++) asm("max.NaN.f32 %0, %0, %1;" : "+f"(vmax) : "f"(fabsf(v[i])));
    }
  } else {
    if (PART == 0) {
      const uint4 pq = make_uint4(phi2(pack_bf16(a[0], a[1])), phi2(pack_bf16(a[2], a[3])), phi2(pack_bf16(a[4], a[5])),
                                  phi2(pack_bf16(a[6], a[7])));
      if (live) c.qf[HH * 32 * 128] = pq;
      pk[0] = movm(phi2(pack_bf16(k[0], k[1])));
      pk[2] = movm(phi2(pack_bf16(k[2], k[3])));
      pk[1] = movm(phi2(pack_bf16(k[4], k[5])));
      pk[3] = movm(phi2(pack_bf16(k[6], k[7])));
    } else {
      const uint32_t b0 = movm(pack_bf16(v[0], v[1]));
      const uint32_t b1 = movm(pack_bf16(v[2], v[3]));
      const uint32_t b2 = movm(pack_bf16(v[4], v[5]));
      const uint32_t b3 = movm(pack_bf16(v[6], v[7]));
      float c0[4] = {0, 0, 0, 0}, c1[4] = {0, 0, 0, 0}, c2[4] = {0, 0, 0, 0};
      hmma(c0, pk[0], pk[1], pk[2], pk[3], b0, b1);
      hmma(c1, pk[0], pk[1], pk[2], pk[3], b2, b3);
      hmma(c2, pk[0], pk[1], pk[2], pk[3], 0x3F803F80u, 0x3F803F80u);
      float* slot = c.red + HH * 2 * 4096;
      if (live) {
#pragma unroll
        for (int i = 0; i < 4; i++) {
          slot[i * 32] = c0[i];
          slot[(4 + i) * 32] = c1[i];
          slot[(8 + i) * 32] = c2[i];
        }
      }
    }
  }
}

template <bool LINEAR>
__device__ __forceinline__ void qkv_consumer(uint32_t sbase, uint8_t* smem_gen, uint32_t* s_red, int cp, int rt) {
  const uint32_t bar_full = sbase + K1_BAR_OFF;
  const uint32_t bar_empty = bar_full + 8 * K1_STAGES;
  const int warp = threadIdx.x >> 5;
  const int wg = warp >> 2;
  const int lane = threadIdx.x & 31;
  float accN[96], accP[96];
  EpiCtx c;
  {
    const int row0 = rt * 128 + wg * 64 + (warp & 3) * 16;
    c.qf = g_qfrag + ((size_t)((LINEAR ? NH : 0) + cp * 8) * 32 + (rt * 2 + wg)) * 128 + (threadIdx.x & 127);
    uint32_t* img = reinterpret_cast<uint32_t*>(reinterpret_cast<uint8_t*>(g_kv) + (size_t)(cp * 8) * KV_HEAD_BYTES);
    c.kp = img + (row0 >> 3) * 64 + lane;
    c.vp = img + KV_K_BYTES / 4 + (row0 >> 3) * 96 + lane;
    c.s_red_addr = smem_u32(s_red);
    c.red = reinterpret_cast<float*>(smem_gen + wg * 8192) + (warp & 3) * 384 + lane;
    c.lane = lane;
  }
  uint32_t pk[4] = {0, 0, 0, 0};
  float vmax = 0.f;
#pragma unroll
  for (int i = 0; i < 96; i++) asm volatile("mov.f32 %0, 0f00000000;" : "=f"(accN[i]));
  int npass;
  asm volatile("mov.u32 %0, 2;" : "=r"(npass));
#pragma unroll 1
  for (int pass = K1_WARM ? 0 : 1; pass < npass; pass++) {
    const bool live = K1_WARM ? pass != 0 : true;
    if (live) {
#pragma unroll 1
      for (int kb = 0; kb < 8; kb++) {
        const int s = kb % K1_STAGES;
        mbar_wait(bar_full + 8 * s, (kb / K1_STAGES) & 1);
        if (threadIdx.x == 0) PROF_T(0, 2 + (kb >> 1));
        const uint64_t dA = mkdesc(sbase + kb * 16384 + wg * 8192, 16, 1024, 1);
        const uint64_t dB = mkdesc(sbase + K1_X_BYTES + s * K1_W_BYTES, 8192, 1024, 1);
        wg_fence();
#pragma unroll
        for (int k = 0; k < 4; k++) wgmma_ss_n192_tb(accP, dA + k * 2, dB + k * 128, (kb | k) != 0);
        wg_commit();
        if (kb > 0) {
          wg_wait<1>();
          if ((threadIdx.x & 127) == 0) {
            const int sp = (kb - 1) % K1_STAGES;
            mbar_arrive_cluster(bar_empty + 8 * sp, 0);
            mbar_arrive_cluster(bar_empty + 8 * sp, 1);
          }
        }
      }
      wg_wait<0>();
      fence_regs(accP);
      if ((threadIdx.x & 127) == 0) {
        mbar_arrive_cluster(bar_empty + 8 * (7 % K1_STAGES), 0);
        mbar_arrive_cluster(bar_empty + 8 * (7 % K1_STAGES), 1);
      }
      if (threadIdx.x == 0) PROF_T(0, 6);
#define K1_T1_STEP(KB)                                                                           \
  {                                                                                              \
    constexpr int g = 8 + KB;                                                                    \
    constexpr int s = g % K1_STAGES;                                                             \
    mbar_wait(bar_full + 8 * s, (g / K1_STAGES) & 1);                                            \
    const uint64_t dA = mkdesc(sbase + KB * 16384 + wg * 8192, 16, 1024, 1);                     \
    const uint64_t dB = mkdesc(sbase + K1_X_BYTES + s * K1_W_BYTES, 8192, 1024, 1);              \
    wg_fence();                                                                                  \
    _Pragma("unroll") for (int k = 0; k < 4; k++) wgmma_ss_n192_tb(accN, dA + k * 2, dB + k * 128, (KB | k) != 0); \
    wg_commit();                                                                                 \
    epi_slice<LINEAR, KB / 2, KB & 1>(accP, c, pk, vmax, true);                                  \
    wg_wait<0>();                                                                                \
    if (KB + K1_STAGES < 8 && (threadIdx.x & 127) == 0) {                                        \
      mbar_arrive_cluster(bar_empty + 8 * s, 0);                                                 \
      mbar_arrive_cluster(bar_empty + 8 * s, 1);                                                 \
    }                                                                                            \
  }
      K1_T1_STEP(0) K1_T1_STEP(1) K1_T1_STEP(2) K1_T1_STEP(3) K1_T1_STEP(4) K1_T1_STEP(5) K1_T1_STEP(6) K1_T1_STEP(7)
#undef K1_T1_STEP
      fence_regs(accN);
      if (threadIdx.x == 0) PROF_T(0, 10);
      c.qf += 4 * 32 * 128;
      c.kp += 4 * (KV_HEAD_BYTES / 4);
      c.vp += 4 * (KV_HEAD_BYTES / 4);
      c.s_red_addr += 32;
      c.red += 4096;
    }
    float vm1 = 0.f;
    epi_slice<LINEAR, 0, 0>(accN, c, pk, vm1, live);
    epi_slice<LINEAR, 0, 1>(accN, c, pk, vm1, live);
    epi_slice<LINEAR, 1, 0>(accN, c, pk, vm1, live);
    epi_slice<LINEAR, 1, 1>(accN, c, pk, vm1, live);
    epi_slice<LINEAR, 2, 0>(accN, c, pk, vm1, live);
    epi_slice<LINEAR, 2, 1>(accN, c, pk, vm1, live);
    epi_slice<LINEAR, 3, 0>(accN, c, pk, vm1, live);
    epi_slice<LINEAR, 3, 1>(accN, c, pk, vm1, live);
    if (live) asm("max.NaN.f32 %0, %0, %1;" : "+f"(vmax) : "f"(vm1));
  }
  if (!LINEAR) {
    const uint32_t vm = __reduce_max_sync(0xffffffffu, __float_as_uint(vmax) & 0x7FFFFFFFu);
    if (lane == 0) atomicMax(&s_red[16], vm);
    asm volatile("bar.sync 1, 256;" ::: "memory");
    if (threadIdx.x < 8) {
      *reinterpret_cast<float4*>(&g_nrm[((cp * 8 + threadIdx.x) * 16 + rt) * 4]) =
          make_float4(__uint_as_float(s_red[threadIdx.x * 2]), __uint_as_float(s_red[threadIdx.x * 2 + 1]), __uint_as_float(s_red[16]), 0.f);
    }
  } else {
    asm volatile("bar.sync 1, 256;" ::: "memory");
    float* dst = g_kvpart + ((size_t)rt * NH + cp * 8) * 384 + threadIdx.x;
    const float* base = reinterpret_cast<const float*>(smem_gen);
#pragma unroll
    for (int i = 0; i < 12; i++) {
      const int h0 = (i / 3) * 2, r = i % 3;
      const bool second = r == 2 || (r == 1 && threadIdx.x >= 128);
      const int e = (int)threadIdx.x + r * 256 - (second ? 384 : 0);
      const float* src = base + (second ? K1_SLOT_KB(h0 + 1) : K1_SLOT_KB(h0)) * 4096 + e;
      float sum = 0.f;
#pragma unroll
      for (int w = 0; w < 8; w++) sum += src[(w >> 2) * 2048 + (w & 3) * 384];
      dst[i * 256] = sum;
    }
  }
}

__global__ void __launch_bounds__(384, 1)
qkv_gemm_kernel(const __grid_constant__ CUtensorMap mxA, const __grid_constant__ CUtensorMap mxB,
                const __grid_constant__ CUtensorMap mwA, const __grid_constant__ CUtensorMap mwB) {
  extern __shared__ uint8_t smem_raw[];
  const uint32_t sbase = (smem_u32(smem_raw) + 1023) & ~1023u;
  uint8_t* smem_gen = smem_raw + (sbase - smem_u32(smem_raw));
  const uint32_t bar_full = sbase + K1_BAR_OFF;
  const uint32_t bar_empty = bar_full + 8 * K1_STAGES;
  uint32_t* s_red = reinterpret_cast<uint32_t*>(smem_gen + K1_BAR_OFF + 64);

  const int rank = blockIdx.x & 1;
  const int pair = blockIdx.x >> 1;
  const int branch = pair >> 5;
  const int rp = (pair & 31) >> 2;
  const int cp = pair & 3;
  const int rt = rp * 2 + rank;
  const int warp = threadIdx.x >> 5;
  if (threadIdx.x == 0) { PROF_G(0, 30); PROF_T(0, 0); }
  const CUtensorMap* mx = branch ? &mxA : &mxB;
  const CUtensorMap* mw = branch ? &mwA : &mwB;

  if (threadIdx.x == 256) {
    asm volatile("prefetch.tensormap [%0];" ::"l"(mx) : "memory");
    asm volatile("prefetch.tensormap [%0];" ::"l"(mw) : "memory");
    for (int i = 0; i < K1_STAGES; i++) {
      mbar_init(bar_full + 8 * i, 1);
      mbar_init(bar_empty + 8 * i, 4);
    }
    fence_barrier_init();
    fence_proxy_async();
    for (int kb = 0; kb < K1_STAGES; kb++) mbar_expect_tx(bar_full + 8 * kb, 16384 + K1_W_BYTES);
    tma_load_2d(sbase, mx, 0, rt * 128, bar_full);
  }
  pdl_launch_dependents();
  if (threadIdx.x < 32) s_red[threadIdx.x] = 0;
  __syncthreads();
  cluster_sync_relaxed();
  if (threadIdx.x == 0) PROF_T(0, 1);

  if (warp >= 8) {
    asm volatile("setmaxnreg.dec.sync.aligned.u32 40;");
    if (threadIdx.x == 256) {
      for (int g = 0; g < 16; g++) {
        const int s = g % K1_STAGES;
        const int kb = g & 7;
        if (g >= K1_STAGES) {
          mbar_wait(bar_empty + 8 * s, ((g / K1_STAGES) - 1) & 1);
          mbar_expect_tx(bar_full + 8 * s, (g < 8 ? 16384 : 0) + K1_W_BYTES);
        }
        if (g > 0 && g < 8) tma_load_2d(sbase + kb * 16384, mx, kb * 64, rt * 128, bar_full + 8 * s);
        const int h0 = cp * 8 + (g >> 3) * 4;
        const uint32_t st = sbase + K1_X_BYTES + s * K1_W_BYTES + rank * 4096;
#pragma unroll
        for (int p = 0; p < 3; p++)
          tma_load_2d_mc(st + p * 8192, mw, p * 512 + h0 * 16, kb * 64 + rank * 32, bar_full + 8 * s, (uint16_t)3);
      }
    }
    __syncwarp();
    cluster_sync_relaxed();
  } else {
    asm volatile("setmaxnreg.inc.sync.aligned.u32 232;");
    if (branch == 0) qkv_consumer<false>(sbase, smem_gen, s_red, cp, rt);
    else qkv_consumer<true>(sbase, smem_gen, s_red, cp, rt);
    if (threadIdx.x == 0) PROF_T(0, 11);
    __syncwarp();
    cluster_sync_relaxed();
    if (threadIdx.x == 0) { PROF_T(0, 12); PROF_G(0, 31); }
  }
}

constexpr int K2_SMEM = KV_HEAD_BYTES + 1024 + 256;

#define ATT_NPOLY 19
#define ATT_CH 8
#define ATT_D 1
#define PRO_MODE 1
#define STAGGER 0
#define K2_WARM 0
#define K2_FIRST 2
#define CONST_SMID 0
#define ATT_STRUCT 1
#define ATT_PIN 0
#define ATT_GM 1
#define ATT_DEG 2
struct ExpC {
  uint32_t k3c00, kmask, seven, c3;
};
__device__ __forceinline__ uint32_t hfma2(uint32_t a, uint32_t b, uint32_t c) {
  uint32_t r;
  asm("fma.rn.f16x2 %0, %1, %2, %3;" : "=r"(r) : "r"(a), "r"(b), "r"(c));
  return r;
}
__device__ __forceinline__ uint32_t exp2_poly_pair(float t0, float t1, const ExpC& c) {
  uint32_t u;
  asm("prmt.b32 %0, %1, %2, 0x5410;" : "=r"(u) : "r"(__float_as_uint(t0)), "r"(__float_as_uint(t1)));
  uint32_t m;
  asm("lop3.b32 %0, %1, 0x03FF03FF, %2, 0xEA;" : "=r"(m) : "r"(u), "r"(c.k3c00));
  uint32_t p = hfma2(m, c.c3, 0xa385a385u);
  p = hfma2(p, m, 0x4ad64ad7u);
  uint32_t mu;
  asm("lop3.b32 %0, %1, 0xFC00FC00, %2, 0xEA;" : "=r"(mu) : "r"(u), "r"(c.kmask));
  uint32_t r;
  asm("{.reg .b32 t; shf.r.wrap.b32 t, %1, %2, 3; add.u32 %0, t, %3;}" : "=r"(r) : "r"(mu), "r"(c.seven), "r"(p));
  return r;
}
__device__ __forceinline__ float gadd(float x, float M, uint32_t g) {
  float r = x;
  asm("{.reg .pred p; setp.ne.b32 p, %2, -1; @p add.f32 %0, %0, %1;}" : "+f"(r) : "f"(M), "r"(g));
  return r;
}
__device__ __forceinline__ float gex2(float x, uint32_t g) {
  float r = x;
  asm("{.reg .pred p; setp.ne.b32 p, %1, -1; @p ex2.approx.ftz.f32 %0, %0;}" : "+f"(r) : "r"(g));
  return r;
}
template <int NPOLY, int NPAIR, int CH, int D, bool G0 = false>
__device__ __forceinline__ void exp_tile(const float (&s)[2 * NPAIR], uint32_t (&p)[NPAIR], const ExpC& c, uint32_t g0 = 0) {
#pragma unroll
  for (int i = 0; i < NPAIR; i++) {
    const bool isPoly = ((i + 1) * NPOLY / 32) != (i * NPOLY / 32);
    const int ch = i / CH;
    const bool gated = ch >= D || G0;
    int gi = (ch - D) * CH + CH - 1;
    if (ch >= D) {
      while (gi > (ch - D) * CH && !(((gi + 1) * NPOLY / 32) != (gi * NPOLY / 32))) gi--;
    }
    const uint32_t g = ch >= D ? p[gi] : g0;
    if (!isPoly) {
      if (gated && ATT_GM) p[i] = pack_bf16(gex2(s[2 * i], g), gex2(s[2 * i + 1], g));
      else p[i] = pack_bf16(ex2f(s[2 * i]), ex2f(s[2 * i + 1]));
    } else {
      if (gated) p[i] = exp2_poly_pair(gadd(s[2 * i], 12329.f, g), gadd(s[2 * i + 1], 12329.f, g), c);
      else p[i] = exp2_poly_pair(s[2 * i] + 12329.f, s[2 * i + 1] + 12329.f, c);
    }
  }
}

__device__ __forceinline__ void store_o(__nv_bfloat16* o, int row0, int head, int lane, const uint32_t (&r)[4]) {
  const int g = lane >> 2, t = lane & 3;
  uint32_t* p0 = reinterpret_cast<uint32_t*>(o + (size_t)(row0 + g) * DM + head * 16) + t;
  uint32_t* p1 = reinterpret_cast<uint32_t*>(o + (size_t)(row0 + g + 8) * DM + head * 16) + t;
  p0[0] = r[0];
  p1[0] = r[1];
  p0[4] = r[2];
  p1[4] = r[3];
}

__device__ __forceinline__ void kv_fetch_piece(uint32_t sbase, uint32_t bar, int piece) {
  const uint8_t* img = reinterpret_cast<const uint8_t*>(g_kv) + (size_t)(blockIdx.x >> 2) * KV_HEAD_BYTES;
  const int g = piece >> 1, isv = piece & 1;
  const int e0 = g == 0 ? 0 : (isv ? 256 : 320) + (g - 1) * 512;
  const int e1 = g == 3 ? 2048 : (isv ? 256 : 320) + g * 512;
  const int bytes = (e1 - e0) * (isv ? 48 : 32);
  const int off = isv ? KV_K_BYTES + e0 * 48 : e0 * 32;
  mbar_expect_tx(bar + 8 * g, bytes);
  bulk_load(sbase + off, img + off, bytes, bar + 8 * g);
}

__device__ __forceinline__ void safe_exp(float (&s)[32], uint32_t (&p)[16], float (&o)[12], float& m0, float& m1) {
#pragma unroll
  for (int i = 0; i < 16; i++) {
    const uint32_t r = pack_bf16(s[2 * i], s[2 * i + 1]);
    s[2 * i] = bf_lo(r) * QSCALE;
    s[2 * i + 1] = bf_hi(r) * QSCALE;
  }
  float x0 = s[0], x1 = s[2];
#pragma unroll
  for (int i = 0; i < 8; i++) {
    x0 = fmaxf(x0, fmaxf(s[4 * i], s[4 * i + 1]));
    x1 = fmaxf(x1, fmaxf(s[4 * i + 2], s[4 * i + 3]));
  }
  x0 = fmaxf(x0, __shfl_xor_sync(0xffffffffu, x0, 1));
  x1 = fmaxf(x1, __shfl_xor_sync(0xffffffffu, x1, 1));
  x0 = fmaxf(x0, __shfl_xor_sync(0xffffffffu, x0, 2));
  x1 = fmaxf(x1, __shfl_xor_sync(0xffffffffu, x1, 2));
  const float n0 = fmaxf(m0, x0), n1 = fmaxf(m1, x1);
  const float c0 = ex2f(m0 - n0), c1 = ex2f(m1 - n1);
  m0 = n0;
  m1 = n1;
#pragma unroll
  for (int i = 0; i < 3; i++) {
    o[4 * i] *= c0;
    o[4 * i + 1] *= c0;
    o[4 * i + 2] *= c1;
    o[4 * i + 3] *= c1;
  }
#pragma unroll
  for (int i = 0; i < 8; i++) {
    p[2 * i] = pack_bf16(ex2f(s[4 * i] - n0), ex2f(s[4 * i + 1] - n0));
    p[2 * i + 1] = pack_bf16(ex2f(s[4 * i + 2] - n1), ex2f(s[4 * i + 3] - n1));
  }
}

__device__ __forceinline__ void attn_step(float (&sx)[32], float (&sy)[32], float (&o)[12], const uint4& qf, uint64_t dK, uint64_t dV,
                                          const ExpC& ec) {
  uint32_t pa[16], pb[16];
  wg_fence();
  wgmma_rs_n64_z(sy, qf.x, qf.y, qf.z, qf.w, dK + 128);
  wg_commit();
  exp_tile<ATT_NPOLY, 16, ATT_CH, ATT_D>(sx, pa, ec);
  wg_fence();
  wgmma_rs_n24_tb(o, pa[12], pa[13], pa[14], pa[15], dV + 3 * 48, 1);
  wg_commit();
  wg_wait<1>();
  fence_regs(sy);
  exp_tile<ATT_NPOLY, 16, ATT_CH, ATT_D>(sy, pb, ec);
  wg_fence();
#pragma unroll
  for (int k = 0; k < 3; k++) wgmma_rs_n24_tb(o, pa[4 * k], pa[4 * k + 1], pa[4 * k + 2], pa[4 * k + 3], dV + k * 48, 1);
#pragma unroll
  for (int k = 0; k < 4; k++) wgmma_rs_n24_tb(o, pb[4 * k], pb[4 * k + 1], pb[4 * k + 2], pb[4 * k + 3], dV + (4 + k) * 48, 1);
  wgmma_rs_n64_z(sy, qf.x, qf.y, qf.z, qf.w, dK + 256);
  wg_commit();
  wg_wait<0>();
  fence_regs(sy);
}

template <bool SAFE>
__device__ __forceinline__ void attn_tile(uint64_t dK, uint64_t dV, uint32_t bar, uint4 qf, const ExpC& ec, uint32_t (&outp)[4],
                                          bool warm) {
  float o[12];
#pragma unroll
  for (int i = 0; i < 12; i++) asm volatile("mov.f32 %0, 0f00000000;" : "=f"(o[i]));
  if (!warm) mbar_wait(bar, 0);
  if (!SAFE) {
    qf.x = pack_bf16(bf_lo(qf.x) * QSCALE, bf_hi(qf.x) * QSCALE);
    qf.y = pack_bf16(bf_lo(qf.y) * QSCALE, bf_hi(qf.y) * QSCALE);
    qf.z = pack_bf16(bf_lo(qf.z) * QSCALE, bf_hi(qf.z) * QSCALE);
    qf.w = pack_bf16(bf_lo(qf.w) * QSCALE, bf_hi(qf.w) * QSCALE);
    float s0[32], s1[32];
    wg_fence();
    wgmma_rs_n64_z(s0, qf.x, qf.y, qf.z, qf.w, dK);
    wg_commit();
    wg_wait<0>();
    fence_regs(s0);
#pragma unroll 1
    for (int p = warm ? 7 : 0; p < 8; p++) {
      if ((p & 1) && !warm) mbar_wait(bar + 8 * min((p + 1) >> 1, 3), 0);
      attn_step(s0, s1, o, qf, dK, dV, ec);
      attn_step(s1, s0, o, qf, dK + 256, dV + 384, ec);
      dK += 512;
      dV += 768;
    }
  } else {
    float m0 = -INFINITY, m1 = -INFINITY;
#pragma unroll 1
    for (int j = 0; j < 32; j++) {
      if (j == 4) { mbar_wait(bar + 8, 0); mbar_wait(bar + 16, 0); mbar_wait(bar + 24, 0); }
      float s[32];
      uint32_t p[16];
      wg_fence();
      wgmma_rs_n64_z(s, qf.x, qf.y, qf.z, qf.w, dK);
      wg_commit();
      wg_wait<0>();
      fence_regs(s);
      safe_exp(s, p, o, m0, m1);
      wg_fence();
#pragma unroll
      for (int k = 0; k < 4; k++) wgmma_rs_n24_tb(o, p[4 * k], p[4 * k + 1], p[4 * k + 2], p[4 * k + 3], dV + k * 48, 1);
      wg_commit();
      wg_wait<0>();
      fence_regs(o);
      dK += 128;
      dV += 192;
    }
  }
  fence_regs(o);
  const float r0 = 1.0f / o[8], r1 = 1.0f / o[10];
  outp[0] = pack_bf16(o[0] * r0, o[1] * r0);
  outp[1] = pack_bf16(o[2] * r1, o[3] * r1);
  outp[2] = pack_bf16(o[4] * r0, o[5] * r0);
  outp[3] = pack_bf16(o[6] * r1, o[7] * r1);
}

__device__ __forceinline__ void linear_attn_cta(uint8_t* smem_raw, uint32_t sbase, const CUtensorMap* mo16, int cta) {
  const int warp = threadIdx.x >> 5, lane = threadIdx.x & 31;
  const int hg = warp & 1;
  const uint4* qp = g_qfrag + (size_t)(NH + cta * 8 + hg * 4) * 32 * 128 + lane;
  auto qaddr = [&](int i) {
    const int blk16 = i * 8 + (warp >> 1);
    return qp + (blk16 >> 2) * 128 + (blk16 & 3) * 32;
  };
  uint4 q[4];
#pragma unroll
  for (int h = 0; h < 4; h++) q[h] = qaddr(0)[h * 32 * 128];
  float* red = reinterpret_cast<float*>(smem_raw + (sbase - smem_u32(smem_raw)) + 131072);
  {
    const float* src = g_kvpart + (size_t)cta * 8 * 384;
    float sum[6];
#pragma unroll
    for (int i = 0; i < 6; i++) sum[i] = 0.f;
#pragma unroll
    for (int r = 0; r < 16; r++) {
#pragma unroll
      for (int i = 0; i < 6; i++) sum[i] += src[(size_t)r * NH * 384 + threadIdx.x + i * 512];
    }
#pragma unroll
    for (int i = 0; i < 6; i++) red[threadIdx.x + i * 512] = round_bf16(sum[i]);
  }
  __syncthreads();
  if (threadIdx.x == 0) PROF_T(1, 1);
  uint32_t bf[4][6];
  {
    const int g = lane >> 2, t = lane & 3;
#pragma unroll
    for (int h = 0; h < 4; h++) {
#pragma unroll
      for (int f = 0; f < 6; f++) {
        const int blk = f >> 1, half = f & 1;
        const int e = (blk == 2) ? 0 : g;
        const int d = 2 * t + 8 * half;
        const int base = (hg * 4 + h) * 384 + (blk * 4 + half * 2 + (e & 1)) * 32 + (e >> 1);
        bf[h][f] = pack_bf16(red[base + (d & 7) * 4], red[base + ((d + 1) & 7) * 4]);
      }
    }
  }
  if (threadIdx.x == 0) PROF_T(1, 2);
  const uint32_t stg = sbase + warp * 8192;
#pragma unroll 1
  for (int i = 0; i < 16; i++) {
    uint4 qc[4];
#pragma unroll
    for (int h = 0; h < 4; h++) qc[h] = q[h];
    if (i + 1 < 16) {
#pragma unroll
      for (int h = 0; h < 4; h++) q[h] = qaddr(i + 1)[h * 32 * 128];
    }
    const uint32_t buf = stg + (i & 3) * 2048;
    if (i >= 4) {
      if (lane == 0) asm volatile("cp.async.bulk.wait_group.read 3;" ::: "memory");
      __syncwarp();
    }
#pragma unroll
    for (int h = 0; h < 4; h++) {
      float n0[4] = {0, 0, 0, 0}, n1[4] = {0, 0, 0, 0}, dn[4] = {0, 0, 0, 0};
      hmma(n0, qc[h].x, qc[h].y, qc[h].z, qc[h].w, bf[h][0], bf[h][1]);
      hmma(n1, qc[h].x, qc[h].y, qc[h].z, qc[h].w, bf[h][2], bf[h][3]);
      hmma(dn, qc[h].x, qc[h].y, qc[h].z, qc[h].w, bf[h][4], bf[h][5]);
      const float d0 = __fdividef(1.0f, dn[0] + 1e-6f), d1 = __fdividef(1.0f, dn[2] + 1e-6f);
      const uint32_t r0 = pack_bf16(n0[0] * d0, n0[1] * d0);
      const uint32_t r1 = pack_bf16(n0[2] * d1, n0[3] * d1);
      const uint32_t r2 = pack_bf16(n1[0] * d0, n1[1] * d0);
      const uint32_t r3 = pack_bf16(n1[2] * d1, n1[3] * d1);
      const int row = lane & 15;
      const int chunk = h * 2 + (lane >> 4);
      const uint32_t addr = buf + row * 128 + ((chunk ^ (row & 7)) << 4);
      asm volatile("stmatrix.sync.aligned.m8n8.x4.shared.b16 [%0], {%1,%2,%3,%4};" ::"r"(addr), "r"(r0), "r"(r1), "r"(r2), "r"(r3)
                   : "memory");
    }
    fence_proxy_async();
    __syncwarp();
    if (lane == 0) {
      tma_store_2d(mo16, buf, cta * 128 + hg * 64, (i * 8 + (warp >> 1)) * 16);
      asm volatile("cp.async.bulk.commit_group;" ::: "memory");
    }
  }
  if (threadIdx.x == 0) PROF_T(1, 3);
  if (lane == 0) asm volatile("cp.async.bulk.wait_group 0;" ::: "memory");
}

__global__ void __launch_bounds__(512, 1)
attn_kernel(const __grid_constant__ CUtensorMap mo16, const uint8_t* __restrict__ woA, const uint8_t* __restrict__ woB) {
  extern __shared__ uint8_t smem_raw[];
  const uint32_t sbase = (smem_u32(smem_raw) + 1023) & ~1023u;
  const uint32_t bar = sbase + KV_HEAD_BYTES;
  if (threadIdx.x == 0) { PROF_G(1, 30); PROF_T(1, 0); }
  if (threadIdx.x == 0) {
    for (int i = 0; i < 4; i++) mbar_init(bar + 8 * i, 2);
    asm volatile("st.shared.v4.u32 [%0], {%1, %2, %3, %4};" ::"r"(bar + 64), "r"(0x3C003C00u), "r"(0x00070000u), "r"(7u),
                 "r"(ATT_DEG == 3 ? 0x2cfd2cfdu : 0x35623562u)
                 : "memory");
    fence_barrier_init();
    fence_proxy_async();
  }
  __syncthreads();
  pdl_launch_dependents();
  if (blockIdx.x >= 128 && threadIdx.x < 16) {
    const int i = (blockIdx.x - 128) * 16 + threadIdx.x;
    const uint8_t* p = (i < 32 ? woA : woB) + (size_t)(i & 31) * 16384;
    asm volatile("cp.async.bulk.prefetch.L2.global [%0], %1;" ::"l"(p), "r"(16384) : "memory");
  }
  if (blockIdx.x >= 128) {
    pdl_wait();
    linear_attn_cta(smem_raw, sbase, &mo16, blockIdx.x - 128);
    if (threadIdx.x == 0) { PROF_T(1, 5); PROF_G(1, 31); }
    return;
  }
  const int head = blockIdx.x >> 2, qb = blockIdx.x & 3;
  const int lane = threadIdx.x & 31;
  const int wg = __shfl_sync(0xffffffffu, threadIdx.x >> 7, 0), warp = __shfl_sync(0xffffffffu, (threadIdx.x >> 5) & 3, 0);
  ExpC ec;
  asm volatile("ld.volatile.shared.v4.u32 {%0, %1, %2, %3}, [%4];" : "=r"(ec.k3c00), "=r"(ec.kmask), "=r"(ec.seven), "=r"(ec.c3) : "r"(bar + 64));
  const uint64_t dK = mkdesc(sbase, 128, 256, 0);
  const uint64_t dV = mkdesc(sbase + KV_K_BYTES, 384, 128, 0);
  uint4 qnext = make_uint4(0, 0, 0, 0);
  bool safe_path = false;
#pragma unroll 1
  for (int t = (K2_WARM && blockIdx.x < 4) ? -1 : 0; t < 2; t++) {
    if (t == 0) {
      pdl_wait();
      if (threadIdx.x == 0) { PROF_T(1, 7); PROF_G(1, 29); }
      if (threadIdx.x == 0) {
#pragma unroll
        for (int piece = 0; piece < K2_FIRST; piece++) kv_fetch_piece(sbase, bar, piece);
      }
      qnext = g_qfrag[(head * 32 + qb * 8 + wg * 2) * 128 + (threadIdx.x & 127)];
      float4 n = make_float4(0.f, 0.f, 0.f, 0.f);
      if (lane < 16) n = *reinterpret_cast<const float4*>(&g_nrm[(head * 16 + lane) * 4]);
      uint32_t qm = ((lane >> 2) == qb) ? __float_as_uint(n.x) : 0u;
      qm = __reduce_max_sync(0xffffffffu, qm);
      const uint32_t km = __reduce_max_sync(0xffffffffu, __float_as_uint(n.y));
      const uint32_t vm = __reduce_max_sync(0xffffffffu, __float_as_uint(n.z));
      const float b2 = __uint_as_float(qm) * (QSCALE * QSCALE) * __uint_as_float(km) * 1.02f;
      const float vmax = __uint_as_float(vm);
      const bool ok = (b2 <= 21.5f * 21.5f) && (vmax <= 1.0e24f) && (vmax >= 1.0e-18f || vmax == 0.f);
      safe_path = !ok;
      if (K2_FIRST < 8) {
        mbar_wait(bar, 0);
        if (threadIdx.x == 0) {
#pragma unroll
          for (int piece = K2_FIRST; piece < 8; piece++) kv_fetch_piece(sbase, bar, piece);
        }
      }
    }
    const int tile64 = qb * 8 + wg * 2 + t;
    const uint4 qf = qnext;
    if (t == 0) qnext = g_qfrag[(head * 32 + tile64 + 1) * 128 + (threadIdx.x & 127)];
    uint32_t r[4];
    if (threadIdx.x == 0 && t >= 0) PROF_T(1, 1 + t);
    if (!safe_path) attn_tile<false>(dK, dV, bar, qf, ec, r, t < 0);
    else attn_tile<true>(dK, dV, bar, qf, ec, r, false);
    if (t >= 0) store_o(g_o + (size_t)S_LEN * DM, tile64 * 64 + warp * 16, head, lane, r);
  }
  if (threadIdx.x == 0) { PROF_T(1, 5); PROF_G(1, 31); }
}

#define K3_WPRE 2
constexpr int K3_STAGES = 5;
constexpr int K3_W_BYTES = 8 * 16384;
constexpr int K3_BAR_OFF = K3_W_BYTES + K3_STAGES * 16384;
constexpr int K3_SMEM = K3_BAR_OFF + 256 + 1024;

__global__ void __launch_bounds__(288, 1)
out_gemm_kernel(const __grid_constant__ CUtensorMap mo, const __grid_constant__ CUtensorMap mwA,
                const __grid_constant__ CUtensorMap mwB, const __grid_constant__ CUtensorMap mout) {
  extern __shared__ uint8_t smem_raw[];
  const uint32_t sbase = (smem_u32(smem_raw) + 1023) & ~1023u;
  const uint32_t bar_full = sbase + K3_BAR_OFF;
  const uint32_t bar_empty = bar_full + 8 * K3_STAGES;
  const uint32_t bar_w = bar_empty + 8 * K3_STAGES;
  const int branch = blockIdx.x >> 6;
  const int rt = (blockIdx.x & 63) >> 2;
  const int ct = blockIdx.x & 3;
  const int warp = threadIdx.x >> 5;
  if (threadIdx.x == 0) { PROF_G(2, 30); PROF_T(2, 0); }
  if (threadIdx.x == 256) {
    const CUtensorMap* mw = branch ? &mwB : &mwA;
    asm volatile("prefetch.tensormap [%0];" ::"l"(mw) : "memory");
    asm volatile("prefetch.tensormap [%0];" ::"l"(&mo) : "memory");
    asm volatile("prefetch.tensormap [%0];" ::"l"(&mout) : "memory");
    for (int i = 0; i < K3_STAGES; i++) {
      mbar_init(bar_full + 8 * i, 1);
      mbar_init(bar_empty + 8 * i, 2);
    }
    for (int i = 0; i < 8; i++) mbar_init(bar_w + 8 * i, 1);
    fence_barrier_init();
    fence_proxy_async();
    for (int kb = 0; kb < K3_WPRE; kb++) {
      mbar_expect_tx(bar_w + 8 * kb, 16384);
      tma_load_2d(sbase + kb * 16384, mw, ct * 128, kb * 64, bar_w + 8 * kb);
      tma_load_2d(sbase + kb * 16384 + 8192, mw, ct * 128 + 64, kb * 64, bar_w + 8 * kb);
    }
  }
  __syncthreads();
  if (warp == 8) {
    if ((threadIdx.x & 31) == 0) {
      const CUtensorMap* mw = branch ? &mwB : &mwA;
      pdl_wait();
      PROF_T(2, 1);
      for (int kb = 0; kb < 8; kb++) {
        const int s = kb % K3_STAGES;
        if (kb >= K3_STAGES) mbar_wait(bar_empty + 8 * s, ((kb / K3_STAGES) - 1) & 1);
        mbar_expect_tx(bar_full + 8 * s, 16384);
        tma_load_2d(sbase + K3_W_BYTES + s * 16384, &mo, kb * 64, branch * S_LEN + rt * 128, bar_full + 8 * s);
        const int kw = kb + K3_WPRE;
        if (kw < 8) {
          mbar_expect_tx(bar_w + 8 * kw, 16384);
          tma_load_2d(sbase + kw * 16384, mw, ct * 128, kw * 64, bar_w + 8 * kw);
          tma_load_2d(sbase + kw * 16384 + 8192, mw, ct * 128 + 64, kw * 64, bar_w + 8 * kw);
        }
      }
    }
  } else {
    const int wg = warp >> 2;
    float acc[64];
    for (int kb = 0; kb < 8; kb++) {
      const int s = kb % K3_STAGES;
      mbar_wait(bar_w + 8 * kb, 0);
      mbar_wait(bar_full + 8 * s, (kb / K3_STAGES) & 1);
      if (threadIdx.x == 0) PROF_T(2, 2 + kb);
      const uint64_t dA = mkdesc(sbase + K3_W_BYTES + s * 16384 + wg * 8192, 16, 1024, 1);
      const uint64_t dB = mkdesc(sbase + kb * 16384, 8192, 1024, 1);
      wg_fence();
#pragma unroll
      for (int k = 0; k < 4; k++) wgmma_ss_n128_tb(acc, dA + k * 2, dB + k * 128, (kb | k) != 0);
      wg_commit();
      if (kb > 0) {
        wg_wait<1>();
        if ((threadIdx.x & 127) == 0) mbar_arrive(bar_empty + 8 * ((kb - 1) % K3_STAGES));
      }
    }
    wg_wait<0>();
    fence_regs(acc);
    if (threadIdx.x == 0) PROF_T(2, 10);
    const uint32_t stg = sbase + K3_W_BYTES + wg * 8192;
    const int lane = threadIdx.x & 31;
    const int rloc = (warp & 3) * 16 + (lane & 15);
#pragma unroll
    for (int c16 = 0; c16 < 8; c16++) {
      const float* a = &acc[c16 * 8];
      const uint32_t r0 = pack_bf16(a[0], a[1]), r1 = pack_bf16(a[2], a[3]), r2 = pack_bf16(a[4], a[5]), r3 = pack_bf16(a[6], a[7]);
      const int chunk = (c16 & 3) * 2 + (lane >> 4);
      const uint32_t addr = stg + (c16 >> 2) * 16384 + rloc * 128 + ((chunk ^ (rloc & 7)) << 4);
      asm volatile("stmatrix.sync.aligned.m8n8.x4.shared.b16 [%0], {%1,%2,%3,%4};" ::"r"(addr), "r"(r0), "r"(r1), "r"(r2), "r"(r3)
                   : "memory");
    }
    fence_proxy_async();
    asm volatile("bar.sync %0, 128;" ::"r"(2 + wg) : "memory");
    if ((threadIdx.x & 127) == 0) {
      tma_store_2d(&mout, stg, branch * DM + ct * 128, rt * 128 + wg * 64);
      tma_store_2d(&mout, stg + 16384, branch * DM + ct * 128 + 64, rt * 128 + wg * 64);
      asm volatile("cp.async.bulk.commit_group;" ::: "memory");
      asm volatile("cp.async.bulk.wait_group.read 0;" ::: "memory");
      if (threadIdx.x == 0) { PROF_T(2, 12); PROF_G(2, 31); }
    }
  }
}

typedef CUresult (*EncodeFn)(CUtensorMap*, CUtensorMapDataType, cuuint32_t, void*, const cuuint64_t*, const cuuint64_t*,
                             const cuuint32_t*, const cuuint32_t*, CUtensorMapInterleave, CUtensorMapSwizzle,
                             CUtensorMapL2promotion, CUtensorMapFloatOOBfill);

void make_map(EncodeFn enc, CUtensorMap* m, const void* ptr, uint64_t inner, uint64_t outer, uint32_t box_inner, uint32_t box_outer) {
  cuuint64_t dims[2] = {inner, outer};
  cuuint64_t strides[1] = {inner * 2};
  cuuint32_t box[2] = {box_inner, box_outer};
  cuuint32_t es[2] = {1, 1};
  enc(m, CU_TENSOR_MAP_DATA_TYPE_BFLOAT16, 2, const_cast<void*>(ptr), dims, strides, box, es, CU_TENSOR_MAP_INTERLEAVE_NONE,
      CU_TENSOR_MAP_SWIZZLE_128B, CU_TENSOR_MAP_L2_PROMOTION_L2_256B, CU_TENSOR_MAP_FLOAT_OOB_FILL_NONE);
}

struct HostState {
  bool init;
  const void* key[7];
  CUtensorMap mxA, mxB, mwA, mwB, mo, mo16, mwoA, mwoB, mout;
};
HostState g_hs;

}

extern "C" void kernel_launch(void* const* d_in, const int* in_sizes, int n_in, void* d_out, int out_size) {
  (void)in_sizes; (void)n_in; (void)out_size;
  HostState& hs = g_hs;
  bool same = hs.init && hs.key[6] == d_out;
  for (int i = 0; i < 6 && same; i++) same = hs.key[i] == d_in[i];
  if (!same) {
    void* fn = nullptr;
    cudaDriverEntryPointQueryResult qr;
    cudaGetDriverEntryPoint("cuTensorMapEncodeTiled", &fn, cudaEnableDefault, &qr);
    EncodeFn enc = (EncodeFn)fn;
    void* go = nullptr;
    cudaGetSymbolAddress(&go, g_o);
    make_map(enc, &hs.mxA, d_in[0], 512, 2048, 64, 128);
    make_map(enc, &hs.mwA, d_in[1], 1536, 512, 64, 32);
    make_map(enc, &hs.mwoA, d_in[2], 512, 512, 64, 64);
    make_map(enc, &hs.mxB, d_in[3], 512, 2048, 64, 128);
    make_map(enc, &hs.mwB, d_in[4], 1536, 512, 64, 32);
    make_map(enc, &hs.mwoB, d_in[5], 512, 512, 64, 64);
    make_map(enc, &hs.mo, go, 512, 4096, 64, 128);
    make_map(enc, &hs.mo16, go, 512, 4096, 64, 16);
    make_map(enc, &hs.mout, d_out, 1024, 2048, 64, 64);
    cudaFuncSetAttribute(qkv_gemm_kernel, cudaFuncAttributeMaxDynamicSharedMemorySize, K1_SMEM);
    cudaFuncSetAttribute(attn_kernel, cudaFuncAttributeMaxDynamicSharedMemorySize, K2_SMEM);
    cudaFuncSetAttribute(out_gemm_kernel, cudaFuncAttributeMaxDynamicSharedMemorySize, K3_SMEM);
    for (int i = 0; i < 6; i++) hs.key[i] = d_in[i];
    hs.key[6] = d_out;
    hs.init = true;
  }
  cudaStream_t st = cudaStreamPerThread;
  {
    cudaLaunchConfig_t cfg = {};
    cfg.gridDim = dim3(128);
    cfg.blockDim = dim3(384);
    cfg.dynamicSmemBytes = K1_SMEM;
    cfg.stream = st;
    cudaLaunchAttribute at[1];
    at[0].id = cudaLaunchAttributeClusterDimension;
    at[0].val.clusterDim.x = 2;
    at[0].val.clusterDim.y = 1;
    at[0].val.clusterDim.z = 1;
    cfg.attrs = at;
    cfg.numAttrs = 1;
    cudaLaunchKernelEx(&cfg, qkv_gemm_kernel, hs.mxA, hs.mxB, hs.mwA, hs.mwB);
  }
  {
    cudaLaunchConfig_t cfg = {};
    cfg.gridDim = dim3(132);
    cfg.blockDim = dim3(512);
    cfg.dynamicSmemBytes = K2_SMEM;
    cfg.stream = st;
    cudaLaunchAttribute at[1];
    at[0].id = cudaLaunchAttributeProgrammaticStreamSerialization;
    at[0].val.programmaticStreamSerializationAllowed = 1;
    cfg.attrs = at;
    cfg.numAttrs = 1;
    cudaLaunchKernelEx(&cfg, attn_kernel, hs.mo16, (const uint8_t*)d_in[2], (const uint8_t*)d_in[5]);
    cfg.gridDim = dim3(128);
    cfg.blockDim = dim3(288);
    cfg.dynamicSmemBytes = K3_SMEM;
    cudaLaunchKernelEx(&cfg, out_gemm_kernel, hs.mo, hs.mwoA, hs.mwoB, hs.mout);
  }
}
```

```cpp
#include <cuda_runtime.h>
#include <cuda_bf16.h>
#include <cuda.h>
#include <stdint.h>

namespace {

constexpr int S_LEN = 2048;
constexpr int DM = 512;
constexpr int NH = 32;

constexpr int KV_K_BYTES = 65536;
constexpr int KV_HEAD_BYTES = KV_K_BYTES + 98304;
__device__ uint4 g_qfrag[2 * NH * 32 * 128];
__device__ uint4 g_kv[NH * KV_HEAD_BYTES / 16];
__device__ float g_kvpart[16 * NH * 384];
__device__ float g_nrm[NH * 16 * 4];
__device__ __nv_bfloat16 g_o[2 * S_LEN * DM];

#define g_prof_set(k, i, v)
#define g_prof_dummy(i) true
#define PROF_T(k, i) do {} while (0)
#define PROF_G(k, i) do {} while (0)
__device__ __forceinline__ uint32_t smem_u32(const void* p) { return (uint32_t)__cvta_generic_to_shared(p); }
__device__ __forceinline__ void mbar_init(uint32_t bar, int cnt) {
  asm volatile("mbarrier.init.shared::cta.b64 [%0], %1;" ::"r"(bar), "r"(cnt) : "memory");
}
__device__ __forceinline__ void mbar_expect_tx(uint32_t bar, uint32_t bytes) {
  asm volatile("mbarrier.arrive.expect_tx.shared::cta.b64 _, [%0], %1;" ::"r"(bar), "r"(bytes) : "memory");
}
__device__ __forceinline__ void mbar_arrive(uint32_t bar) {
  asm volatile("mbarrier.arrive.shared::cta.b64 _, [%0];" ::"r"(bar) : "memory");
}
__device__ __forceinline__ void mbar_arrive_cluster(uint32_t bar, uint32_t cta) {
  asm volatile(
      "{\n.reg .b32 ra;\nmapa.shared::cluster.u32 ra, %0, %1;\n"
      "mbarrier.arrive.shared::cluster.b64 _, [ra];\n}" ::"r"(bar), "r"(cta) : "memory");
}
__device__ __forceinline__ void mbar_wait(uint32_t bar, uint32_t parity) {
  asm volatile(
      "{\n.reg .pred p;\n.reg .u32 n;\n"
      "mov.u32 n, 0;\n"
      "WAIT_LOOP:\n"
      "mbarrier.try_wait.parity.shared::cta.b64 p, [%0], %1, 0x400000;\n"
      "@p bra WAIT_DONE;\n"
      "add.u32 n, n, 1;\n"
      "setp.lt.u32 p, n, 4000000;\n"
      "@p bra WAIT_LOOP;\n"
      "trap;\n"
      "WAIT_DONE:\n}" ::"r"(bar), "r"(parity) : "memory");
}
__device__ __forceinline__ void fence_barrier_init() {
  asm volatile("fence.mbarrier_init.release.cluster;" ::: "memory");
}
__device__ __forceinline__ void fence_proxy_async() { asm volatile("fence.proxy.async.shared::cta;" ::: "memory"); }
__device__ __forceinline__ void cluster_sync_relaxed() {
  asm volatile("barrier.cluster.arrive.relaxed.aligned;\nbarrier.cluster.wait.aligned;" ::: "memory");
}
__device__ __forceinline__ void tma_load_2d(uint32_t dst, const CUtensorMap* m, int x, int y, uint32_t bar) {
  asm volatile(
      "cp.async.bulk.tensor.2d.shared::cluster.global.mbarrier::complete_tx::bytes [%0], [%1, {%3, %4}], [%2];" ::"r"(dst),
      "l"(m), "r"(bar), "r"(x), "r"(y)
      : "memory");
}
__device__ __forceinline__ void tma_load_2d_mc(uint32_t dst, const CUtensorMap* m, int x, int y, uint32_t bar, uint16_t mask) {
  asm volatile(
      "cp.async.bulk.tensor.2d.shared::cluster.global.mbarrier::complete_tx::bytes.multicast::cluster [%0], [%1, {%3, %4}], "
      "[%2], %5;" ::"r"(dst),
      "l"(m), "r"(bar), "r"(x), "r"(y), "h"(mask)
      : "memory");
}
__device__ __forceinline__ void tma_store_2d(const CUtensorMap* m, uint32_t src, int x, int y) {
  asm volatile("cp.async.bulk.tensor.2d.global.shared::cta.bulk_group [%0, {%2, %3}], [%1];" ::"l"(m), "r"(src), "r"(x),
               "r"(y)
               : "memory");
}
__device__ __forceinline__ void bulk_load(uint32_t dst, const void* src, uint32_t bytes, uint32_t bar) {
  asm volatile("cp.async.bulk.shared::cluster.global.mbarrier::complete_tx::bytes [%0], [%1], %2, [%3];" ::"r"(dst),
               "l"(src), "r"(bytes), "r"(bar)
               : "memory");
}
__device__ __forceinline__ void bulk_load_mc(uint32_t dst, const void* src, uint32_t bytes, uint32_t bar, uint16_t mask) {
  asm volatile("cp.async.bulk.shared::cluster.global.mbarrier::complete_tx::bytes.multicast::cluster [%0], [%1], %2, [%3], %4;" ::"r"(dst),
               "l"(src), "r"(bytes), "r"(bar), "h"(mask)
               : "memory");
}
__device__ __forceinline__ void pdl_launch_dependents() { asm volatile("griddepcontrol.launch_dependents;" ::: "memory"); }
__device__ __forceinline__ void pdl_wait() { asm volatile("griddepcontrol.wait;" ::: "memory"); }
__device__ __forceinline__ void wg_fence() { asm volatile("wgmma.fence.sync.aligned;" ::: "memory"); }
__device__ __forceinline__ void wg_commit() { asm volatile("wgmma.commit_group.sync.aligned;" ::: "memory"); }
template <int N>
__device__ __forceinline__ void wg_wait() {
  asm volatile("wgmma.wait_group.sync.aligned %0;" ::"n"(N) : "memory");
}
template <int M>
__device__ __forceinline__ void fence_regs(float (&r)[M]) {
#pragma unroll
  for (int i = 0; i < M; i++) asm volatile("" : "+f"(r[i])::"memory");
}
__device__ __forceinline__ uint64_t mkdesc(uint32_t addr, uint32_t lbo, uint32_t sbo, uint32_t layout) {
  return (uint64_t)((addr & 0x3FFFF) >> 4) | ((uint64_t)(lbo >> 4) << 16) | ((uint64_t)(sbo >> 4) << 32) |
         ((uint64_t)layout << 62);
}
__device__ __forceinline__ uint32_t pack_bf16(float lo, float hi) {
  uint32_t r;
  asm("cvt.rn.bf16x2.f32 %0, %1, %2;" : "=r"(r) : "f"(hi), "f"(lo));
  return r;
}
__device__ __forceinline__ float bf_lo(uint32_t v) { return __uint_as_float(v << 16); }
__device__ __forceinline__ float bf_hi(uint32_t v) { return __uint_as_float(v & 0xFFFF0000u); }
__device__ __forceinline__ float round_bf16(float x) { return bf_lo(pack_bf16(x, 0.f)); }
__device__ __forceinline__ float ex2f(float x) {
  float y;
  asm("ex2.approx.ftz.f32 %0, %1;" : "=f"(y) : "f"(x));
  return y;
}

__device__ __forceinline__ void wgmma_rs_n24_tb(float (&d)[12], uint32_t a0, uint32_t a1, uint32_t a2, uint32_t a3, uint64_t descB, int scaleD) {
  asm volatile("{\n.reg .pred p;\nsetp.ne.b32 p, %17, 0;\n"
    "wgmma.mma_async.sync.aligned.m64n24k16.f32.bf16.bf16 "
    "{%0, %1, %2, %3, %4, %5, %6, %7, %8, %9, %10, %11}, {%12, %13, %14, %15}, %16, p, 1, 1, 1;\n}\n"
    : "+f"(d[0]), "+f"(d[1]), "+f"(d[2]), "+f"(d[3]), "+f"(d[4]), "+f"(d[5]), "+f"(d[6]), "+f"(d[7]),
      "+f"(d[8]), "+f"(d[9]), "+f"(d[10]), "+f"(d[11])
    : "r"(a0), "r"(a1), "r"(a2), "r"(a3), "l"(descB), "r"(scaleD));
}
__device__ __forceinline__ void wgmma_rs_n64_z(float (&d)[32], uint32_t a0, uint32_t a1, uint32_t a2, uint32_t a3, uint64_t descB) {
  asm volatile("{\n.reg .pred p;\nsetp.ne.b32 p, %37, 0;\n"
    "wgmma.mma_async.sync.aligned.m64n64k16.f32.bf16.bf16 "
    "{%0, %1, %2, %3, %4, %5, %6, %7, %8, %9, %10, %11, %12, %13, %14, %15, %16, %17, %18, %19, %20, %21, %22, %23, %24, %25, %26, %27, %28, %29, %30, %31}, {%32, %33, %34, %35}, %36, p, 1, 1, 0;\n}\n"
    : "=f"(d[0]), "=f"(d[1]), "=f"(d[2]), "=f"(d[3]), "=f"(d[4]), "=f"(d[5]), "=f"(d[6]), "=f"(d[7]),
      "=f"(d[8]), "=f"(d[9]), "=f"(d[10]), "=f"(d[11]), "=f"(d[12]), "=f"(d[13]), "=f"(d[14]), "=f"(d[15]),
      "=f"(d[16]), "=f"(d[17]), "=f"(d[18]), "=f"(d[19]), "=f"(d[20]), "=f"(d[21]), "=f"(d[22]), "=f"(d[23]),
      "=f"(d[24]), "=f"(d[25]), "=f"(d[26]), "=f"(d[27]), "=f"(d[28]), "=f"(d[29]), "=f"(d[30]), "=f"(d[31])
    : "r"(a0), "r"(a1), "r"(a2), "r"(a3), "l"(descB), "n"(0));
}
__device__ __forceinline__ void wgmma_ss_n128_tb(float (&d)[64], uint64_t descA, uint64_t descB, int scaleD) {
  asm volatile("{\n.reg .pred p;\nsetp.ne.b32 p, %66, 0;\n"
    "wgmma.mma_async.sync.aligned.m64n128k16.f32.bf16.bf16 "
    "{%0, %1, %2, %3, %4, %5, %6, %7, %8, %9, %10, %11, %12, %13, %14, %15, %16, %17, %18, %19, %20, %21, %22, %23, %24, %25, %26, %27, %28, %29, %30, %31, %32, %33, %34, %35, %36, %37, %38, %39, %40, %41, %42, %43, %44, %45, %46, %47, %48, %49, %50, %51, %52, %53, %54, %55, %56, %57, %58, %59, %60, %61, %62, %63}, %64, %65, p, 1, 1, 0, 1;\n}\n"
    : "+f"(d[0]), "+f"(d[1]), "+f"(d[2]), "+f"(d[3]), "+f"(d[4]), "+f"(d[5]), "+f"(d[6]), "+f"(d[7]),
      "+f"(d[8]), "+f"(d[9]), "+f"(d[10]), "+f"(d[11]), "+f"(d[12]), "+f"(d[13]), "+f"(d[14]), "+f"(d[15]),
      "+f"(d[16]), "+f"(d[17]), "+f"(d[18]), "+f"(d[19]), "+f"(d[20]), "+f"(d[21]), "+f"(d[22]), "+f"(d[23]),
      "+f"(d[24]), "+f"(d[25]), "+f"(d[26]), "+f"(d[27]), "+f"(d[28]), "+f"(d[29]), "+f"(d[30]), "+f"(d[31]),
      "+f"(d[32]), "+f"(d[33]), "+f"(d[34]), "+f"(d[35]), "+f"(d[36]), "+f"(d[37]), "+f"(d[38]), "+f"(d[39]),
      "+f"(d[40]), "+f"(d[41]), "+f"(d[42]), "+f"(d[43]), "+f"(d[44]), "+f"(d[45]), "+f"(d[46]), "+f"(d[47]),
      "+f"(d[48]), "+f"(d[49]), "+f"(d[50]), "+f"(d[51]), "+f"(d[52]), "+f"(d[53]), "+f"(d[54]), "+f"(d[55]),
      "+f"(d[56]), "+f"(d[57]), "+f"(d[58]), "+f"(d[59]), "+f"(d[60]), "+f"(d[61]), "+f"(d[62]), "+f"(d[63])
    : "l"(descA), "l"(descB), "r"(scaleD));
}
__device__ __forceinline__ void wgmma_ss_n192_tb(float (&d)[96], uint64_t descA, uint64_t descB, int scaleD) {
  asm volatile("{\n.reg .pred p;\nsetp.ne.b32 p, %98, 0;\n"
    "wgmma.mma_async.sync.aligned.m64n192k16.f32.bf16.bf16 "
    "{%0, %1, %2, %3, %4, %5, %6, %7, %8, %9, %10, %11, %12, %13, %14, %15, %16, %17, %18, %19, %20, %21, %22, %23, %24, %25, %26, %27, %28, %29, %30, %31, %32, %33, %34, %35, %36, %37, %38, %39, %40, %41, %42, %43, %44, %45, %46, %47, %48, %49, %50, %51, %52, %53, %54, %55, %56, %57, %58, %59, %60, %61, %62, %63, %64, %65, %66, %67, %68, %69, %70, %71, %72, %73, %74, %75, %76, %77, %78, %79, %80, %81, %82, %83, %84, %85, %86, %87, %88, %89, %90, %91, %92, %93, %94, %95}, %96, %97, p, 1, 1, 0, 1;\n}\n"
    : "+f"(d[0]), "+f"(d[1]), "+f"(d[2]), "+f"(d[3]), "+f"(d[4]), "+f"(d[5]), "+f"(d[6]), "+f"(d[7]),
      "+f"(d[8]), "+f"(d[9]), "+f"(d[10]), "+f"(d[11]), "+f"(d[12]), "+f"(d[13]), "+f"(d[14]), "+f"(d[15]),
      "+f"(d[16]), "+f"(d[17]), "+f"(d[18]), "+f"(d[19]), "+f"(d[20]), "+f"(d[21]), "+f"(d[22]), "+f"(d[23]),
      "+f"(d[24]), "+f"(d[25]), "+f"(d[26]), "+f"(d[27]), "+f"(d[28]), "+f"(d[29]), "+f"(d[30]), "+f"(d[31]),
      "+f"(d[32]), "+f"(d[33]), "+f"(d[34]), "+f"(d[35]), "+f"(d[36]), "+f"(d[37]), "+f"(d[38]), "+f"(d[39]),
      "+f"(d[40]), "+f"(d[41]), "+f"(d[42]), "+f"(d[43]), "+f"(d[44]), "+f"(d[45]), "+f"(d[46]), "+f"(d[47]),
      "+f"(d[48]), "+f"(d[49]), "+f"(d[50]), "+f"(d[51]), "+f"(d[52]), "+f"(d[53]), "+f"(d[54]), "+f"(d[55]),
      "+f"(d[56]), "+f"(d[57]), "+f"(d[58]), "+f"(d[59]), "+f"(d[60]), "+f"(d[61]), "+f"(d[62]), "+f"(d[63]),
      "+f"(d[64]), "+f"(d[65]), "+f"(d[66]), "+f"(d[67]), "+f"(d[68]), "+f"(d[69]), "+f"(d[70]), "+f"(d[71]),
      "+f"(d[72]), "+f"(d[73]), "+f"(d[74]), "+f"(d[75]), "+f"(d[76]), "+f"(d[77]), "+f"(d[78]), "+f"(d[79]),
      "+f"(d[80]), "+f"(d[81]), "+f"(d[82]), "+f"(d[83]), "+f"(d[84]), "+f"(d[85]), "+f"(d[86]), "+f"(d[87]),
      "+f"(d[88]), "+f"(d[89]), "+f"(d[90]), "+f"(d[91]), "+f"(d[92]), "+f"(d[93]), "+f"(d[94]), "+f"(d[95])
    : "l"(descA), "l"(descB), "r"(scaleD));
}

__device__ __forceinline__ void ldsm4t(uint32_t (&b)[4], uint32_t addr) {
  asm volatile("ldmatrix.sync.aligned.m8n8.x4.trans.shared.b16 {%0,%1,%2,%3}, [%4];"
               : "=r"(b[0]), "=r"(b[1]), "=r"(b[2]), "=r"(b[3])
               : "r"(addr));
}
__device__ __forceinline__ void hmma(float (&c)[4], uint32_t a0, uint32_t a1, uint32_t a2, uint32_t a3, uint32_t b0, uint32_t b1) {
  asm("mma.sync.aligned.m16n8k16.row.col.f32.bf16.bf16.f32 {%0,%1,%2,%3}, {%4,%5,%6,%7}, {%8,%9}, {%0,%1,%2,%3};"
      : "+f"(c[0]), "+f"(c[1]), "+f"(c[2]), "+f"(c[3])
      : "r"(a0), "r"(a1), "r"(a2), "r"(a3), "r"(b0), "r"(b1));
}

__device__ __forceinline__ uint32_t movm(uint32_t a) {
  uint32_t d;
  asm volatile("movmatrix.sync.aligned.m8n8.trans.b16 %0, %1;" : "=r"(d) : "r"(a));
  return d;
}

#define K1_WARM 0
constexpr int K1_STAGES = 4;
constexpr int K1_W_BYTES = 3 * 8192;
constexpr int K1_X_BYTES = 8 * 16384;
constexpr int K1_BAR_OFF = K1_X_BYTES + K1_STAGES * K1_W_BYTES;
constexpr int K1_SMEM = K1_BAR_OFF + 192 + 1024;
constexpr float QSCALE = 0.25f * 1.4426950408889634f;

__device__ __forceinline__ uint32_t phi2(uint32_t t2) {
  uint32_t a2, mask, r2, o2;
  asm("add.rn.bf16x2 %0, %1, %2;" : "=r"(a2) : "r"(t2), "r"(0x3F803F80u));
  const uint32_t e2 = pack_bf16(ex2f(bf_lo(t2) * 1.4426950408889634f), ex2f(bf_hi(t2) * 1.4426950408889634f));
  asm("set.gt.u32.bf16x2 %0, %1, %2;" : "=r"(mask) : "r"(t2), "r"(0u));
  r2 = (a2 & mask) | (e2 & ~mask);
  asm("add.rn.bf16x2 %0, %1, %2;" : "=r"(o2) : "r"(r2), "r"(0x35863586u));
  return o2;
}

#define K1_SLOT_KB(h) ((h) < 4 ? 2 * (h) : 2 * ((h) - 4) + 1)
struct EpiCtx {
  uint4* qf;
  uint32_t* kp;
  uint32_t* vp;
  uint32_t s_red_addr;
  float* red;
  int lane;
};

template <bool LINEAR, int HH, int PART>
__device__ __forceinline__ void epi_slice(const float (&acc)[96], const EpiCtx& c, uint32_t (&pk)[4], float& vmax, bool live) {
  const float* a = &acc[HH * 8];
  const float* k = &acc[32 + HH * 8];
  const float* v = &acc[64 + HH * 8];
  if (!LINEAR) {
    if (PART == 0) {
      uint32_t* kh = c.kp + HH * (KV_HEAD_BYTES / 4);
      if (live) {
        c.qf[HH * 32 * 128] = make_uint4(pack_bf16(a[0], a[1]), pack_bf16(a[2], a[3]), pack_bf16(a[4], a[5]), pack_bf16(a[6], a[7]));
        kh[0] = pack_bf16(k[0], k[1]);
        kh[64] = pack_bf16(k[2], k[3]);
        kh[32] = pack_bf16(k[4], k[5]);
        kh[96] = pack_bf16(k[6], k[7]);
      }
      float q0 = a[0] * a[0] + a[1] * a[1] + a[4] * a[4] + a[5] * a[5];
      float q1 = a[2] * a[2] + a[3] * a[3] + a[6] * a[6] + a[7] * a[7];
      float k0 = k[0] * k[0] + k[1] * k[1] + k[4] * k[4] + k[5] * k[5];
      float k1 = k[2] * k[2] + k[3] * k[3] + k[6] * k[6] + k[7] * k[7];
#pragma unroll
      for (int o = 1; o <= 2; o <<= 1) {
        q0 += __shfl_xor_sync(0xffffffffu, q0, o);
        q1 += __shfl_xor_sync(0xffffffffu, q1, o);
        k0 += __shfl_xor_sync(0xffffffffu, k0, o);
        k1 += __shfl_xor_sync(0xffffffffu, k1, o);
      }
      const uint32_t qm = __reduce_max_sync(0xffffffffu, max(__float_as_uint(q0) & 0x7FFFFFFFu, __float_as_uint(q1) & 0x7FFFFFFFu));
      const uint32_t km = __reduce_max_sync(0xffffffffu, max(__float_as_uint(k0) & 0x7FFFFFFFu, __float_as_uint(k1) & 0x7FFFFFFFu));
      asm volatile(
          "{\n.reg .pred p;\nsetp.ne.b32 p, %3, 0;\n"
          "@p red.shared.max.u32 [%0], %1;\n@p red.shared.max.u32 [%0+4], %2;\n}" ::"r"(c.s_red_addr + HH * 8),
          "r"(qm), "r"(km), "r"((c.lane == 0 && live) ? 1 : 0)
          : "memory");
    } else {
      uint32_t* vh = c.vp + HH * (KV_HEAD_BYTES / 4);
      if (live) {
        vh[0] = pack_bf16(v[0], v[1]);
        vh[96] = pack_bf16(v[2], v[3]);
        vh[32] = pack_bf16(v[4], v[5]);
        vh[128] = pack_bf16(v[6], v[7]);
        vh[64] = 0x3F803F80u;
        vh[160] = 0x3F803F80u;
      }
#pragma unroll
      for (int i = 0; i < 8; i++) asm("max.NaN.f32 %0, %0, %1;" : "+f"(vmax) : "f"(fabsf(v[i])));
    }
  } else {
    if (PART == 0) {
      const uint4 pq = make_uint4(phi2(pack_bf16(a[0], a[1])), phi2(pack_bf16(a[2], a[3])), phi2(pack_bf16(a[4], a[5])),
                                  phi2(pack_bf16(a[6], a[7])));
      if (live) c.qf[HH * 32 * 128] = pq;
      pk[0] = movm(phi2(pack_bf16(k[0], k[1])));
      pk[2] = movm(phi2(pack_bf16(k[2], k[3])));
      pk[1] = movm(phi2(pack_bf16(k[4], k[5])));
      pk[3] = movm(phi2(pack_bf16(k[6], k[7])));
    } else {
      const uint32_t b0 = movm(pack_bf16(v[0], v[1]));
      const uint32_t b1 = movm(pack_bf16(v[2], v[3]));
      const uint32_t b2 = movm(pack_bf16(v[4], v[5]));
      const uint32_t b3 = movm(pack_bf16(v[6], v[7]));
      float c0[4] = {0, 0, 0, 0}, c1[4] = {0, 0, 0, 0}, c2[4] = {0, 0, 0, 0};
      hmma(c0, pk[0], pk[1], pk[2], pk[3], b0, b1);
      hmma(c1, pk[0], pk[1], pk[2], pk[3], b2, b3);
      hmma(c2, pk[0], pk[1], pk[2], pk[3], 0x3F803F80u, 0x3F803F80u);
      float* slot = c.red + HH * 2 * 4096;
      if (live) {
#pragma unroll
        for (int i = 0; i < 4; i++) {
          slot[i * 32] = c0[i];
          slot[(4 + i) * 32] = c1[i];
          slot[(8 + i) * 32] = c2[i];
        }
      }
    }
  }
}

template <bool LINEAR>
__device__ __forceinline__ void qkv_consumer(uint32_t sbase, uint8_t* smem_gen, uint32_t* s_red, int cp, int rt) {
  const uint32_t bar_full = sbase + K1_BAR_OFF;
  const uint32_t bar_empty = bar_full + 8 * K1_STAGES;
  const int warp = threadIdx.x >> 5;
  const int wg = warp >> 2;
  const int lane = threadIdx.x & 31;
  float accN[96], accP[96];
  EpiCtx c;
  {
    const int row0 = rt * 128 + wg * 64 + (warp & 3) * 16;
    c.qf = g_qfrag + ((size_t)((LINEAR ? NH : 0) + cp * 8) * 32 + (rt * 2 + wg)) * 128 + (threadIdx.x & 127);
    uint32_t* img = reinterpret_cast<uint32_t*>(reinterpret_cast<uint8_t*>(g_kv) + (size_t)(cp * 8) * KV_HEAD_BYTES);
    c.kp = img + (row0 >> 3) * 64 + lane;
    c.vp = img + KV_K_BYTES / 4 + (row0 >> 3) * 96 + lane;
    c.s_red_addr = smem_u32(s_red);
    c.red = reinterpret_cast<float*>(smem_gen + wg * 8192) + (warp & 3) * 384 + lane;
    c.lane = lane;
  }
  uint32_t pk[4] = {0, 0, 0, 0};
  float vmax = 0.f;
#pragma unroll
  for (int i = 0; i < 96; i++) asm volatile("mov.f32 %0, 0f00000000;" : "=f"(accN[i]));
  int npass;
  asm volatile("mov.u32 %0, 2;" : "=r"(npass));
#pragma unroll 1
  for (int pass = K1_WARM ? 0 : 1; pass < npass; pass++) {
    const bool live = K1_WARM ? pass != 0 : true;
    if (live) {
#pragma unroll 1
      for (int kb = 0; kb < 8; kb++) {
        const int s = kb % K1_STAGES;
        mbar_wait(bar_full + 8 * s, (kb / K1_STAGES) & 1);
        if (threadIdx.x == 0) PROF_T(0, 2 + (kb >> 1));
        const uint64_t dA = mkdesc(sbase + kb * 16384 + wg * 8192, 16, 1024, 1);
        const uint64_t dB = mkdesc(sbase + K1_X_BYTES + s * K1_W_BYTES, 8192, 1024, 1);
        wg_fence();
#pragma unroll
        for (int k = 0; k < 4; k++) wgmma_ss_n192_tb(accP, dA + k * 2, dB + k * 128, (kb | k) != 0);
        wg_commit();
        if (kb > 0) {
          wg_wait<1>();
          if ((threadIdx.x & 127) == 0) {
            const int sp = (kb - 1) % K1_STAGES;
            mbar_arrive_cluster(bar_empty + 8 * sp, 0);
            mbar_arrive_cluster(bar_empty + 8 * sp, 1);
          }
        }
      }
      wg_wait<0>();
      fence_regs(accP);
      if ((threadIdx.x & 127) == 0) {
        mbar_arrive_cluster(bar_empty + 8 * (7 % K1_STAGES), 0);
        mbar_arrive_cluster(bar_empty + 8 * (7 % K1_STAGES), 1);
      }
      if (threadIdx.x == 0) PROF_T(0, 6);
#define K1_T1_STEP(KB)                                                                           \
  {                                                                                              \
    constexpr int g = 8 + KB;                                                                    \
    constexpr int s = g % K1_STAGES;                                                             \
    mbar_wait(bar_full + 8 * s, (g / K1_STAGES) & 1);                                            \
    const uint64_t dA = mkdesc(sbase + KB * 16384 + wg * 8192, 16, 1024, 1);                     \
    const uint64_t dB = mkdesc(sbase + K1_X_BYTES + s * K1_W_BYTES, 8192, 1024, 1);              \
    wg_fence();                                                                                  \
    _Pragma("unroll") for (int k = 0; k < 4; k++) wgmma_ss_n192_tb(accN, dA + k * 2, dB + k * 128, (KB | k) != 0); \
    wg_commit();                                                                                 \
    epi_slice<LINEAR, KB / 2, KB & 1>(accP, c, pk, vmax, true);                                  \
    wg_wait<0>();                                                                                \
    if (KB + K1_STAGES < 8 && (threadIdx.x & 127) == 0) {                                        \
      mbar_arrive_cluster(bar_empty + 8 * s, 0);                                                 \
      mbar_arrive_cluster(bar_empty + 8 * s, 1);                                                 \
    }                                                                                            \
  }
      K1_T1_STEP(0) K1_T1_STEP(1) K1_T1_STEP(2) K1_T1_STEP(3) K1_T1_STEP(4) K1_T1_STEP(5) K1_T1_STEP(6) K1_T1_STEP(7)
#undef K1_T1_STEP
      fence_regs(accN);
      if (threadIdx.x == 0) PROF_T(0, 10);
      c.qf += 4 * 32 * 128;
      c.kp += 4 * (KV_HEAD_BYTES / 4);
      c.vp += 4 * (KV_HEAD_BYTES / 4);
      c.s_red_addr += 32;
      c.red += 4096;
    }
    float vm1 = 0.f;
    epi_slice<LINEAR, 0, 0>(accN, c, pk, vm1, live);
    epi_slice<LINEAR, 0, 1>(accN, c, pk, vm1, live);
    epi_slice<LINEAR, 1, 0>(accN, c, pk, vm1, live);
    epi_slice<LINEAR, 1, 1>(accN, c, pk, vm1, live);
    epi_slice<LINEAR, 2, 0>(accN, c, pk, vm1, live);
    epi_slice<LINEAR, 2, 1>(accN, c, pk, vm1, live);
    epi_slice<LINEAR, 3, 0>(accN, c, pk, vm1, live);
    epi_slice<LINEAR, 3, 1>(accN, c, pk, vm1, live);
    if (live) asm("max.NaN.f32 %0, %0, %1;" : "+f"(vmax) : "f"(vm1));
  }
  if (!LINEAR) {
    const uint32_t vm = __reduce_max_sync(0xffffffffu, __float_as_uint(vmax) & 0x7FFFFFFFu);
    if (lane == 0) atomicMax(&s_red[16], vm);
    asm volatile("bar.sync 1, 256;" ::: "memory");
    if (threadIdx.x < 8) {
      *reinterpret_cast<float4*>(&g_nrm[((cp * 8 + threadIdx.x) * 16 + rt) * 4]) =
          make_float4(__uint_as_float(s_red[threadIdx.x * 2]), __uint_as_float(s_red[threadIdx.x * 2 + 1]), __uint_as_float(s_red[16]), 0.f);
    }
  } else {
    asm volatile("bar.sync 1, 256;" ::: "memory");
    float* dst = g_kvpart + ((size_t)rt * NH + cp * 8) * 384 + threadIdx.x;
    const float* base = reinterpret_cast<const float*>(smem_gen);
#pragma unroll
    for (int i = 0; i < 12; i++) {
      const int h0 = (i / 3) * 2, r = i % 3;
      const bool second = r == 2 || (r == 1 && threadIdx.x >= 128);
      const int e = (int)threadIdx.x + r * 256 - (second ? 384 : 0);
      const float* src = base + (second ? K1_SLOT_KB(h0 + 1) : K1_SLOT_KB(h0)) * 4096 + e;
      float sum = 0.f;
#pragma unroll
      for (int w = 0; w < 8; w++) sum += src[(w >> 2) * 2048 + (w & 3) * 384];
      dst[i * 256] = sum;
    }
  }
}

__global__ void __launch_bounds__(384, 1)
qkv_gemm_kernel(const __grid_constant__ CUtensorMap mxA, const __grid_constant__ CUtensorMap mxB,
                const __grid_constant__ CUtensorMap mwA, const __grid_constant__ CUtensorMap mwB) {
  extern __shared__ uint8_t smem_raw[];
  const uint32_t sbase = (smem_u32(smem_raw) + 1023) & ~1023u;
  uint8_t* smem_gen = smem_raw + (sbase - smem_u32(smem_raw));
  const uint32_t bar_full = sbase + K1_BAR_OFF;
  const uint32_t bar_empty = bar_full + 8 * K1_STAGES;
  uint32_t* s_red = reinterpret_cast<uint32_t*>(smem_gen + K1_BAR_OFF + 64);

  const int rank = blockIdx.x & 1;
  const int pair = blockIdx.x >> 1;
  const int branch = pair >> 5;
  const int rp = (pair & 31) >> 2;
  const int cp = pair & 3;
  const int rt = rp * 2 + rank;
  const int warp = threadIdx.x >> 5;
  if (threadIdx.x == 0) { PROF_G(0, 30); PROF_T(0, 0); }
  const CUtensorMap* mx = branch ? &mxA : &mxB;
  const CUtensorMap* mw = branch ? &mwA : &mwB;

  if (threadIdx.x == 256) {
    asm volatile("prefetch.tensormap [%0];" ::"l"(mx) : "memory");
    asm volatile("prefetch.tensormap [%0];" ::"l"(mw) : "memory");
    for (int i = 0; i < K1_STAGES; i++) {
      mbar_init(bar_full + 8 * i, 1);
      mbar_init(bar_empty + 8 * i, 4);
    }
    fence_barrier_init();
    fence_proxy_async();
    for (int kb = 0; kb < K1_STAGES; kb++) mbar_expect_tx(bar_full + 8 * kb, 16384 + K1_W_BYTES);
    tma_load_2d(sbase, mx, 0, rt * 128, bar_full);
  }
  pdl_launch_dependents();
  if (threadIdx.x < 32) s_red[threadIdx.x] = 0;
  __syncthreads();
  cluster_sync_relaxed();
  if (threadIdx.x == 0) PROF_T(0, 1);

  if (warp >= 8) {
    asm volatile("setmaxnreg.dec.sync.aligned.u32 40;");
    if (threadIdx.x == 256) {
      for (int g = 0; g < 16; g++) {
        const int s = g % K1_STAGES;
        const int kb = g & 7;
        if (g >= K1_STAGES) {
          mbar_wait(bar_empty + 8 * s, ((g / K1_STAGES) - 1) & 1);
          mbar_expect_tx(bar_full + 8 * s, (g < 8 ? 16384 : 0) + K1_W_BYTES);
        }
        if (g > 0 && g < 8) tma_load_2d(sbase + kb * 16384, mx, kb * 64, rt * 128, bar_full + 8 * s);
        const int h0 = cp * 8 + (g >> 3) * 4;
        const uint32_t st = sbase + K1_X_BYTES + s * K1_W_BYTES + rank * 4096;
#pragma unroll
        for (int p = 0; p < 3; p++)
          tma_load_2d_mc(st + p * 8192, mw, p * 512 + h0 * 16, kb * 64 + rank * 32, bar_full + 8 * s, (uint16_t)3);
      }
    }
    __syncwarp();
    cluster_sync_relaxed();
  } else {
    asm volatile("setmaxnreg.inc.sync.aligned.u32 232;");
    if (branch == 0) qkv_consumer<false>(sbase, smem_gen, s_red, cp, rt);
    else qkv_consumer<true>(sbase, smem_gen, s_red, cp, rt);
    if (threadIdx.x == 0) PROF_T(0, 11);
    __syncwarp();
    cluster_sync_relaxed();
    if (threadIdx.x == 0) { PROF_T(0, 12); PROF_G(0, 31); }
  }
}

constexpr int K2_SMEM = KV_HEAD_BYTES + 1024 + 256;

#define ATT_NPOLY 19
#define ATT_CH 8
#define ATT_D 1
#define PRO_MODE 1
#define STAGGER 0
#define K2_G0_CPASYNC 1
#define CONST_SMID 0
#define ATT_STRUCT 1
#define ATT_PIN 0
#define ATT_GM 1
#define ATT_DEG 2
struct ExpC {
  uint32_t k3c00, kmask, seven, c3;
};
__device__ __forceinline__ uint32_t hfma2(uint32_t a, uint32_t b, uint32_t c) {
  uint32_t r;
  asm("fma.rn.f16x2 %0, %1, %2, %3;" : "=r"(r) : "r"(a), "r"(b), "r"(c));
  return r;
}
__device__ __forceinline__ uint32_t exp2_poly_pair(float t0, float t1, const ExpC& c) {
  uint32_t u;
  asm("prmt.b32 %0, %1, %2, 0x5410;" : "=r"(u) : "r"(__float_as_uint(t0)), "r"(__float_as_uint(t1)));
  uint32_t m;
  asm("lop3.b32 %0, %1, 0x03FF03FF, %2, 0xEA;" : "=r"(m) : "r"(u), "r"(c.k3c00));
  uint32_t p = hfma2(m, c.c3, 0xa385a385u);
  p = hfma2(p, m, 0x4ad64ad7u);
  uint32_t mu;
  asm("lop3.b32 %0, %1, 0xFC00FC00, %2, 0xEA;" : "=r"(mu) : "r"(u), "r"(c.kmask));
  uint32_t r;
  asm("{.reg .b32 t; shf.r.wrap.b32 t, %1, %2, 3; add.u32 %0, t, %3;}" : "=r"(r) : "r"(mu), "r"(c.seven), "r"(p));
  return r;
}
__device__ __forceinline__ float gadd(float x, float M, uint32_t g) {
  float r = x;
  asm("{.reg .pred p; setp.ne.b32 p, %2, -1; @p add.f32 %0, %0, %1;}" : "+f"(r) : "f"(M), "r"(g));
  return r;
}
__device__ __forceinline__ float gex2(float x, uint32_t g) {
  float r = x;
  asm("{.reg .pred p; setp.ne.b32 p, %1, -1; @p ex2.approx.ftz.f32 %0, %0;}" : "+f"(r) : "r"(g));
  return r;
}
#define ATT_PAT 0
__host__ __device__ constexpr bool is_poly(int i, int npoly) {
  return ATT_PAT == 0   ? ((i + 1) * npoly / 32) != (i * npoly / 32)
         : ATT_PAT == 1 ? ((32 - i) * npoly / 32) != ((31 - i) * npoly / 32)
         : ATT_PAT == 2 ? ((i & 7) >= 8 - (((i / 8 + 1) * 8) * npoly / 32 - ((i / 8) * 8) * npoly / 32))
                        : ((i & 7) < (((i / 8 + 1) * 8) * npoly / 32 - ((i / 8) * 8) * npoly / 32));
}
template <int NPOLY, int NPAIR, int CH, int D, bool G0 = false>
__device__ __forceinline__ void exp_tile(const float (&s)[2 * NPAIR], uint32_t (&p)[NPAIR], const ExpC& c, uint32_t g0 = 0) {
#pragma unroll
  for (int i = 0; i < NPAIR; i++) {
    const bool isPoly = is_poly(i, NPOLY);
    const int ch = i / CH;
    const bool gated = ch >= D || G0;
    int gi = (ch - D) * CH + CH - 1;
    if (ch >= D) {
      while (gi > (ch - D) * CH && !is_poly(gi, NPOLY)) gi--;
    }
    const uint32_t g = ch >= D ? p[gi] : g0;
    if (!isPoly) {
      if (gated && ATT_GM) p[i] = pack_bf16(gex2(s[2 * i], g), gex2(s[2 * i + 1], g));
      else p[i] = pack_bf16(ex2f(s[2 * i]), ex2f(s[2 * i + 1]));
    } else {
      if (gated) p[i] = exp2_poly_pair(gadd(s[2 * i], 12329.f, g), gadd(s[2 * i + 1], 12329.f, g), c);
      else p[i] = exp2_poly_pair(s[2 * i] + 12329.f, s[2 * i + 1] + 12329.f, c);
    }
  }
}

__device__ __forceinline__ void store_o(__nv_bfloat16* o, int row0, int head, int lane, const uint32_t (&r)[4]) {
  const int g = lane >> 2, t = lane & 3;
  uint32_t* p0 = reinterpret_cast<uint32_t*>(o + (size_t)(row0 + g) * DM + head * 16) + t;
  uint32_t* p1 = reinterpret_cast<uint32_t*>(o + (size_t)(row0 + g + 8) * DM + head * 16) + t;
  p0[0] = r[0];
  p1[0] = r[1];
  p0[4] = r[2];
  p1[4] = r[3];
}

__device__ __forceinline__ void kv_fetch_piece(uint32_t sbase, uint32_t bar, int piece) {
  const uint8_t* img = reinterpret_cast<const uint8_t*>(g_kv) + (size_t)(blockIdx.x >> 2) * KV_HEAD_BYTES;
  const int g = piece >> 1, isv = piece & 1;
  const int e0 = g == 0 ? 0 : (isv ? 256 : 320) + (g - 1) * 512;
  const int e1 = g == 3 ? 2048 : (isv ? 256 : 320) + g * 512;
  const int bytes = (e1 - e0) * (isv ? 48 : 32);
  const int off = isv ? KV_K_BYTES + e0 * 48 : e0 * 32;
  mbar_expect_tx(bar + 8 * g, bytes);
  bulk_load(sbase + off, img + off, bytes, bar + 8 * g);
}

__device__ __forceinline__ void safe_exp(float (&s)[32], uint32_t (&p)[16], float (&o)[12], float& m0, float& m1) {
#pragma unroll
  for (int i = 0; i < 16; i++) {
    const uint32_t r = pack_bf16(s[2 * i], s[2 * i + 1]);
    s[2 * i] = bf_lo(r) * QSCALE;
    s[2 * i + 1] = bf_hi(r) * QSCALE;
  }
  float x0 = s[0], x1 = s[2];
#pragma unroll
  for (int i = 0; i < 8; i++) {
    x0 = fmaxf(x0, fmaxf(s[4 * i], s[4 * i + 1]));
    x1 = fmaxf(x1, fmaxf(s[4 * i + 2], s[4 * i + 3]));
  }
  x0 = fmaxf(x0, __shfl_xor_sync(0xffffffffu, x0, 1));
  x1 = fmaxf(x1, __shfl_xor_sync(0xffffffffu, x1, 1));
  x0 = fmaxf(x0, __shfl_xor_sync(0xffffffffu, x0, 2));
  x1 = fmaxf(x1, __shfl_xor_sync(0xffffffffu, x1, 2));
  const float n0 = fmaxf(m0, x0), n1 = fmaxf(m1, x1);
  const float c0 = ex2f(m0 - n0), c1 = ex2f(m1 - n1);
  m0 = n0;
  m1 = n1;
#pragma unroll
  for (int i = 0; i < 3; i++) {
    o[4 * i] *= c0;
    o[4 * i + 1] *= c0;
    o[4 * i + 2] *= c1;
    o[4 * i + 3] *= c1;
  }
#pragma unroll
  for (int i = 0; i < 8; i++) {
    p[2 * i] = pack_bf16(ex2f(s[4 * i] - n0), ex2f(s[4 * i + 1] - n0));
    p[2 * i + 1] = pack_bf16(ex2f(s[4 * i + 2] - n1), ex2f(s[4 * i + 3] - n1));
  }
}

__device__ __forceinline__ void attn_step(float (&sx)[32], float (&sy)[32], float (&o)[12], const uint4& qf, uint64_t dK, uint64_t dV,
                                          const ExpC& ec) {
  uint32_t pa[16], pb[16];
  wg_fence();
  wgmma_rs_n64_z(sy, qf.x, qf.y, qf.z, qf.w, dK + 128);
  wg_commit();
  exp_tile<ATT_NPOLY, 16, ATT_CH, ATT_D>(sx, pa, ec);
  wg_fence();
  wgmma_rs_n24_tb(o, pa[12], pa[13], pa[14], pa[15], dV + 3 * 48, 1);
  wg_commit();
  wg_wait<1>();
  fence_regs(sy);
  exp_tile<ATT_NPOLY, 16, ATT_CH, ATT_D>(sy, pb, ec);
  wg_fence();
#pragma unroll
  for (int k = 0; k < 3; k++) wgmma_rs_n24_tb(o, pa[4 * k], pa[4 * k + 1], pa[4 * k + 2], pa[4 * k + 3], dV + k * 48, 1);
#pragma unroll
  for (int k = 0; k < 4; k++) wgmma_rs_n24_tb(o, pb[4 * k], pb[4 * k + 1], pb[4 * k + 2], pb[4 * k + 3], dV + (4 + k) * 48, 1);
  wgmma_rs_n64_z(sy, qf.x, qf.y, qf.z, qf.w, dK + 256);
  wg_commit();
  wg_wait<0>();
  fence_regs(sy);
}

template <bool SAFE>
__device__ __forceinline__ void attn_tile(uint64_t dK, uint64_t dV, uint32_t bar, uint4 qf, const ExpC& ec, uint32_t (&outp)[4]) {
  float o[12];
#pragma unroll
  for (int i = 0; i < 12; i++) asm volatile("mov.f32 %0, 0f00000000;" : "=f"(o[i]));
  if (!SAFE) {
    qf.x = pack_bf16(bf_lo(qf.x) * QSCALE, bf_hi(qf.x) * QSCALE);
    qf.y = pack_bf16(bf_lo(qf.y) * QSCALE, bf_hi(qf.y) * QSCALE);
    qf.z = pack_bf16(bf_lo(qf.z) * QSCALE, bf_hi(qf.z) * QSCALE);
    qf.w = pack_bf16(bf_lo(qf.w) * QSCALE, bf_hi(qf.w) * QSCALE);
    float s0[32], s1[32];
    wg_fence();
    wgmma_rs_n64_z(s0, qf.x, qf.y, qf.z, qf.w, dK);
    wg_commit();
    wg_wait<0>();
    fence_regs(s0);
#pragma unroll 1
    for (int p = 0; p < 8; p++) {
      if (p & 1) mbar_wait(bar + 8 * min((p + 1) >> 1, 3), 0);
      attn_step(s0, s1, o, qf, dK, dV, ec);
      attn_step(s1, s0, o, qf, dK + 256, dV + 384, ec);
      dK += 512;
      dV += 768;
    }
  } else {
    float m0 = -INFINITY, m1 = -INFINITY;
#pragma unroll 1
    for (int j = 0; j < 32; j++) {
      if (j == 4) { mbar_wait(bar + 8, 0); mbar_wait(bar + 16, 0); mbar_wait(bar + 24, 0); }
      float s[32];
      uint32_t p[16];
      wg_fence();
      wgmma_rs_n64_z(s, qf.x, qf.y, qf.z, qf.w, dK);
      wg_commit();
      wg_wait<0>();
      fence_regs(s);
      safe_exp(s, p, o, m0, m1);
      wg_fence();
#pragma unroll
      for (int k = 0; k < 4; k++) wgmma_rs_n24_tb(o, p[4 * k], p[4 * k + 1], p[4 * k + 2], p[4 * k + 3], dV + k * 48, 1);
      wg_commit();
      wg_wait<0>();
      fence_regs(o);
      dK += 128;
      dV += 192;
    }
  }
  fence_regs(o);
  const float r0 = 1.0f / o[8], r1 = 1.0f / o[10];
  outp[0] = pack_bf16(o[0] * r0, o[1] * r0);
  outp[1] = pack_bf16(o[2] * r1, o[3] * r1);
  outp[2] = pack_bf16(o[4] * r0, o[5] * r0);
  outp[3] = pack_bf16(o[6] * r1, o[7] * r1);
}

__device__ __forceinline__ void linear_attn_cta(uint8_t* smem_raw, uint32_t sbase, const CUtensorMap* mo16, int cta) {
  const int warp = threadIdx.x >> 5, lane = threadIdx.x & 31;
  const int hg = warp & 1;
  const uint4* qp = g_qfrag + (size_t)(NH + cta * 8 + hg * 4) * 32 * 128 + lane;
  auto qaddr = [&](int i) {
    const int blk16 = i * 8 + (warp >> 1);
    return qp + (blk16 >> 2) * 128 + (blk16 & 3) * 32;
  };
  uint4 q[4];
#pragma unroll
  for (int h = 0; h < 4; h++) q[h] = qaddr(0)[h * 32 * 128];
  float* red = reinterpret_cast<float*>(smem_raw + (sbase - smem_u32(smem_raw)) + 131072);
  {
    const float* src = g_kvpart + (size_t)cta * 8 * 384;
    float sum[6];
#pragma unroll
    for (int i = 0; i < 6; i++) sum[i] = 0.f;
#pragma unroll
    for (int r = 0; r < 16; r++) {
#pragma unroll
      for (int i = 0; i < 6; i++) sum[i] += src[(size_t)r * NH * 384 + threadIdx.x + i * 512];
    }
#pragma unroll
    for (int i = 0; i < 6; i++) red[threadIdx.x + i * 512] = round_bf16(sum[i]);
  }
  __syncthreads();
  if (threadIdx.x == 0) PROF_T(1, 1);
  uint32_t bf[4][6];
  {
    const int g = lane >> 2, t = lane & 3;
#pragma unroll
    for (int h = 0; h < 4; h++) {
#pragma unroll
      for (int f = 0; f < 6; f++) {
        const int blk = f >> 1, half = f & 1;
        const int e = (blk == 2) ? 0 : g;
        const int d = 2 * t + 8 * half;
        const int base = (hg * 4 + h) * 384 + (blk * 4 + half * 2 + (e & 1)) * 32 + (e >> 1);
        bf[h][f] = pack_bf16(red[base + (d & 7) * 4], red[base + ((d + 1) & 7) * 4]);
      }
    }
  }
  if (threadIdx.x == 0) PROF_T(1, 2);
  const uint32_t stg = sbase + warp * 8192;
#pragma unroll 1
  for (int i = 0; i < 16; i++) {
    uint4 qc[4];
#pragma unroll
    for (int h = 0; h < 4; h++) qc[h] = q[h];
    if (i + 1 < 16) {
#pragma unroll
      for (int h = 0; h < 4; h++) q[h] = qaddr(i + 1)[h * 32 * 128];
    }
    const uint32_t buf = stg + (i & 3) * 2048;
    if (i >= 4) {
      if (lane == 0) asm volatile("cp.async.bulk.wait_group.read 3;" ::: "memory");
      __syncwarp();
    }
#pragma unroll
    for (int h = 0; h < 4; h++) {
      float n0[4] = {0, 0, 0, 0}, n1[4] = {0, 0, 0, 0}, dn[4] = {0, 0, 0, 0};
      hmma(n0, qc[h].x, qc[h].y, qc[h].z, qc[h].w, bf[h][0], bf[h][1]);
      hmma(n1, qc[h].x, qc[h].y, qc[h].z, qc[h].w, bf[h][2], bf[h][3]);
      hmma(dn, qc[h].x, qc[h].y, qc[h].z, qc[h].w, bf[h][4], bf[h][5]);
      const float d0 = __fdividef(1.0f, dn[0] + 1e-6f), d1 = __fdividef(1.0f, dn[2] + 1e-6f);
      const uint32_t r0 = pack_bf16(n0[0] * d0, n0[1] * d0);
      const uint32_t r1 = pack_bf16(n0[2] * d1, n0[3] * d1);
      const uint32_t r2 = pack_bf16(n1[0] * d0, n1[1] * d0);
      const uint32_t r3 = pack_bf16(n1[2] * d1, n1[3] * d1);
      const int row = lane & 15;
      const int chunk = h * 2 + (lane >> 4);
      const uint32_t addr = buf + row * 128 + ((chunk ^ (row & 7)) << 4);
      asm volatile("stmatrix.sync.aligned.m8n8.x4.shared.b16 [%0], {%1,%2,%3,%4};" ::"r"(addr), "r"(r0), "r"(r1), "r"(r2), "r"(r3)
                   : "memory");
    }
    fence_proxy_async();
    __syncwarp();
    if (lane == 0) {
      tma_store_2d(mo16, buf, cta * 128 + hg * 64, (i * 8 + (warp >> 1)) * 16);
      asm volatile("cp.async.bulk.commit_group;" ::: "memory");
    }
  }
  if (threadIdx.x == 0) PROF_T(1, 3);
  if (lane == 0) asm volatile("cp.async.bulk.wait_group 0;" ::: "memory");
}

__global__ void __launch_bounds__(512, 1)
attn_kernel(const __grid_constant__ CUtensorMap mo16, const uint8_t* __restrict__ woA, const uint8_t* __restrict__ woB) {
  extern __shared__ uint8_t smem_raw[];
  const uint32_t sbase = (smem_u32(smem_raw) + 1023) & ~1023u;
  const uint32_t bar = sbase + KV_HEAD_BYTES;
  if (threadIdx.x == 0) { PROF_G(1, 30); PROF_T(1, 0); }
  if (threadIdx.x == 0) {
    for (int i = 0; i < 4; i++) mbar_init(bar + 8 * i, 2);
    asm volatile("st.shared.v4.u32 [%0], {%1, %2, %3, %4};" ::"r"(bar + 64), "r"(0x3C003C00u), "r"(0x00070000u), "r"(7u),
                 "r"(ATT_DEG == 3 ? 0x2cfd2cfdu : 0x35623562u)
                 : "memory");
    fence_barrier_init();
    fence_proxy_async();
  }
  __syncthreads();
  pdl_launch_dependents();
  if (blockIdx.x >= 128 && threadIdx.x < 16) {
    const int i = (blockIdx.x - 128) * 16 + threadIdx.x;
    const uint8_t* p = (i < 32 ? woA : woB) + (size_t)(i & 31) * 16384;
    asm volatile("cp.async.bulk.prefetch.L2.global [%0], %1;" ::"l"(p), "r"(16384) : "memory");
  }
  if (blockIdx.x >= 128) {
    pdl_wait();
    linear_attn_cta(smem_raw, sbase, &mo16, blockIdx.x - 128);
    if (threadIdx.x == 0) { PROF_T(1, 5); PROF_G(1, 31); }
    return;
  }
  const int head = blockIdx.x >> 2, qb = blockIdx.x & 3;
  const int lane = threadIdx.x & 31;
  const int wg = __shfl_sync(0xffffffffu, threadIdx.x >> 7, 0), warp = __shfl_sync(0xffffffffu, (threadIdx.x >> 5) & 3, 0);
  ExpC ec;
  asm volatile("ld.volatile.shared.v4.u32 {%0, %1, %2, %3}, [%4];" : "=r"(ec.k3c00), "=r"(ec.kmask), "=r"(ec.seven), "=r"(ec.c3) : "r"(bar + 64));
  const uint64_t dK = mkdesc(sbase, 128, 256, 0);
  const uint64_t dV = mkdesc(sbase + KV_K_BYTES, 384, 128, 0);
  pdl_wait();
  if (threadIdx.x == 0) { PROF_T(1, 7); PROF_G(1, 29); }
  {
    const uint8_t* img = reinterpret_cast<const uint8_t*>(g_kv) + (size_t)head * KV_HEAD_BYTES;
#pragma unroll
    for (int i = 0; i < 3; i++) {
      const int c = threadIdx.x + i * 512;
      if (c < 1408) {
        const int off = c < 640 ? c * 16 : KV_K_BYTES + (c - 640) * 16;
        asm volatile("cp.async.cg.shared.global [%0], [%1], 16;" ::"r"(sbase + off), "l"(img + off) : "memory");
      }
    }
    asm volatile("cp.async.commit_group;" ::: "memory");
  }
  if (threadIdx.x == 0) {
#pragma unroll
    for (int piece = 2; piece < 8; piece++) kv_fetch_piece(sbase, bar, piece);
  }
  uint4 qnext = g_qfrag[(head * 32 + qb * 8 + wg * 2) * 128 + (threadIdx.x & 127)];
  bool safe_path;
  {
    float4 n = make_float4(0.f, 0.f, 0.f, 0.f);
    if (lane < 16) n = *reinterpret_cast<const float4*>(&g_nrm[(head * 16 + lane) * 4]);
    uint32_t qm = ((lane >> 2) == qb) ? __float_as_uint(n.x) : 0u;
    qm = __reduce_max_sync(0xffffffffu, qm);
    const uint32_t km = __reduce_max_sync(0xffffffffu, __float_as_uint(n.y));
    const uint32_t vm = __reduce_max_sync(0xffffffffu, __float_as_uint(n.z));
    const float b2 = __uint_as_float(qm) * (QSCALE * QSCALE) * __uint_as_float(km) * 1.02f;
    const float vmax = __uint_as_float(vm);
    const bool ok = (b2 <= 21.5f * 21.5f) && (vmax <= 1.0e24f) && (vmax >= 1.0e-18f || vmax == 0.f);
    safe_path = !ok;
  }
  asm volatile("cp.async.wait_all;" ::: "memory");
  fence_proxy_async();
  __syncthreads();
#pragma unroll 1
  for (int t = 0; t < 2; t++) {
    const int tile64 = qb * 8 + wg * 2 + t;
    const uint4 qf = qnext;
    if (t == 0) qnext = g_qfrag[(head * 32 + tile64 + 1) * 128 + (threadIdx.x & 127)];
    uint32_t r[4];
    if (threadIdx.x == 0) PROF_T(1, 1 + t);
    if (!safe_path) attn_tile<false>(dK, dV, bar, qf, ec, r);
    else attn_tile<true>(dK, dV, bar, qf, ec, r);
    store_o(g_o + (size_t)S_LEN * DM, tile64 * 64 + warp * 16, head, lane, r);
  }
  if (threadIdx.x == 0) { PROF_T(1, 5); PROF_G(1, 31); }
}

#define K3_WPRE 2
constexpr int K3_STAGES = 5;
constexpr int K3_W_BYTES = 8 * 16384;
constexpr int K3_BAR_OFF = K3_W_BYTES + K3_STAGES * 16384;
constexpr int K3_SMEM = K3_BAR_OFF + 256 + 1024;

__global__ void __launch_bounds__(288, 1)
out_gemm_kernel(const __grid_constant__ CUtensorMap mo, const __grid_constant__ CUtensorMap mwA,
                const __grid_constant__ CUtensorMap mwB, const __grid_constant__ CUtensorMap mout) {
  extern __shared__ uint8_t smem_raw[];
  const uint32_t sbase = (smem_u32(smem_raw) + 1023) & ~1023u;
  const uint32_t bar_full = sbase + K3_BAR_OFF;
  const uint32_t bar_empty = bar_full + 8 * K3_STAGES;
  const uint32_t bar_w = bar_empty + 8 * K3_STAGES;
  const int branch = blockIdx.x >> 6;
  const int rt = (blockIdx.x & 63) >> 2;
  const int ct = blockIdx.x & 3;
  const int warp = threadIdx.x >> 5;
  if (threadIdx.x == 0) { PROF_G(2, 30); PROF_T(2, 0); }
  if (threadIdx.x == 256) {
    const CUtensorMap* mw = branch ? &mwB : &mwA;
    asm volatile("prefetch.tensormap [%0];" ::"l"(mw) : "memory");
    asm volatile("prefetch.tensormap [%0];" ::"l"(&mo) : "memory");
    asm volatile("prefetch.tensormap [%0];" ::"l"(&mout) : "memory");
    for (int i = 0; i < K3_STAGES; i++) {
      mbar_init(bar_full + 8 * i, 1);
      mbar_init(bar_empty + 8 * i, 2);
    }
    for (int i = 0; i < 8; i++) mbar_init(bar_w + 8 * i, 1);
    fence_barrier_init();
    fence_proxy_async();
    for (int kb = 0; kb < K3_WPRE; kb++) {
      mbar_expect_tx(bar_w + 8 * kb, 16384);
      tma_load_2d(sbase + kb * 16384, mw, ct * 128, kb * 64, bar_w + 8 * kb);
      tma_load_2d(sbase + kb * 16384 + 8192, mw, ct * 128 + 64, kb * 64, bar_w + 8 * kb);
    }
  }
  __syncthreads();
  if (warp == 8) {
    if ((threadIdx.x & 31) == 0) {
      const CUtensorMap* mw = branch ? &mwB : &mwA;
      pdl_wait();
      PROF_T(2, 1);
      for (int kb = 0; kb < 8; kb++) {
        const int s = kb % K3_STAGES;
        if (kb >= K3_STAGES) mbar_wait(bar_empty + 8 * s, ((kb / K3_STAGES) - 1) & 1);
        mbar_expect_tx(bar_full + 8 * s, 16384);
        tma_load_2d(sbase + K3_W_BYTES + s * 16384, &mo, kb * 64, branch * S_LEN + rt * 128, bar_full + 8 * s);
        const int kw = kb + K3_WPRE;
        if (kw < 8) {
          mbar_expect_tx(bar_w + 8 * kw, 16384);
          tma_load_2d(sbase + kw * 16384, mw, ct * 128, kw * 64, bar_w + 8 * kw);
          tma_load_2d(sbase + kw * 16384 + 8192, mw, ct * 128 + 64, kw * 64, bar_w + 8 * kw);
        }
      }
    }
  } else {
    const int wg = warp >> 2;
    float acc[64];
    for (int kb = 0; kb < 8; kb++) {
      const int s = kb % K3_STAGES;
      mbar_wait(bar_w + 8 * kb, 0);
      mbar_wait(bar_full + 8 * s, (kb / K3_STAGES) & 1);
      if (threadIdx.x == 0) PROF_T(2, 2 + kb);
      const uint64_t dA = mkdesc(sbase + K3_W_BYTES + s * 16384 + wg * 8192, 16, 1024, 1);
      const uint64_t dB = mkdesc(sbase + kb * 16384, 8192, 1024, 1);
      wg_fence();
#pragma unroll
      for (int k = 0; k < 4; k++) wgmma_ss_n128_tb(acc, dA + k * 2, dB + k * 128, (kb | k) != 0);
      wg_commit();
      if (kb > 0) {
        wg_wait<1>();
        if ((threadIdx.x & 127) == 0) mbar_arrive(bar_empty + 8 * ((kb - 1) % K3_STAGES));
      }
    }
    wg_wait<0>();
    fence_regs(acc);
    if (threadIdx.x == 0) PROF_T(2, 10);
    const uint32_t stg = sbase + K3_W_BYTES + wg * 8192;
    const int lane = threadIdx.x & 31;
    const int rloc = (warp & 3) * 16 + (lane & 15);
#pragma unroll
    for (int c16 = 0; c16 < 8; c16++) {
      const float* a = &acc[c16 * 8];
      const uint32_t r0 = pack_bf16(a[0], a[1]), r1 = pack_bf16(a[2], a[3]), r2 = pack_bf16(a[4], a[5]), r3 = pack_bf16(a[6], a[7]);
      const int chunk = (c16 & 3) * 2 + (lane >> 4);
      const uint32_t addr = stg + (c16 >> 2) * 16384 + rloc * 128 + ((chunk ^ (rloc & 7)) << 4);
      asm volatile("stmatrix.sync.aligned.m8n8.x4.shared.b16 [%0], {%1,%2,%3,%4};" ::"r"(addr), "r"(r0), "r"(r1), "r"(r2), "r"(r3)
                   : "memory");
    }
    fence_proxy_async();
    asm volatile("bar.sync %0, 128;" ::"r"(2 + wg) : "memory");
    if ((threadIdx.x & 127) == 0) {
      tma_store_2d(&mout, stg, branch * DM + ct * 128, rt * 128 + wg * 64);
      tma_store_2d(&mout, stg + 16384, branch * DM + ct * 128 + 64, rt * 128 + wg * 64);
      asm volatile("cp.async.bulk.commit_group;" ::: "memory");
      asm volatile("cp.async.bulk.wait_group.read 0;" ::: "memory");
      if (threadIdx.x == 0) { PROF_T(2, 12); PROF_G(2, 31); }
    }
  }
}

typedef CUresult (*EncodeFn)(CUtensorMap*, CUtensorMapDataType, cuuint32_t, void*, const cuuint64_t*, const cuuint64_t*,
                             const cuuint32_t*, const cuuint32_t*, CUtensorMapInterleave, CUtensorMapSwizzle,
                             CUtensorMapL2promotion, CUtensorMapFloatOOBfill);

void make_map(EncodeFn enc, CUtensorMap* m, const void* ptr, uint64_t inner, uint64_t outer, uint32_t box_inner, uint32_t box_outer) {
  cuuint64_t dims[2] = {inner, outer};
  cuuint64_t strides[1] = {inner * 2};
  cuuint32_t box[2] = {box_inner, box_outer};
  cuuint32_t es[2] = {1, 1};
  enc(m, CU_TENSOR_MAP_DATA_TYPE_BFLOAT16, 2, const_cast<void*>(ptr), dims, strides, box, es, CU_TENSOR_MAP_INTERLEAVE_NONE,
      CU_TENSOR_MAP_SWIZZLE_128B, CU_TENSOR_MAP_L2_PROMOTION_L2_256B, CU_TENSOR_MAP_FLOAT_OOB_FILL_NONE);
}

struct HostState {
  bool init;
  const void* key[7];
  CUtensorMap mxA, mxB, mwA, mwB, mo, mo16, mwoA, mwoB, mout;
};
HostState g_hs;

}

extern "C" void kernel_launch(void* const* d_in, const int* in_sizes, int n_in, void* d_out, int out_size) {
  (void)in_sizes; (void)n_in; (void)out_size;
  HostState& hs = g_hs;
  bool same = hs.init && hs.key[6] == d_out;
  for (int i = 0; i < 6 && same; i++) same = hs.key[i] == d_in[i];
  if (!same) {
    void* fn = nullptr;
    cudaDriverEntryPointQueryResult qr;
    cudaGetDriverEntryPoint("cuTensorMapEncodeTiled", &fn, cudaEnableDefault, &qr);
    EncodeFn enc = (EncodeFn)fn;
    void* go = nullptr;
    cudaGetSymbolAddress(&go, g_o);
    make_map(enc, &hs.mxA, d_in[0], 512, 2048, 64, 128);
    make_map(enc, &hs.mwA, d_in[1], 1536, 512, 64, 32);
    make_map(enc, &hs.mwoA, d_in[2], 512, 512, 64, 64);
    make_map(enc, &hs.mxB, d_in[3], 512, 2048, 64, 128);
    make_map(enc, &hs.mwB, d_in[4], 1536, 512, 64, 32);
    make_map(enc, &hs.mwoB, d_in[5], 512, 512, 64, 64);
    make_map(enc, &hs.mo, go, 512, 4096, 64, 128);
    make_map(enc, &hs.mo16, go, 512, 4096, 64, 16);
    make_map(enc, &hs.mout, d_out, 1024, 2048, 64, 64);
    cudaFuncSetAttribute(qkv_gemm_kernel, cudaFuncAttributeMaxDynamicSharedMemorySize, K1_SMEM);
    cudaFuncSetAttribute(attn_kernel, cudaFuncAttributeMaxDynamicSharedMemorySize, K2_SMEM);
    cudaFuncSetAttribute(out_gemm_kernel, cudaFuncAttributeMaxDynamicSharedMemorySize, K3_SMEM);
    for (int i = 0; i < 6; i++) hs.key[i] = d_in[i];
    hs.key[6] = d_out;
    hs.init = true;
  }
  cudaStream_t st = cudaStreamPerThread;
  {
    cudaLaunchConfig_t cfg = {};
    cfg.gridDim = dim3(128);
    cfg.blockDim = dim3(384);
    cfg.dynamicSmemBytes = K1_SMEM;
    cfg.stream = st;
    cudaLaunchAttribute at[1];
    at[0].id = cudaLaunchAttributeClusterDimension;
    at[0].val.clusterDim.x = 2;
    at[0].val.clusterDim.y = 1;
    at[0].val.clusterDim.z = 1;
    cfg.attrs = at;
    cfg.numAttrs = 1;
    cudaLaunchKernelEx(&cfg, qkv_gemm_kernel, hs.mxA, hs.mxB, hs.mwA, hs.mwB);
  }
  {
    cudaLaunchConfig_t cfg = {};
    cfg.gridDim = dim3(132);
    cfg.blockDim = dim3(512);
    cfg.dynamicSmemBytes = K2_SMEM;
    cfg.stream = st;
    cudaLaunchAttribute at[1];
    at[0].id = cudaLaunchAttributeProgrammaticStreamSerialization;
    at[0].val.programmaticStreamSerializationAllowed = 1;
    cfg.attrs = at;
    cfg.numAttrs = 1;
    cudaLaunchKernelEx(&cfg, attn_kernel, hs.mo16, (const uint8_t*)d_in[2], (const uint8_t*)d_in[5]);
    cfg.gridDim = dim3(128);
    cfg.blockDim = dim3(288);
    cfg.dynamicSmemBytes = K3_SMEM;
    cudaLaunchKernelEx(&cfg, out_gemm_kernel, hs.mo, hs.mwoA, hs.mwoB, hs.mout);
  }
}
```

```cpp
#include <cuda_runtime.h>
#include <cuda_bf16.h>
#include <cuda.h>
#include <stdint.h>

namespace {

constexpr int S_LEN = 2048;
constexpr int DM = 512;
constexpr int NH = 32;

constexpr int KV_K_BYTES = 65536;
constexpr int KV_HEAD_BYTES = KV_K_BYTES + 98304;
__device__ uint4 g_qfrag[2 * NH * 32 * 128];
__device__ uint4 g_kv[NH * KV_HEAD_BYTES / 16];
__device__ float g_kvpart[16 * NH * 384];
__device__ float g_nrm[NH * 16 * 4];
__device__ __nv_bfloat16 g_o[2 * S_LEN * DM];

#define g_prof_set(k, i, v)
#define g_prof_dummy(i) true
#define PROF_T(k, i) do {} while (0)
#define PROF_G(k, i) do {} while (0)
__device__ __forceinline__ uint32_t smem_u32(const void* p) { return (uint32_t)__cvta_generic_to_shared(p); }
__device__ __forceinline__ void mbar_init(uint32_t bar, int cnt) {
  asm volatile("mbarrier.init.shared::cta.b64 [%0], %1;" ::"r"(bar), "r"(cnt) : "memory");
}
__device__ __forceinline__ void mbar_expect_tx(uint32_t bar, uint32_t bytes) {
  asm volatile("mbarrier.arrive.expect_tx.shared::cta.b64 _, [%0], %1;" ::"r"(bar), "r"(bytes) : "memory");
}
__device__ __forceinline__ void mbar_arrive(uint32_t bar) {
  asm volatile("mbarrier.arrive.shared::cta.b64 _, [%0];" ::"r"(bar) : "memory");
}
__device__ __forceinline__ void mbar_arrive_cluster(uint32_t bar, uint32_t cta) {
  asm volatile(
      "{\n.reg .b32 ra;\nmapa.shared::cluster.u32 ra, %0, %1;\n"
      "mbarrier.arrive.shared::cluster.b64 _, [ra];\n}" ::"r"(bar), "r"(cta) : "memory");
}
__device__ __forceinline__ void mbar_wait(uint32_t bar, uint32_t parity) {
  asm volatile(
      "{\n.reg .pred p;\n.reg .u32 n;\n"
      "mov.u32 n, 0;\n"
      "WAIT_LOOP:\n"
      "mbarrier.try_wait.parity.shared::cta.b64 p, [%0], %1, 0x400000;\n"
      "@p bra WAIT_DONE;\n"
      "add.u32 n, n, 1;\n"
      "setp.lt.u32 p, n, 4000000;\n"
      "@p bra WAIT_LOOP;\n"
      "trap;\n"
      "WAIT_DONE:\n}" ::"r"(bar), "r"(parity) : "memory");
}
__device__ __forceinline__ void fence_barrier_init() {
  asm volatile("fence.mbarrier_init.release.cluster;" ::: "memory");
}
__device__ __forceinline__ void fence_proxy_async() { asm volatile("fence.proxy.async.shared::cta;" ::: "memory"); }
__device__ __forceinline__ void cluster_sync_relaxed() {
  asm volatile("barrier.cluster.arrive.relaxed.aligned;\nbarrier.cluster.wait.aligned;" ::: "memory");
}
__device__ __forceinline__ void tma_load_2d(uint32_t dst, const CUtensorMap* m, int x, int y, uint32_t bar) {
  asm volatile(
      "cp.async.bulk.tensor.2d.shared::cluster.global.mbarrier::complete_tx::bytes [%0], [%1, {%3, %4}], [%2];" ::"r"(dst),
      "l"(m), "r"(bar), "r"(x), "r"(y)
      : "memory");
}
__device__ __forceinline__ void tma_load_2d_mc(uint32_t dst, const CUtensorMap* m, int x, int y, uint32_t bar, uint16_t mask) {
  asm volatile(
      "cp.async.bulk.tensor.2d.shared::cluster.global.mbarrier::complete_tx::bytes.multicast::cluster [%0], [%1, {%3, %4}], "
      "[%2], %5;" ::"r"(dst),
      "l"(m), "r"(bar), "r"(x), "r"(y), "h"(mask)
      : "memory");
}
__device__ __forceinline__ void tma_store_2d(const CUtensorMap* m, uint32_t src, int x, int y) {
  asm volatile("cp.async.bulk.tensor.2d.global.shared::cta.bulk_group [%0, {%2, %3}], [%1];" ::"l"(m), "r"(src), "r"(x),
               "r"(y)
               : "memory");
}
__device__ __forceinline__ void bulk_load(uint32_t dst, const void* src, uint32_t bytes, uint32_t bar) {
  asm volatile("cp.async.bulk.shared::cluster.global.mbarrier::complete_tx::bytes [%0], [%1], %2, [%3];" ::"r"(dst),
               "l"(src), "r"(bytes), "r"(bar)
               : "memory");
}
__device__ __forceinline__ void bulk_load_mc(uint32_t dst, const void* src, uint32_t bytes, uint32_t bar, uint16_t mask) {
  asm volatile("cp.async.bulk.shared::cluster.global.mbarrier::complete_tx::bytes.multicast::cluster [%0], [%1], %2, [%3], %4;" ::"r"(dst),
               "l"(src), "r"(bytes), "r"(bar), "h"(mask)
               : "memory");
}
__device__ __forceinline__ void pdl_launch_dependents() { asm volatile("griddepcontrol.launch_dependents;" ::: "memory"); }
__device__ __forceinline__ void pdl_wait() { asm volatile("griddepcontrol.wait;" ::: "memory"); }
__device__ __forceinline__ void wg_fence() { asm volatile("wgmma.fence.sync.aligned;" ::: "memory"); }
__device__ __forceinline__ void wg_commit() { asm volatile("wgmma.commit_group.sync.aligned;" ::: "memory"); }
template <int N>
__device__ __forceinline__ void wg_wait() {
  asm volatile("wgmma.wait_group.sync.aligned %0;" ::"n"(N) : "memory");
}
template <int M>
__device__ __forceinline__ void fence_regs(float (&r)[M]) {
#pragma unroll
  for (int i = 0; i < M; i++) asm volatile("" : "+f"(r[i])::"memory");
}
__device__ __forceinline__ uint64_t mkdesc(uint32_t addr, uint32_t lbo, uint32_t sbo, uint32_t layout) {
  return (uint64_t)((addr & 0x3FFFF) >> 4) | ((uint64_t)(lbo >> 4) << 16) | ((uint64_t)(sbo >> 4) << 32) |
         ((uint64_t)layout << 62);
}
__device__ __forceinline__ uint32_t pack_bf16(float lo, float hi) {
  uint32_t r;
  asm("cvt.rn.bf16x2.f32 %0, %1, %2;" : "=r"(r) : "f"(hi), "f"(lo));
  return r;
}
__device__ __forceinline__ float bf_lo(uint32_t v) { return __uint_as_float(v << 16); }
__device__ __forceinline__ float bf_hi(uint32_t v) { return __uint_as_float(v & 0xFFFF0000u); }
__device__ __forceinline__ float round_bf16(float x) { return bf_lo(pack_bf16(x, 0.f)); }
__device__ __forceinline__ float ex2f(float x) {
  float y;
  asm("ex2.approx.ftz.f32 %0, %1;" : "=f"(y) : "f"(x));
  return y;
}

__device__ __forceinline__ void wgmma_rs_n24_tb(float (&d)[12], uint32_t a0, uint32_t a1, uint32_t a2, uint32_t a3, uint64_t descB, int scaleD) {
  asm volatile("{\n.reg .pred p;\nsetp.ne.b32 p, %17, 0;\n"
    "wgmma.mma_async.sync.aligned.m64n24k16.f32.bf16.bf16 "
    "{%0, %1, %2, %3, %4, %5, %6, %7, %8, %9, %10, %11}, {%12, %13, %14, %15}, %16, p, 1, 1, 1;\n}\n"
    : "+f"(d[0]), "+f"(d[1]), "+f"(d[2]), "+f"(d[3]), "+f"(d[4]), "+f"(d[5]), "+f"(d[6]), "+f"(d[7]),
      "+f"(d[8]), "+f"(d[9]), "+f"(d[10]), "+f"(d[11])
    : "r"(a0), "r"(a1), "r"(a2), "r"(a3), "l"(descB), "r"(scaleD));
}
__device__ __forceinline__ void wgmma_rs_n64_z(float (&d)[32], uint32_t a0, uint32_t a1, uint32_t a2, uint32_t a3, uint64_t descB) {
  asm volatile("{\n.reg .pred p;\nsetp.ne.b32 p, %37, 0;\n"
    "wgmma.mma_async.sync.aligned.m64n64k16.f32.bf16.bf16 "
    "{%0, %1, %2, %3, %4, %5, %6, %7, %8, %9, %10, %11, %12, %13, %14, %15, %16, %17, %18, %19, %20, %21, %22, %23, %24, %25, %26, %27, %28, %29, %30, %31}, {%32, %33, %34, %35}, %36, p, 1, 1, 0;\n}\n"
    : "=f"(d[0]), "=f"(d[1]), "=f"(d[2]), "=f"(d[3]), "=f"(d[4]), "=f"(d[5]), "=f"(d[6]), "=f"(d[7]),
      "=f"(d[8]), "=f"(d[9]), "=f"(d[10]), "=f"(d[11]), "=f"(d[12]), "=f"(d[13]), "=f"(d[14]), "=f"(d[15]),
      "=f"(d[16]), "=f"(d[17]), "=f"(d[18]), "=f"(d[19]), "=f"(d[20]), "=f"(d[21]), "=f"(d[22]), "=f"(d[23]),
      "=f"(d[24]), "=f"(d[25]), "=f"(d[26]), "=f"(d[27]), "=f"(d[28]), "=f"(d[29]), "=f"(d[30]), "=f"(d[31])
    : "r"(a0), "r"(a1), "r"(a2), "r"(a3), "l"(descB), "n"(0));
}
__device__ __forceinline__ void wgmma_ss_n128_tb(float (&d)[64], uint64_t descA, uint64_t descB, int scaleD) {
  asm volatile("{\n.reg .pred p;\nsetp.ne.b32 p, %66, 0;\n"
    "wgmma.mma_async.sync.aligned.m64n128k16.f32.bf16.bf16 "
    "{%0, %1, %2, %3, %4, %5, %6, %7, %8, %9, %10, %11, %12, %13, %14, %15, %16, %17, %18, %19, %20, %21, %22, %23, %24, %25, %26, %27, %28, %29, %30, %31, %32, %33, %34, %35, %36, %37, %38, %39, %40, %41, %42, %43, %44, %45, %46, %47, %48, %49, %50, %51, %52, %53, %54, %55, %56, %57, %58, %59, %60, %61, %62, %63}, %64, %65, p, 1, 1, 0, 1;\n}\n"
    : "+f"(d[0]), "+f"(d[1]), "+f"(d[2]), "+f"(d[3]), "+f"(d[4]), "+f"(d[5]), "+f"(d[6]), "+f"(d[7]),
      "+f"(d[8]), "+f"(d[9]), "+f"(d[10]), "+f"(d[11]), "+f"(d[12]), "+f"(d[13]), "+f"(d[14]), "+f"(d[15]),
      "+f"(d[16]), "+f"(d[17]), "+f"(d[18]), "+f"(d[19]), "+f"(d[20]), "+f"(d[21]), "+f"(d[22]), "+f"(d[23]),
      "+f"(d[24]), "+f"(d[25]), "+f"(d[26]), "+f"(d[27]), "+f"(d[28]), "+f"(d[29]), "+f"(d[30]), "+f"(d[31]),
      "+f"(d[32]), "+f"(d[33]), "+f"(d[34]), "+f"(d[35]), "+f"(d[36]), "+f"(d[37]), "+f"(d[38]), "+f"(d[39]),
      "+f"(d[40]), "+f"(d[41]), "+f"(d[42]), "+f"(d[43]), "+f"(d[44]), "+f"(d[45]), "+f"(d[46]), "+f"(d[47]),
      "+f"(d[48]), "+f"(d[49]), "+f"(d[50]), "+f"(d[51]), "+f"(d[52]), "+f"(d[53]), "+f"(d[54]), "+f"(d[55]),
      "+f"(d[56]), "+f"(d[57]), "+f"(d[58]), "+f"(d[59]), "+f"(d[60]), "+f"(d[61]), "+f"(d[62]), "+f"(d[63])
    : "l"(descA), "l"(descB), "r"(scaleD));
}
__device__ __forceinline__ void wgmma_ss_n192_tb(float (&d)[96], uint64_t descA, uint64_t descB, int scaleD) {
  asm volatile("{\n.reg .pred p;\nsetp.ne.b32 p, %98, 0;\n"
    "wgmma.mma_async.sync.aligned.m64n192k16.f32.bf16.bf16 "
    "{%0, %1, %2, %3, %4, %5, %6, %7, %8, %9, %10, %11, %12, %13, %14, %15, %16, %17, %18, %19, %20, %21, %22, %23, %24, %25, %26, %27, %28, %29, %30, %31, %32, %33, %34, %35, %36, %37, %38, %39, %40, %41, %42, %43, %44, %45, %46, %47, %48, %49, %50, %51, %52, %53, %54, %55, %56, %57, %58, %59, %60, %61, %62, %63, %64, %65, %66, %67, %68, %69, %70, %71, %72, %73, %74, %75, %76, %77, %78, %79, %80, %81, %82, %83, %84, %85, %86, %87, %88, %89, %90, %91, %92, %93, %94, %95}, %96, %97, p, 1, 1, 0, 1;\n}\n"
    : "+f"(d[0]), "+f"(d[1]), "+f"(d[2]), "+f"(d[3]), "+f"(d[4]), "+f"(d[5]), "+f"(d[6]), "+f"(d[7]),
      "+f"(d[8]), "+f"(d[9]), "+f"(d[10]), "+f"(d[11]), "+f"(d[12]), "+f"(d[13]), "+f"(d[14]), "+f"(d[15]),
      "+f"(d[16]), "+f"(d[17]), "+f"(d[18]), "+f"(d[19]), "+f"(d[20]), "+f"(d[21]), "+f"(d[22]), "+f"(d[23]),
      "+f"(d[24]), "+f"(d[25]), "+f"(d[26]), "+f"(d[27]), "+f"(d[28]), "+f"(d[29]), "+f"(d[30]), "+f"(d[31]),
      "+f"(d[32]), "+f"(d[33]), "+f"(d[34]), "+f"(d[35]), "+f"(d[36]), "+f"(d[37]), "+f"(d[38]), "+f"(d[39]),
      "+f"(d[40]), "+f"(d[41]), "+f"(d[42]), "+f"(d[43]), "+f"(d[44]), "+f"(d[45]), "+f"(d[46]), "+f"(d[47]),
      "+f"(d[48]), "+f"(d[49]), "+f"(d[50]), "+f"(d[51]), "+f"(d[52]), "+f"(d[53]), "+f"(d[54]), "+f"(d[55]),
      "+f"(d[56]), "+f"(d[57]), "+f"(d[58]), "+f"(d[59]), "+f"(d[60]), "+f"(d[61]), "+f"(d[62]), "+f"(d[63]),
      "+f"(d[64]), "+f"(d[65]), "+f"(d[66]), "+f"(d[67]), "+f"(d[68]), "+f"(d[69]), "+f"(d[70]), "+f"(d[71]),
      "+f"(d[72]), "+f"(d[73]), "+f"(d[74]), "+f"(d[75]), "+f"(d[76]), "+f"(d[77]), "+f"(d[78]), "+f"(d[79]),
      "+f"(d[80]), "+f"(d[81]), "+f"(d[82]), "+f"(d[83]), "+f"(d[84]), "+f"(d[85]), "+f"(d[86]), "+f"(d[87]),
      "+f"(d[88]), "+f"(d[89]), "+f"(d[90]), "+f"(d[91]), "+f"(d[92]), "+f"(d[93]), "+f"(d[94]), "+f"(d[95])
    : "l"(descA), "l"(descB), "r"(scaleD));
}

__device__ __forceinline__ void ldsm4t(uint32_t (&b)[4], uint32_t addr) {
  asm volatile("ldmatrix.sync.aligned.m8n8.x4.trans.shared.b16 {%0,%1,%2,%3}, [%4];"
               : "=r"(b[0]), "=r"(b[1]), "=r"(b[2]), "=r"(b[3])
               : "r"(addr));
}
__device__ __forceinline__ void hmma(float (&c)[4], uint32_t a0, uint32_t a1, uint32_t a2, uint32_t a3, uint32_t b0, uint32_t b1) {
  asm("mma.sync.aligned.m16n8k16.row.col.f32.bf16.bf16.f32 {%0,%1,%2,%3}, {%4,%5,%6,%7}, {%8,%9}, {%0,%1,%2,%3};"
      : "+f"(c[0]), "+f"(c[1]), "+f"(c[2]), "+f"(c[3])
      : "r"(a0), "r"(a1), "r"(a2), "r"(a3), "r"(b0), "r"(b1));
}

__device__ __forceinline__ uint32_t movm(uint32_t a) {
  uint32_t d;
  asm volatile("movmatrix.sync.aligned.m8n8.trans.b16 %0, %1;" : "=r"(d) : "r"(a));
  return d;
}

#define K1_W0_LOCAL 1
#define K1_WARM 0
constexpr int K1_STAGES = 4;
constexpr int K1_W_BYTES = 3 * 8192;
constexpr int K1_X_BYTES = 8 * 16384;
constexpr int K1_BAR_OFF = K1_X_BYTES + K1_STAGES * K1_W_BYTES;
constexpr int K1_SMEM = K1_BAR_OFF + 192 + 1024;
constexpr float QSCALE = 0.25f * 1.4426950408889634f;

__device__ __forceinline__ uint32_t phi2(uint32_t t2) {
  uint32_t a2, mask, r2, o2;
  asm("add.rn.bf16x2 %0, %1, %2;" : "=r"(a2) : "r"(t2), "r"(0x3F803F80u));
  const uint32_t e2 = pack_bf16(ex2f(bf_lo(t2) * 1.4426950408889634f), ex2f(bf_hi(t2) * 1.4426950408889634f));
  asm("set.gt.u32.bf16x2 %0, %1, %2;" : "=r"(mask) : "r"(t2), "r"(0u));
  r2 = (a2 & mask) | (e2 & ~mask);
  asm("add.rn.bf16x2 %0, %1, %2;" : "=r"(o2) : "r"(r2), "r"(0x35863586u));
  return o2;
}

#define K1_SLOT_KB(h) ((h) < 4 ? 2 * (h) : 2 * ((h) - 4) + 1)
struct EpiCtx {
  uint4* qf;
  uint32_t* kp;
  uint32_t* vp;
  uint32_t s_red_addr;
  float* red;
  int lane;
};

template <bool LINEAR, int HH, int PART>
__device__ __forceinline__ void epi_slice(const float (&acc)[96], const EpiCtx& c, uint32_t (&pk)[4], float& vmax, bool live) {
  const float* a = &acc[HH * 8];
  const float* k = &acc[32 + HH * 8];
  const float* v = &acc[64 + HH * 8];
  if (!LINEAR) {
    if (PART == 0) {
      uint32_t* kh = c.kp + HH * (KV_HEAD_BYTES / 4);
      if (live) {
        c.qf[HH * 32 * 128] = make_uint4(pack_bf16(a[0], a[1]), pack_bf16(a[2], a[3]), pack_bf16(a[4], a[5]), pack_bf16(a[6], a[7]));
        kh[0] = pack_bf16(k[0], k[1]);
        kh[64] = pack_bf16(k[2], k[3]);
        kh[32] = pack_bf16(k[4], k[5]);
        kh[96] = pack_bf16(k[6], k[7]);
      }
      float q0 = a[0] * a[0] + a[1] * a[1] + a[4] * a[4] + a[5] * a[5];
      float q1 = a[2] * a[2] + a[3] * a[3] + a[6] * a[6] + a[7] * a[7];
      float k0 = k[0] * k[0] + k[1] * k[1] + k[4] * k[4] + k[5] * k[5];
      float k1 = k[2] * k[2] + k[3] * k[3] + k[6] * k[6] + k[7] * k[7];
#pragma unroll
      for (int o = 1; o <= 2; o <<= 1) {
        q0 += __shfl_xor_sync(0xffffffffu, q0, o);
        q1 += __shfl_xor_sync(0xffffffffu, q1, o);
        k0 += __shfl_xor_sync(0xffffffffu, k0, o);
        k1 += __shfl_xor_sync(0xffffffffu, k1, o);
      }
      const uint32_t qm = __reduce_max_sync(0xffffffffu, max(__float_as_uint(q0) & 0x7FFFFFFFu, __float_as_uint(q1) & 0x7FFFFFFFu));
      const uint32_t km = __reduce_max_sync(0xffffffffu, max(__float_as_uint(k0) & 0x7FFFFFFFu, __float_as_uint(k1) & 0x7FFFFFFFu));
      asm volatile(
          "{\n.reg .pred p;\nsetp.ne.b32 p, %3, 0;\n"
          "@p red.shared.max.u32 [%0], %1;\n@p red.shared.max.u32 [%0+4], %2;\n}" ::"r"(c.s_red_addr + HH * 8),
          "r"(qm), "r"(km), "r"((c.lane == 0 && live) ? 1 : 0)
          : "memory");
    } else {
      uint32_t* vh = c.vp + HH * (KV_HEAD_BYTES / 4);
      if (live) {
        vh[0] = pack_bf16(v[0], v[1]);
        vh[96] = pack_bf16(v[2], v[3]);
        vh[32] = pack_bf16(v[4], v[5]);
        vh[128] = pack_bf16(v[6], v[7]);
        vh[64] = 0x3F803F80u;
        vh[160] = 0x3F803F80u;
      }
#pragma unroll
      for (int i = 0; i < 8; i++) asm("max.NaN.f32 %0, %0, %1;" : "+f"(vmax) : "f"(fabsf(v[i])));
    }
  } else {
    if (PART == 0) {
      const uint4 pq = make_uint4(phi2(pack_bf16(a[0], a[1])), phi2(pack_bf16(a[2], a[3])), phi2(pack_bf16(a[4], a[5])),
                                  phi2(pack_bf16(a[6], a[7])));
      if (live) c.qf[HH * 32 * 128] = pq;
      pk[0] = movm(phi2(pack_bf16(k[0], k[1])));
      pk[2] = movm(phi2(pack_bf16(k[2], k[3])));
      pk[1] = movm(phi2(pack_bf16(k[4], k[5])));
      pk[3] = movm(phi2(pack_bf16(k[6], k[7])));
    } else {
      const uint32_t b0 = movm(pack_bf16(v[0], v[1]));
      const uint32_t b1 = movm(pack_bf16(v[2], v[3]));
      const uint32_t b2 = movm(pack_bf16(v[4], v[5]));
      const uint32_t b3 = movm(pack_bf16(v[6], v[7]));
      float c0[4] = {0, 0, 0, 0}, c1[4] = {0, 0, 0, 0}, c2[4] = {0, 0, 0, 0};
      hmma(c0, pk[0], pk[1], pk[2], pk[3], b0, b1);
      hmma(c1, pk[0], pk[1], pk[2], pk[3], b2, b3);
      hmma(c2, pk[0], pk[1], pk[2], pk[3], 0x3F803F80u, 0x3F803F80u);
      float* slot = c.red + HH * 2 * 4096;
      if (live) {
#pragma unroll
        for (int i = 0; i < 4; i++) {
          slot[i * 32] = c0[i];
          slot[(4 + i) * 32] = c1[i];
          slot[(8 + i) * 32] = c2[i];
        }
      }
    }
  }
}

template <bool LINEAR>
__device__ __forceinline__ void qkv_consumer(uint32_t sbase, uint8_t* smem_gen, uint32_t* s_red, int cp, int rt) {
  const uint32_t bar_full = sbase + K1_BAR_OFF;
  const uint32_t bar_empty = bar_full + 8 * K1_STAGES;
  const int warp = threadIdx.x >> 5;
  const int wg = warp >> 2;
  const int lane = threadIdx.x & 31;
  float accN[96], accP[96];
  EpiCtx c;
  {
    const int row0 = rt * 128 + wg * 64 + (warp & 3) * 16;
    c.qf = g_qfrag + ((size_t)((LINEAR ? NH : 0) + cp * 8) * 32 + (rt * 2 + wg)) * 128 + (threadIdx.x & 127);
    uint32_t* img = reinterpret_cast<uint32_t*>(reinterpret_cast<uint8_t*>(g_kv) + (size_t)(cp * 8) * KV_HEAD_BYTES);
    c.kp = img + (row0 >> 3) * 64 + lane;
    c.vp = img + KV_K_BYTES / 4 + (row0 >> 3) * 96 + lane;
    c.s_red_addr = smem_u32(s_red);
    c.red = reinterpret_cast<float*>(smem_gen + wg * 8192) + (warp & 3) * 384 + lane;
    c.lane = lane;
  }
  uint32_t pk[4] = {0, 0, 0, 0};
  float vmax = 0.f;
#pragma unroll
  for (int i = 0; i < 96; i++) asm volatile("mov.f32 %0, 0f00000000;" : "=f"(accN[i]));
  int npass;
  asm volatile("mov.u32 %0, 2;" : "=r"(npass));
#pragma unroll 1
  for (int pass = K1_WARM ? 0 : 1; pass < npass; pass++) {
    const bool live = K1_WARM ? pass != 0 : true;
    if (live) {
#pragma unroll 1
      for (int kb = 0; kb < 8; kb++) {
        const int s = kb % K1_STAGES;
        mbar_wait(bar_full + 8 * s, (kb / K1_STAGES) & 1);
        if (threadIdx.x == 0) PROF_T(0, 2 + (kb >> 1));
        const uint64_t dA = mkdesc(sbase + kb * 16384 + wg * 8192, 16, 1024, 1);
        const uint64_t dB = mkdesc(sbase + K1_X_BYTES + s * K1_W_BYTES, 8192, 1024, 1);
        wg_fence();
#pragma unroll
        for (int k = 0; k < 4; k++) wgmma_ss_n192_tb(accP, dA + k * 2, dB + k * 128, (kb | k) != 0);
        wg_commit();
        if (kb > 0) {
          wg_wait<1>();
          if ((threadIdx.x & 127) == 0) {
            const int sp = (kb - 1) % K1_STAGES;
            mbar_arrive_cluster(bar_empty + 8 * sp, 0);
            mbar_arrive_cluster(bar_empty + 8 * sp, 1);
          }
        }
      }
      wg_wait<0>();
      fence_regs(accP);
      if ((threadIdx.x & 127) == 0) {
        mbar_arrive_cluster(bar_empty + 8 * (7 % K1_STAGES), 0);
        mbar_arrive_cluster(bar_empty + 8 * (7 % K1_STAGES), 1);
      }
      if (threadIdx.x == 0) PROF_T(0, 6);
#define K1_T1_STEP(KB)                                                                           \
  {                                                                                              \
    constexpr int g = 8 + KB;                                                                    \
    constexpr int s = g % K1_STAGES;                                                             \
    mbar_wait(bar_full + 8 * s, (g / K1_STAGES) & 1);                                            \
    const uint64_t dA = mkdesc(sbase + KB * 16384 + wg * 8192, 16, 1024, 1);                     \
    const uint64_t dB = mkdesc(sbase + K1_X_BYTES + s * K1_W_BYTES, 8192, 1024, 1);              \
    wg_fence();                                                                                  \
    _Pragma("unroll") for (int k = 0; k < 4; k++) wgmma_ss_n192_tb(accN, dA + k * 2, dB + k * 128, (KB | k) != 0); \
    wg_commit();                                                                                 \
    epi_slice<LINEAR, KB / 2, KB & 1>(accP, c, pk, vmax, true);                                  \
    wg_wait<0>();                                                                                \
    if (KB + K1_STAGES < 8 && (threadIdx.x & 127) == 0) {                                        \
      mbar_arrive_cluster(bar_empty + 8 * s, 0);                                                 \
      mbar_arrive_cluster(bar_empty + 8 * s, 1);                                                 \
    }                                                                                            \
  }
      K1_T1_STEP(0) K1_T1_STEP(1) K1_T1_STEP(2) K1_T1_STEP(3) K1_T1_STEP(4) K1_T1_STEP(5) K1_T1_STEP(6) K1_T1_STEP(7)
#undef K1_T1_STEP
      fence_regs(accN);
      if (threadIdx.x == 0) PROF_T(0, 10);
      c.qf += 4 * 32 * 128;
      c.kp += 4 * (KV_HEAD_BYTES / 4);
      c.vp += 4 * (KV_HEAD_BYTES / 4);
      c.s_red_addr += 32;
      c.red += 4096;
    }
    float vm1 = 0.f;
    epi_slice<LINEAR, 0, 0>(accN, c, pk, vm1, live);
    epi_slice<LINEAR, 0, 1>(accN, c, pk, vm1, live);
    epi_slice<LINEAR, 1, 0>(accN, c, pk, vm1, live);
    epi_slice<LINEAR, 1, 1>(accN, c, pk, vm1, live);
    epi_slice<LINEAR, 2, 0>(accN, c, pk, vm1, live);
    epi_slice<LINEAR, 2, 1>(accN, c, pk, vm1, live);
    epi_slice<LINEAR, 3, 0>(accN, c, pk, vm1, live);
    epi_slice<LINEAR, 3, 1>(accN, c, pk, vm1, live);
    if (live) asm("max.NaN.f32 %0, %0, %1;" : "+f"(vmax) : "f"(vm1));
  }
  if (!LINEAR) {
    const uint32_t vm = __reduce_max_sync(0xffffffffu, __float_as_uint(vmax) & 0x7FFFFFFFu);
    if (lane == 0) atomicMax(&s_red[16], vm);
    asm volatile("bar.sync 1, 256;" ::: "memory");
    if (threadIdx.x < 8) {
      *reinterpret_cast<float4*>(&g_nrm[((cp * 8 + threadIdx.x) * 16 + rt) * 4]) =
          make_float4(__uint_as_float(s_red[threadIdx.x * 2]), __uint_as_float(s_red[threadIdx.x * 2 + 1]), __uint_as_float(s_red[16]), 0.f);
    }
  } else {
    asm volatile("bar.sync 1, 256;" ::: "memory");
    float* dst = g_kvpart + ((size_t)rt * NH + cp * 8) * 384 + threadIdx.x;
    const float* base = reinterpret_cast<const float*>(smem_gen);
#pragma unroll
    for (int i = 0; i < 12; i++) {
      const int h0 = (i / 3) * 2, r = i % 3;
      const bool second = r == 2 || (r == 1 && threadIdx.x >= 128);
      const int e = (int)threadIdx.x + r * 256 - (second ? 384 : 0);
      const float* src = base + (second ? K1_SLOT_KB(h0 + 1) : K1_SLOT_KB(h0)) * 4096 + e;
      float sum = 0.f;
#pragma unroll
      for (int w = 0; w < 8; w++) sum += src[(w >> 2) * 2048 + (w & 3) * 384];
      dst[i * 256] = sum;
    }
  }
}

__global__ void __launch_bounds__(384, 1)
qkv_gemm_kernel(const __grid_constant__ CUtensorMap mxA, const __grid_constant__ CUtensorMap mxB,
                const __grid_constant__ CUtensorMap mwA, const __grid_constant__ CUtensorMap mwB) {
  extern __shared__ uint8_t smem_raw[];
  const uint32_t sbase = (smem_u32(smem_raw) + 1023) & ~1023u;
  uint8_t* smem_gen = smem_raw + (sbase - smem_u32(smem_raw));
  const uint32_t bar_full = sbase + K1_BAR_OFF;
  const uint32_t bar_empty = bar_full + 8 * K1_STAGES;
  uint32_t* s_red = reinterpret_cast<uint32_t*>(smem_gen + K1_BAR_OFF + 64);

  const int rank = blockIdx.x & 1;
  const int pair = blockIdx.x >> 1;
  const int branch = pair >> 5;
  const int rp = (pair & 31) >> 2;
  const int cp = pair & 3;
  const int rt = rp * 2 + rank;
  const int warp = threadIdx.x >> 5;
  if (threadIdx.x == 0) { PROF_G(0, 30); PROF_T(0, 0); }
  const CUtensorMap* mx = branch ? &mxA : &mxB;
  const CUtensorMap* mw = branch ? &mwA : &mwB;

  if (threadIdx.x == 256) {
    asm volatile("prefetch.tensormap [%0];" ::"l"(mx) : "memory");
    asm volatile("prefetch.tensormap [%0];" ::"l"(mw) : "memory");
    for (int i = 0; i < K1_STAGES; i++) {
      mbar_init(bar_full + 8 * i, 1);
      mbar_init(bar_empty + 8 * i, 4);
    }
    fence_barrier_init();
    fence_proxy_async();
    for (int kb = 0; kb < K1_STAGES; kb++) mbar_expect_tx(bar_full + 8 * kb, 16384 + K1_W_BYTES);
    tma_load_2d(sbase, mx, 0, rt * 128, bar_full);
    for (int p = 0; p < 3; p++)
      for (int hf = 0; hf < 2; hf++)
        tma_load_2d(sbase + K1_X_BYTES + p * 8192 + hf * 4096, mw, p * 512 + cp * 128, hf * 32, bar_full);
  }
  pdl_launch_dependents();
  if (threadIdx.x < 32) s_red[threadIdx.x] = 0;
  __syncthreads();
  cluster_sync_relaxed();
  if (threadIdx.x == 0) PROF_T(0, 1);

  if (warp >= 8) {
    asm volatile("setmaxnreg.dec.sync.aligned.u32 40;");
    if (threadIdx.x == 256) {
      for (int g = K1_W0_LOCAL ? 1 : 0; g < 16; g++) {
        const int s = g % K1_STAGES;
        const int kb = g & 7;
        if (g >= K1_STAGES) {
          mbar_wait(bar_empty + 8 * s, ((g / K1_STAGES) - 1) & 1);
          mbar_expect_tx(bar_full + 8 * s, (g < 8 ? 16384 : 0) + K1_W_BYTES);
        }
        if (g > 0 && g < 8) tma_load_2d(sbase + kb * 16384, mx, kb * 64, rt * 128, bar_full + 8 * s);
        const int h0 = cp * 8 + (g >> 3) * 4;
        const uint32_t st = sbase + K1_X_BYTES + s * K1_W_BYTES + rank * 4096;
#pragma unroll
        for (int p = 0; p < 3; p++)
          tma_load_2d_mc(st + p * 8192, mw, p * 512 + h0 * 16, kb * 64 + rank * 32, bar_full + 8 * s, (uint16_t)3);
      }
    }
    __syncwarp();
    cluster_sync_relaxed();
  } else {
    asm volatile("setmaxnreg.inc.sync.aligned.u32 232;");
    if (branch == 0) qkv_consumer<false>(sbase, smem_gen, s_red, cp, rt);
    else qkv_consumer<true>(sbase, smem_gen, s_red, cp, rt);
    if (threadIdx.x == 0) PROF_T(0, 11);
    __syncwarp();
    cluster_sync_relaxed();
    if (threadIdx.x == 0) { PROF_T(0, 12); PROF_G(0, 31); }
  }
}

constexpr int K2_SMEM = KV_HEAD_BYTES + 1024 + 256;

#define ATT_NPOLY 19
#define ATT_CH 8
#define ATT_D 1
#define PRO_MODE 1
#define STAGGER 0
#define K2_G0_CPASYNC 0
#define STAG_MODE 0
#define CONST_SMID 0
#define ATT_STRUCT 1
#define ATT_PIN 0
#define ATT_GM 1
#define ATT_DEG 2
struct ExpC {
  uint32_t k3c00, kmask, seven, c3;
};
__device__ __forceinline__ uint32_t hfma2(uint32_t a, uint32_t b, uint32_t c) {
  uint32_t r;
  asm("fma.rn.f16x2 %0, %1, %2, %3;" : "=r"(r) : "r"(a), "r"(b), "r"(c));
  return r;
}
__device__ __forceinline__ uint32_t exp2_poly_pair(float t0, float t1, const ExpC& c) {
  uint32_t u;
  asm("prmt.b32 %0, %1, %2, 0x5410;" : "=r"(u) : "r"(__float_as_uint(t0)), "r"(__float_as_uint(t1)));
  uint32_t m;
  asm("lop3.b32 %0, %1, 0x03FF03FF, %2, 0xEA;" : "=r"(m) : "r"(u), "r"(c.k3c00));
  uint32_t p = hfma2(m, c.c3, 0xa385a385u);
  p = hfma2(p, m, 0x4ad64ad7u);
  uint32_t mu;
  asm("lop3.b32 %0, %1, 0xFC00FC00, %2, 0xEA;" : "=r"(mu) : "r"(u), "r"(c.kmask));
  uint32_t r;
  asm("{.reg .b32 t; shf.r.wrap.b32 t, %1, %2, 3; add.u32 %0, t, %3;}" : "=r"(r) : "r"(mu), "r"(c.seven), "r"(p));
  return r;
}
__device__ __forceinline__ float gadd(float x, float M, uint32_t g) {
  float r = x;
  asm("{.reg .pred p; setp.ne.b32 p, %2, -1; @p add.f32 %0, %0, %1;}" : "+f"(r) : "f"(M), "r"(g));
  return r;
}
__device__ __forceinline__ float gex2(float x, uint32_t g) {
  float r = x;
  asm("{.reg .pred p; setp.ne.b32 p, %1, -1; @p ex2.approx.ftz.f32 %0, %0;}" : "+f"(r) : "r"(g));
  return r;
}
#define ATT_PAT 0
__host__ __device__ constexpr bool is_poly(int i, int npoly) {
  return ATT_PAT == 0   ? ((i + 1) * npoly / 32) != (i * npoly / 32)
         : ATT_PAT == 1 ? ((32 - i) * npoly / 32) != ((31 - i) * npoly / 32)
         : ATT_PAT == 2 ? ((i & 7) >= 8 - (((i / 8 + 1) * 8) * npoly / 32 - ((i / 8) * 8) * npoly / 32))
                        : ((i & 7) < (((i / 8 + 1) * 8) * npoly / 32 - ((i / 8) * 8) * npoly / 32));
}
template <int NPOLY, int NPAIR, int CH, int D, bool G0 = false>
__device__ __forceinline__ void exp_tile(const float (&s)[2 * NPAIR], uint32_t (&p)[NPAIR], const ExpC& c, uint32_t g0 = 0) {
#pragma unroll
  for (int i = 0; i < NPAIR; i++) {
    const bool isPoly = is_poly(i, NPOLY);
    const int ch = i / CH;
    const bool gated = ch >= D || G0;
    int gi = (ch - D) * CH + CH - 1;
    if (ch >= D) {
      while (gi > (ch - D) * CH && !is_poly(gi, NPOLY)) gi--;
    }
    const uint32_t g = ch >= D ? p[gi] : g0;
    if (!isPoly) {
      if (gated && ATT_GM) p[i] = pack_bf16(gex2(s[2 * i], g), gex2(s[2 * i + 1], g));
      else p[i] = pack_bf16(ex2f(s[2 * i]), ex2f(s[2 * i + 1]));
    } else {
      if (gated) p[i] = exp2_poly_pair(gadd(s[2 * i], 12329.f, g), gadd(s[2 * i + 1], 12329.f, g), c);
      else p[i] = exp2_poly_pair(s[2 * i] + 12329.f, s[2 * i + 1] + 12329.f, c);
    }
  }
}

__device__ __forceinline__ void store_o(__nv_bfloat16* o, int row0, int head, int lane, const uint32_t (&r)[4]) {
  const int g = lane >> 2, t = lane & 3;
  uint32_t* p0 = reinterpret_cast<uint32_t*>(o + (size_t)(row0 + g) * DM + head * 16) + t;
  uint32_t* p1 = reinterpret_cast<uint32_t*>(o + (size_t)(row0 + g + 8) * DM + head * 16) + t;
  p0[0] = r[0];
  p1[0] = r[1];
  p0[4] = r[2];
  p1[4] = r[3];
}

template <int NPOLY, int LO, int HI, int CH>
__device__ __forceinline__ void exp_range(const float (&s)[32], uint32_t (&p)[16], const ExpC& c) {
#pragma unroll
  for (int i = LO; i < HI; i++) {
    const bool isPoly = is_poly(i, NPOLY);
    const int ch = (i - LO) / CH;
    const bool gated = ch >= 1;
    int gi = LO + (ch - 1) * CH + CH - 1;
    if (gated) {
      while (gi > LO + (ch - 1) * CH && !is_poly(gi, NPOLY)) gi--;
    }
    const uint32_t g = gated ? p[gi] : 0;
    if (!isPoly) {
      if (gated && ATT_GM) p[i] = pack_bf16(gex2(s[2 * i], g), gex2(s[2 * i + 1], g));
      else p[i] = pack_bf16(ex2f(s[2 * i]), ex2f(s[2 * i + 1]));
    } else {
      if (gated) p[i] = exp2_poly_pair(gadd(s[2 * i], 12329.f, g), gadd(s[2 * i + 1], 12329.f, g), c);
      else p[i] = exp2_poly_pair(s[2 * i] + 12329.f, s[2 * i + 1] + 12329.f, c);
    }
  }
}

__device__ __forceinline__ void kv_fetch_piece(uint32_t sbase, uint32_t bar, int piece) {
  const uint8_t* img = reinterpret_cast<const uint8_t*>(g_kv) + (size_t)(blockIdx.x >> 2) * KV_HEAD_BYTES;
  const int g = piece >> 1, isv = piece & 1;
  const int e0 = g == 0 ? 0 : (isv ? 256 : 320) + (g - 1) * 512;
  const int e1 = g == 3 ? 2048 : (isv ? 256 : 320) + g * 512;
  const int bytes = (e1 - e0) * (isv ? 48 : 32);
  const int off = isv ? KV_K_BYTES + e0 * 48 : e0 * 32;
  mbar_expect_tx(bar + 8 * g, bytes);
  bulk_load(sbase + off, img + off, bytes, bar + 8 * g);
}

__device__ __forceinline__ void safe_exp(float (&s)[32], uint32_t (&p)[16], float (&o)[12], float& m0, float& m1) {
#pragma unroll
  for (int i = 0; i < 16; i++) {
    const uint32_t r = pack_bf16(s[2 * i], s[2 * i + 1]);
    s[2 * i] = bf_lo(r) * QSCALE;
    s[2 * i + 1] = bf_hi(r) * QSCALE;
  }
  float x0 = s[0], x1 = s[2];
#pragma unroll
  for (int i = 0; i < 8; i++) {
    x0 = fmaxf(x0, fmaxf(s[4 * i], s[4 * i + 1]));
    x1 = fmaxf(x1, fmaxf(s[4 * i + 2], s[4 * i + 3]));
  }
  x0 = fmaxf(x0, __shfl_xor_sync(0xffffffffu, x0, 1));
  x1 = fmaxf(x1, __shfl_xor_sync(0xffffffffu, x1, 1));
  x0 = fmaxf(x0, __shfl_xor_sync(0xffffffffu, x0, 2));
  x1 = fmaxf(x1, __shfl_xor_sync(0xffffffffu, x1, 2));
  const float n0 = fmaxf(m0, x0), n1 = fmaxf(m1, x1);
  const float c0 = ex2f(m0 - n0), c1 = ex2f(m1 - n1);
  m0 = n0;
  m1 = n1;
#pragma unroll
  for (int i = 0; i < 3; i++) {
    o[4 * i] *= c0;
    o[4 * i + 1] *= c0;
    o[4 * i + 2] *= c1;
    o[4 * i + 3] *= c1;
  }
#pragma unroll
  for (int i = 0; i < 8; i++) {
    p[2 * i] = pack_bf16(ex2f(s[4 * i] - n0), ex2f(s[4 * i + 1] - n0));
    p[2 * i + 1] = pack_bf16(ex2f(s[4 * i + 2] - n1), ex2f(s[4 * i + 3] - n1));
  }
}

__device__ __forceinline__ void attn_step(float (&sx)[32], float (&sy)[32], float (&o)[12], const uint4& qf, uint64_t dK, uint64_t dV,
                                          const ExpC& ec) {
  uint32_t pa[16], pb[16];
  wg_fence();
  wgmma_rs_n64_z(sy, qf.x, qf.y, qf.z, qf.w, dK + 128);
  wg_commit();
  exp_tile<ATT_NPOLY, 16, ATT_CH, ATT_D>(sx, pa, ec);
  wg_fence();
  wgmma_rs_n24_tb(o, pa[12], pa[13], pa[14], pa[15], dV + 3 * 48, 1);
  wg_commit();
  wg_wait<1>();
  fence_regs(sy);
  exp_tile<ATT_NPOLY, 16, ATT_CH, ATT_D>(sy, pb, ec);
  wg_fence();
#pragma unroll
  for (int k = 0; k < 3; k++) wgmma_rs_n24_tb(o, pa[4 * k], pa[4 * k + 1], pa[4 * k + 2], pa[4 * k + 3], dV + k * 48, 1);
#pragma unroll
  for (int k = 0; k < 4; k++) wgmma_rs_n24_tb(o, pb[4 * k], pb[4 * k + 1], pb[4 * k + 2], pb[4 * k + 3], dV + (4 + k) * 48, 1);
  wgmma_rs_n64_z(sy, qf.x, qf.y, qf.z, qf.w, dK + 256);
  wg_commit();
  wg_wait<0>();
  fence_regs(sy);
}

template <bool SAFE>
__device__ __forceinline__ void attn_tile(uint64_t dK, uint64_t dV, uint32_t bar, uint4 qf, const ExpC& ec, uint32_t (&outp)[4]) {
  float o[12];
#pragma unroll
  for (int i = 0; i < 12; i++) asm volatile("mov.f32 %0, 0f00000000;" : "=f"(o[i]));
  if (!SAFE) {
    qf.x = pack_bf16(bf_lo(qf.x) * QSCALE, bf_hi(qf.x) * QSCALE);
    qf.y = pack_bf16(bf_lo(qf.y) * QSCALE, bf_hi(qf.y) * QSCALE);
    qf.z = pack_bf16(bf_lo(qf.z) * QSCALE, bf_hi(qf.z) * QSCALE);
    qf.w = pack_bf16(bf_lo(qf.w) * QSCALE, bf_hi(qf.w) * QSCALE);
    float s0[32], s1[32];
    wg_fence();
    wgmma_rs_n64_z(s0, qf.x, qf.y, qf.z, qf.w, dK);
    wg_commit();
    wg_wait<0>();
    fence_regs(s0);
#pragma unroll 1
    for (int p = 0; p < 8; p++) {
      if (p & 1) mbar_wait(bar + 8 * min((p + 1) >> 1, 3), 0);
      attn_step(s0, s1, o, qf, dK, dV, ec);
      attn_step(s1, s0, o, qf, dK + 256, dV + 384, ec);
      dK += 512;
      dV += 768;
    }
    wg_wait<0>();
  } else {
    float m0 = -INFINITY, m1 = -INFINITY;
#pragma unroll 1
    for (int j = 0; j < 32; j++) {
      if (j == 4) { mbar_wait(bar + 8, 0); mbar_wait(bar + 16, 0); mbar_wait(bar + 24, 0); }
      float s[32];
      uint32_t p[16];
      wg_fence();
      wgmma_rs_n64_z(s, qf.x, qf.y, qf.z, qf.w, dK);
      wg_commit();
      wg_wait<0>();
      fence_regs(s);
      safe_exp(s, p, o, m0, m1);
      wg_fence();
#pragma unroll
      for (int k = 0; k < 4; k++) wgmma_rs_n24_tb(o, p[4 * k], p[4 * k + 1], p[4 * k + 2], p[4 * k + 3], dV + k * 48, 1);
      wg_commit();
      wg_wait<0>();
      fence_regs(o);
      dK += 128;
      dV += 192;
    }
  }
  fence_regs(o);
  const float r0 = 1.0f / o[8], r1 = 1.0f / o[10];
  outp[0] = pack_bf16(o[0] * r0, o[1] * r0);
  outp[1] = pack_bf16(o[2] * r1, o[3] * r1);
  outp[2] = pack_bf16(o[4] * r0, o[5] * r0);
  outp[3] = pack_bf16(o[6] * r1, o[7] * r1);
}

__device__ __forceinline__ void linear_attn_cta(uint8_t* smem_raw, uint32_t sbase, const CUtensorMap* mo16, int cta) {
  const int warp = threadIdx.x >> 5, lane = threadIdx.x & 31;
  const int hg = warp & 1;
  const uint4* qp = g_qfrag + (size_t)(NH + cta * 8 + hg * 4) * 32 * 128 + lane;
  auto qaddr = [&](int i) {
    const int blk16 = i * 8 + (warp >> 1);
    return qp + (blk16 >> 2) * 128 + (blk16 & 3) * 32;
  };
  uint4 q[4];
#pragma unroll
  for (int h = 0; h < 4; h++) q[h] = qaddr(0)[h * 32 * 128];
  float* red = reinterpret_cast<float*>(smem_raw + (sbase - smem_u32(smem_raw)) + 131072);
  {
    const float* src = g_kvpart + (size_t)cta * 8 * 384;
    float sum[6];
#pragma unroll
    for (int i = 0; i < 6; i++) sum[i] = 0.f;
#pragma unroll
    for (int r = 0; r < 16; r++) {
#pragma unroll
      for (int i = 0; i < 6; i++) sum[i] += src[(size_t)r * NH * 384 + threadIdx.x + i * 512];
    }
#pragma unroll
    for (int i = 0; i < 6; i++) red[threadIdx.x + i * 512] = round_bf16(sum[i]);
  }
  __syncthreads();
  if (threadIdx.x == 0) PROF_T(1, 1);
  uint32_t bf[4][6];
  {
    const int g = lane >> 2, t = lane & 3;
#pragma unroll
    for (int h = 0; h < 4; h++) {
#pragma unroll
      for (int f = 0; f < 6; f++) {
        const int blk = f >> 1, half = f & 1;
        const int e = (blk == 2) ? 0 : g;
        const int d = 2 * t + 8 * half;
        const int base = (hg * 4 + h) * 384 + (blk * 4 + half * 2 + (e & 1)) * 32 + (e >> 1);
        bf[h][f] = pack_bf16(red[base + (d & 7) * 4], red[base + ((d + 1) & 7) * 4]);
      }
    }
  }
  if (threadIdx.x == 0) PROF_T(1, 2);
  const uint32_t stg = sbase + warp * 8192;
#pragma unroll 1
  for (int i = 0; i < 16; i++) {
    uint4 qc[4];
#pragma unroll
    for (int h = 0; h < 4; h++) qc[h] = q[h];
    if (i + 1 < 16) {
#pragma unroll
      for (int h = 0; h < 4; h++) q[h] = qaddr(i + 1)[h * 32 * 128];
    }
    const uint32_t buf = stg + (i & 3) * 2048;
    if (i >= 4) {
      if (lane == 0) asm volatile("cp.async.bulk.wait_group.read 3;" ::: "memory");
      __syncwarp();
    }
#pragma unroll
    for (int h = 0; h < 4; h++) {
      float n0[4] = {0, 0, 0, 0}, n1[4] = {0, 0, 0, 0}, dn[4] = {0, 0, 0, 0};
      hmma(n0, qc[h].x, qc[h].y, qc[h].z, qc[h].w, bf[h][0], bf[h][1]);
      hmma(n1, qc[h].x, qc[h].y, qc[h].z, qc[h].w, bf[h][2], bf[h][3]);
      hmma(dn, qc[h].x, qc[h].y, qc[h].z, qc[h].w, bf[h][4], bf[h][5]);
      const float d0 = __fdividef(1.0f, dn[0] + 1e-6f), d1 = __fdividef(1.0f, dn[2] + 1e-6f);
      const uint32_t r0 = pack_bf16(n0[0] * d0, n0[1] * d0);
      const uint32_t r1 = pack_bf16(n0[2] * d1, n0[3] * d1);
      const uint32_t r2 = pack_bf16(n1[0] * d0, n1[1] * d0);
      const uint32_t r3 = pack_bf16(n1[2] * d1, n1[3] * d1);
      const int row = lane & 15;
      const int chunk = h * 2 + (lane >> 4);
      const uint32_t addr = buf + row * 128 + ((chunk ^ (row & 7)) << 4);
      asm volatile("stmatrix.sync.aligned.m8n8.x4.shared.b16 [%0], {%1,%2,%3,%4};" ::"r"(addr), "r"(r0), "r"(r1), "r"(r2), "r"(r3)
                   : "memory");
    }
    fence_proxy_async();
    __syncwarp();
    if (lane == 0) {
      tma_store_2d(mo16, buf, cta * 128 + hg * 64, (i * 8 + (warp >> 1)) * 16);
      asm volatile("cp.async.bulk.commit_group;" ::: "memory");
    }
  }
  if (threadIdx.x == 0) PROF_T(1, 3);
  if (lane == 0) asm volatile("cp.async.bulk.wait_group 0;" ::: "memory");
}

__global__ void __launch_bounds__(512, 1)
attn_kernel(const __grid_constant__ CUtensorMap mo16, const uint8_t* __restrict__ woA, const uint8_t* __restrict__ woB) {
  extern __shared__ uint8_t smem_raw[];
  const uint32_t sbase = (smem_u32(smem_raw) + 1023) & ~1023u;
  const uint32_t bar = sbase + KV_HEAD_BYTES;
  if (threadIdx.x == 0) { PROF_G(1, 30); PROF_T(1, 0); }
  if (threadIdx.x == 0) {
    for (int i = 0; i < 4; i++) mbar_init(bar + 8 * i, 2);
    asm volatile("st.shared.v4.u32 [%0], {%1, %2, %3, %4};" ::"r"(bar + 64), "r"(0x3C003C00u), "r"(0x00070000u), "r"(7u),
                 "r"(ATT_DEG == 3 ? 0x2cfd2cfdu : 0x35623562u)
                 : "memory");
    fence_barrier_init();
    fence_proxy_async();
  }
  __syncthreads();
  pdl_launch_dependents();
  if (blockIdx.x >= 128 && threadIdx.x < 16) {
    const int i = (blockIdx.x - 128) * 16 + threadIdx.x;
    const uint8_t* p = (i < 32 ? woA : woB) + (size_t)(i & 31) * 16384;
    asm volatile("cp.async.bulk.prefetch.L2.global [%0], %1;" ::"l"(p), "r"(16384) : "memory");
  }
  if (blockIdx.x >= 128) {
    pdl_wait();
    linear_attn_cta(smem_raw, sbase, &mo16, blockIdx.x - 128);
    if (threadIdx.x == 0) { PROF_T(1, 5); PROF_G(1, 31); }
    return;
  }
  const int head = blockIdx.x >> 2, qb = blockIdx.x & 3;
  const int lane = threadIdx.x & 31;
  const int wg = __shfl_sync(0xffffffffu, threadIdx.x >> 7, 0), warp = __shfl_sync(0xffffffffu, (threadIdx.x >> 5) & 3, 0);
  ExpC ec;
  asm volatile("ld.volatile.shared.v4.u32 {%0, %1, %2, %3}, [%4];" : "=r"(ec.k3c00), "=r"(ec.kmask), "=r"(ec.seven), "=r"(ec.c3) : "r"(bar + 64));
  const uint64_t dK = mkdesc(sbase, 128, 256, 0);
  const uint64_t dV = mkdesc(sbase + KV_K_BYTES, 384, 128, 0);
  pdl_wait();
  if (threadIdx.x == 0) { PROF_T(1, 7); PROF_G(1, 29); }
  if (threadIdx.x == 0) {
#pragma unroll
    for (int piece = 0; piece < 8; piece++) kv_fetch_piece(sbase, bar, piece);
  }
  uint4 qnext = g_qfrag[(head * 32 + qb * 8 + wg * 2) * 128 + (threadIdx.x & 127)];
  bool safe_path;
  {
    float4 n = make_float4(0.f, 0.f, 0.f, 0.f);
    if (lane < 16) n = *reinterpret_cast<const float4*>(&g_nrm[(head * 16 + lane) * 4]);
    uint32_t qm = ((lane >> 2) == qb) ? __float_as_uint(n.x) : 0u;
    qm = __reduce_max_sync(0xffffffffu, qm);
    const uint32_t km = __reduce_max_sync(0xffffffffu, __float_as_uint(n.y));
    const uint32_t vm = __reduce_max_sync(0xffffffffu, __float_as_uint(n.z));
    const float b2 = __uint_as_float(qm) * (QSCALE * QSCALE) * __uint_as_float(km) * 1.02f;
    const float vmax = __uint_as_float(vm);
    const bool ok = (b2 <= 21.5f * 21.5f) && (vmax <= 1.0e24f) && (vmax >= 1.0e-18f || vmax == 0.f);
    safe_path = !ok;
  }
  mbar_wait(bar, 0);
#pragma unroll 1
  for (int t = 0; t < 2; t++) {
    const int tile64 = qb * 8 + wg * 2 + t;
    const uint4 qf = qnext;
    if (t == 0) qnext = g_qfrag[(head * 32 + tile64 + 1) * 128 + (threadIdx.x & 127)];
    uint32_t r[4];
    if (threadIdx.x == 0) PROF_T(1, 1 + t);
    if (!safe_path) attn_tile<false>(dK, dV, bar, qf, ec, r);
    else attn_tile<true>(dK, dV, bar, qf, ec, r);
    store_o(g_o + (size_t)S_LEN * DM, tile64 * 64 + warp * 16, head, lane, r);
  }
  if (threadIdx.x == 0) { PROF_T(1, 5); PROF_G(1, 31); }
}

#define K3_WPRE 2
constexpr int K3_STAGES = 5;
constexpr int K3_W_BYTES = 8 * 16384;
constexpr int K3_BAR_OFF = K3_W_BYTES + K3_STAGES * 16384;
constexpr int K3_SMEM = K3_BAR_OFF + 256 + 1024;

__global__ void __launch_bounds__(288, 1)
out_gemm_kernel(const __grid_constant__ CUtensorMap mo, const __grid_constant__ CUtensorMap mwA,
                const __grid_constant__ CUtensorMap mwB, const __grid_constant__ CUtensorMap mout) {
  extern __shared__ uint8_t smem_raw[];
  const uint32_t sbase = (smem_u32(smem_raw) + 1023) & ~1023u;
  const uint32_t bar_full = sbase + K3_BAR_OFF;
  const uint32_t bar_empty = bar_full + 8 * K3_STAGES;
  const uint32_t bar_w = bar_empty + 8 * K3_STAGES;
  const int branch = blockIdx.x >> 6;
  const int rt = (blockIdx.x & 63) >> 2;
  const int ct = blockIdx.x & 3;
  const int warp = threadIdx.x >> 5;
  if (threadIdx.x == 0) { PROF_G(2, 30); PROF_T(2, 0); }
  if (threadIdx.x == 256) {
    const CUtensorMap* mw = branch ? &mwB : &mwA;
    asm volatile("prefetch.tensormap [%0];" ::"l"(mw) : "memory");
    asm volatile("prefetch.tensormap [%0];" ::"l"(&mo) : "memory");
    asm volatile("prefetch.tensormap [%0];" ::"l"(&mout) : "memory");
    for (int i = 0; i < K3_STAGES; i++) {
      mbar_init(bar_full + 8 * i, 1);
      mbar_init(bar_empty + 8 * i, 2);
    }
    for (int i = 0; i < 8; i++) mbar_init(bar_w + 8 * i, 1);
    fence_barrier_init();
    fence_proxy_async();
    for (int kb = 0; kb < K3_WPRE; kb++) {
      mbar_expect_tx(bar_w + 8 * kb, 16384);
      tma_load_2d(sbase + kb * 16384, mw, ct * 128, kb * 64, bar_w + 8 * kb);
      tma_load_2d(sbase + kb * 16384 + 8192, mw, ct * 128 + 64, kb * 64, bar_w + 8 * kb);
    }
  }
  __syncthreads();
  if (warp == 8) {
    if ((threadIdx.x & 31) == 0) {
      const CUtensorMap* mw = branch ? &mwB : &mwA;
      pdl_wait();
      PROF_T(2, 1);
      for (int kb = 0; kb < 8; kb++) {
        const int s = kb % K3_STAGES;
        if (kb >= K3_STAGES) mbar_wait(bar_empty + 8 * s, ((kb / K3_STAGES) - 1) & 1);
        mbar_expect_tx(bar_full + 8 * s, 16384);
        tma_load_2d(sbase + K3_W_BYTES + s * 16384, &mo, kb * 64, branch * S_LEN + rt * 128, bar_full + 8 * s);
        const int kw = kb + K3_WPRE;
        if (kw < 8) {
          mbar_expect_tx(bar_w + 8 * kw, 16384);
          tma_load_2d(sbase + kw * 16384, mw, ct * 128, kw * 64, bar_w + 8 * kw);
          tma_load_2d(sbase + kw * 16384 + 8192, mw, ct * 128 + 64, kw * 64, bar_w + 8 * kw);
        }
      }
    }
  } else {
    const int wg = warp >> 2;
    float acc[64];
    for (int kb = 0; kb < 8; kb++) {
      const int s = kb % K3_STAGES;
      mbar_wait(bar_w + 8 * kb, 0);
      mbar_wait(bar_full + 8 * s, (kb / K3_STAGES) & 1);
      if (threadIdx.x == 0) PROF_T(2, 2 + kb);
      const uint64_t dA = mkdesc(sbase + K3_W_BYTES + s * 16384 + wg * 8192, 16, 1024, 1);
      const uint64_t dB = mkdesc(sbase + kb * 16384, 8192, 1024, 1);
      wg_fence();
#pragma unroll
      for (int k = 0; k < 4; k++) wgmma_ss_n128_tb(acc, dA + k * 2, dB + k * 128, (kb | k) != 0);
      wg_commit();
      if (kb > 0) {
        wg_wait<1>();
        if ((threadIdx.x & 127) == 0) mbar_arrive(bar_empty + 8 * ((kb - 1) % K3_STAGES));
      }
    }
    wg_wait<0>();
    fence_regs(acc);
    if (threadIdx.x == 0) PROF_T(2, 10);
    const uint32_t stg = sbase + K3_W_BYTES + wg * 8192;
    const int lane = threadIdx.x & 31;
    const int rloc = (warp & 3) * 16 + (lane & 15);
#pragma unroll
    for (int c16 = 0; c16 < 8; c16++) {
      const float* a = &acc[c16 * 8];
      const uint32_t r0 = pack_bf16(a[0], a[1]), r1 = pack_bf16(a[2], a[3]), r2 = pack_bf16(a[4], a[5]), r3 = pack_bf16(a[6], a[7]);
      const int chunk = (c16 & 3) * 2 + (lane >> 4);
      const uint32_t addr = stg + (c16 >> 2) * 16384 + rloc * 128 + ((chunk ^ (rloc & 7)) << 4);
      asm volatile("stmatrix.sync.aligned.m8n8.x4.shared.b16 [%0], {%1,%2,%3,%4};" ::"r"(addr), "r"(r0), "r"(r1), "r"(r2), "r"(r3)
                   : "memory");
    }
    fence_proxy_async();
    asm volatile("bar.sync %0, 128;" ::"r"(2 + wg) : "memory");
    if ((threadIdx.x & 127) == 0) {
      tma_store_2d(&mout, stg, branch * DM + ct * 128, rt * 128 + wg * 64);
      tma_store_2d(&mout, stg + 16384, branch * DM + ct * 128 + 64, rt * 128 + wg * 64);
      asm volatile("cp.async.bulk.commit_group;" ::: "memory");
      asm volatile("cp.async.bulk.wait_group.read 0;" ::: "memory");
      if (threadIdx.x == 0) { PROF_T(2, 12); PROF_G(2, 31); }
    }
  }
}

typedef CUresult (*EncodeFn)(CUtensorMap*, CUtensorMapDataType, cuuint32_t, void*, const cuuint64_t*, const cuuint64_t*,
                             const cuuint32_t*, const cuuint32_t*, CUtensorMapInterleave, CUtensorMapSwizzle,
                             CUtensorMapL2promotion, CUtensorMapFloatOOBfill);

void make_map(EncodeFn enc, CUtensorMap* m, const void* ptr, uint64_t inner, uint64_t outer, uint32_t box_inner, uint32_t box_outer) {
  cuuint64_t dims[2] = {inner, outer};
  cuuint64_t strides[1] = {inner * 2};
  cuuint32_t box[2] = {box_inner, box_outer};
  cuuint32_t es[2] = {1, 1};
  enc(m, CU_TENSOR_MAP_DATA_TYPE_BFLOAT16, 2, const_cast<void*>(ptr), dims, strides, box, es, CU_TENSOR_MAP_INTERLEAVE_NONE,
      CU_TENSOR_MAP_SWIZZLE_128B, CU_TENSOR_MAP_L2_PROMOTION_L2_256B, CU_TENSOR_MAP_FLOAT_OOB_FILL_NONE);
}

struct HostState {
  bool init;
  const void* key[7];
  CUtensorMap mxA, mxB, mwA, mwB, mo, mo16, mwoA, mwoB, mout;
};
HostState g_hs;

}

extern "C" void kernel_launch(void* const* d_in, const int* in_sizes, int n_in, void* d_out, int out_size) {
  (void)in_sizes; (void)n_in; (void)out_size;
  HostState& hs = g_hs;
  bool same = hs.init && hs.key[6] == d_out;
  for (int i = 0; i < 6 && same; i++) same = hs.key[i] == d_in[i];
  if (!same) {
    void* fn = nullptr;
    cudaDriverEntryPointQueryResult qr;
    cudaGetDriverEntryPoint("cuTensorMapEncodeTiled", &fn, cudaEnableDefault, &qr);
    EncodeFn enc = (EncodeFn)fn;
    void* go = nullptr;
    cudaGetSymbolAddress(&go, g_o);
    make_map(enc, &hs.mxA, d_in[0], 512, 2048, 64, 128);
    make_map(enc, &hs.mwA, d_in[1], 1536, 512, 64, 32);
    make_map(enc, &hs.mwoA, d_in[2], 512, 512, 64, 64);
    make_map(enc, &hs.mxB, d_in[3], 512, 2048, 64, 128);
    make_map(enc, &hs.mwB, d_in[4], 1536, 512, 64, 32);
    make_map(enc, &hs.mwoB, d_in[5], 512, 512, 64, 64);
    make_map(enc, &hs.mo, go, 512, 4096, 64, 128);
    make_map(enc, &hs.mo16, go, 512, 4096, 64, 16);
    make_map(enc, &hs.mout, d_out, 1024, 2048, 64, 64);
    cudaFuncSetAttribute(qkv_gemm_kernel, cudaFuncAttributeMaxDynamicSharedMemorySize, K1_SMEM);
    cudaFuncSetAttribute(attn_kernel, cudaFuncAttributeMaxDynamicSharedMemorySize, K2_SMEM);
    cudaFuncSetAttribute(out_gemm_kernel, cudaFuncAttributeMaxDynamicSharedMemorySize, K3_SMEM);
    for (int i = 0; i < 6; i++) hs.key[i] = d_in[i];
    hs.key[6] = d_out;
    hs.init = true;
  }
  cudaStream_t st = cudaStreamPerThread;
  {
    cudaLaunchConfig_t cfg = {};
    cfg.gridDim = dim3(128);
    cfg.blockDim = dim3(384);
    cfg.dynamicSmemBytes = K1_SMEM;
    cfg.stream = st;
    cudaLaunchAttribute at[1];
    at[0].id = cudaLaunchAttributeClusterDimension;
    at[0].val.clusterDim.x = 2;
    at[0].val.clusterDim.y = 1;
    at[0].val.clusterDim.z = 1;
    cfg.attrs = at;
    cfg.numAttrs = 1;
    cudaLaunchKernelEx(&cfg, qkv_gemm_kernel, hs.mxA, hs.mxB, hs.mwA, hs.mwB);
  }
  {
    cudaLaunchConfig_t cfg = {};
    cfg.gridDim = dim3(132);
    cfg.blockDim = dim3(512);
    cfg.dynamicSmemBytes = K2_SMEM;
    cfg.stream = st;
    cudaLaunchAttribute at[1];
    at[0].id = cudaLaunchAttributeProgrammaticStreamSerialization;
    at[0].val.programmaticStreamSerializationAllowed = 1;
    cfg.attrs = at;
    cfg.numAttrs = 1;
    cudaLaunchKernelEx(&cfg, attn_kernel, hs.mo16, (const uint8_t*)d_in[2], (const uint8_t*)d_in[5]);
    cfg.gridDim = dim3(128);
    cfg.blockDim = dim3(288);
    cfg.dynamicSmemBytes = K3_SMEM;
    cudaLaunchKernelEx(&cfg, out_gemm_kernel, hs.mo, hs.mwoA, hs.mwoB, hs.mout);
  }
}
```

```cpp
#include <cuda_runtime.h>
#include <cuda_bf16.h>
#include <cuda.h>
#include <stdint.h>

namespace {

constexpr int S_LEN = 2048;
constexpr int DM = 512;
constexpr int NH = 32;

constexpr int KV_K_BYTES = 65536;
constexpr int KV_HEAD_BYTES = KV_K_BYTES + 98304;
__device__ uint4 g_qfrag[2 * NH * 32 * 128];
__device__ uint4 g_kv[NH * KV_HEAD_BYTES / 16];
__device__ float g_kvpart[16 * NH * 384];
__device__ float g_nrm[NH * 16 * 4];
__device__ __nv_bfloat16 g_o[2 * S_LEN * DM];

#define g_prof_set(k, i, v)
#define g_prof_dummy(i) true
#define PROF_T(k, i) do {} while (0)
#define PROF_G(k, i) do {} while (0)
__device__ __forceinline__ uint32_t smem_u32(const void* p) { return (uint32_t)__cvta_generic_to_shared(p); }
__device__ __forceinline__ void mbar_init(uint32_t bar, int cnt) {
  asm volatile("mbarrier.init.shared::cta.b64 [%0], %1;" ::"r"(bar), "r"(cnt) : "memory");
}
__device__ __forceinline__ void mbar_expect_tx(uint32_t bar, uint32_t bytes) {
  asm volatile("mbarrier.arrive.expect_tx.shared::cta.b64 _, [%0], %1;" ::"r"(bar), "r"(bytes) : "memory");
}
__device__ __forceinline__ void mbar_arrive(uint32_t bar) {
  asm volatile("mbarrier.arrive.shared::cta.b64 _, [%0];" ::"r"(bar) : "memory");
}
__device__ __forceinline__ void mbar_arrive_cluster(uint32_t bar, uint32_t cta) {
  asm volatile(
      "{\n.reg .b32 ra;\nmapa.shared::cluster.u32 ra, %0, %1;\n"
      "mbarrier.arrive.shared::cluster.b64 _, [ra];\n}" ::"r"(bar), "r"(cta) : "memory");
}
__device__ __forceinline__ void mbar_wait(uint32_t bar, uint32_t parity) {
  asm volatile(
      "{\n.reg .pred p;\n.reg .u32 n;\n"
      "mov.u32 n, 0;\n"
      "WAIT_LOOP:\n"
      "mbarrier.try_wait.parity.shared::cta.b64 p, [%0], %1, 0x400000;\n"
      "@p bra WAIT_DONE;\n"
      "add.u32 n, n, 1;\n"
      "setp.lt.u32 p, n, 4000000;\n"
      "@p bra WAIT_LOOP;\n"
      "trap;\n"
      "WAIT_DONE:\n}" ::"r"(bar), "r"(parity) : "memory");
}
__device__ __forceinline__ void fence_barrier_init() {
  asm volatile("fence.mbarrier_init.release.cluster;" ::: "memory");
}
__device__ __forceinline__ void fence_proxy_async() { asm volatile("fence.proxy.async.shared::cta;" ::: "memory"); }
__device__ __forceinline__ void cluster_sync_relaxed() {
  asm volatile("barrier.cluster.arrive.relaxed.aligned;\nbarrier.cluster.wait.aligned;" ::: "memory");
}
__device__ __forceinline__ void tma_load_2d(uint32_t dst, const CUtensorMap* m, int x, int y, uint32_t bar) {
  asm volatile(
      "cp.async.bulk.tensor.2d.shared::cluster.global.mbarrier::complete_tx::bytes [%0], [%1, {%3, %4}], [%2];" ::"r"(dst),
      "l"(m), "r"(bar), "r"(x), "r"(y)
      : "memory");
}
__device__ __forceinline__ void tma_load_2d_mc(uint32_t dst, const CUtensorMap* m, int x, int y, uint32_t bar, uint16_t mask) {
  asm volatile(
      "cp.async.bulk.tensor.2d.shared::cluster.global.mbarrier::complete_tx::bytes.multicast::cluster [%0], [%1, {%3, %4}], "
      "[%2], %5;" ::"r"(dst),
      "l"(m), "r"(bar), "r"(x), "r"(y), "h"(mask)
      : "memory");
}
__device__ __forceinline__ void tma_store_2d(const CUtensorMap* m, uint32_t src, int x, int y) {
  asm volatile("cp.async.bulk.tensor.2d.global.shared::cta.bulk_group [%0, {%2, %3}], [%1];" ::"l"(m), "r"(src), "r"(x),
               "r"(y)
               : "memory");
}
__device__ __forceinline__ void bulk_load(uint32_t dst, const void* src, uint32_t bytes, uint32_t bar) {
  asm volatile("cp.async.bulk.shared::cluster.global.mbarrier::complete_tx::bytes [%0], [%1], %2, [%3];" ::"r"(dst),
               "l"(src), "r"(bytes), "r"(bar)
               : "memory");
}
__device__ __forceinline__ void bulk_load_mc(uint32_t dst, const void* src, uint32_t bytes, uint32_t bar, uint16_t mask) {
  asm volatile("cp.async.bulk.shared::cluster.global.mbarrier::complete_tx::bytes.multicast::cluster [%0], [%1], %2, [%3], %4;" ::"r"(dst),
               "l"(src), "r"(bytes), "r"(bar), "h"(mask)
               : "memory");
}
__device__ __forceinline__ void pdl_launch_dependents() { asm volatile("griddepcontrol.launch_dependents;" ::: "memory"); }
__device__ __forceinline__ void pdl_wait() { asm volatile("griddepcontrol.wait;" ::: "memory"); }
__device__ __forceinline__ void wg_fence() { asm volatile("wgmma.fence.sync.aligned;" ::: "memory"); }
__device__ __forceinline__ void wg_commit() { asm volatile("wgmma.commit_group.sync.aligned;" ::: "memory"); }
template <int N>
__device__ __forceinline__ void wg_wait() {
  asm volatile("wgmma.wait_group.sync.aligned %0;" ::"n"(N) : "memory");
}
template <int M>
__device__ __forceinline__ void fence_regs(float (&r)[M]) {
#pragma unroll
  for (int i = 0; i < M; i++) asm volatile("" : "+f"(r[i])::"memory");
}
__device__ __forceinline__ uint64_t mkdesc(uint32_t addr, uint32_t lbo, uint32_t sbo, uint32_t layout) {
  return (uint64_t)((addr & 0x3FFFF) >> 4) | ((uint64_t)(lbo >> 4) << 16) | ((uint64_t)(sbo >> 4) << 32) |
         ((uint64_t)layout << 62);
}
__device__ __forceinline__ uint32_t pack_bf16(float lo, float hi) {
  uint32_t r;
  asm("cvt.rn.bf16x2.f32 %0, %1, %2;" : "=r"(r) : "f"(hi), "f"(lo));
  return r;
}
__device__ __forceinline__ float bf_lo(uint32_t v) { return __uint_as_float(v << 16); }
__device__ __forceinline__ float bf_hi(uint32_t v) { return __uint_as_float(v & 0xFFFF0000u); }
__device__ __forceinline__ float round_bf16(float x) { return bf_lo(pack_bf16(x, 0.f)); }
__device__ __forceinline__ float ex2f(float x) {
  float y;
  asm("ex2.approx.ftz.f32 %0, %1;" : "=f"(y) : "f"(x));
  return y;
}

__device__ __forceinline__ void wgmma_rs_n24_tb(float (&d)[12], uint32_t a0, uint32_t a1, uint32_t a2, uint32_t a3, uint64_t descB, int scaleD) {
  asm volatile("{\n.reg .pred p;\nsetp.ne.b32 p, %17, 0;\n"
    "wgmma.mma_async.sync.aligned.m64n24k16.f32.bf16.bf16 "
    "{%0, %1, %2, %3, %4, %5, %6, %7, %8, %9, %10, %11}, {%12, %13, %14, %15}, %16, p, 1, 1, 1;\n}\n"
    : "+f"(d[0]), "+f"(d[1]), "+f"(d[2]), "+f"(d[3]), "+f"(d[4]), "+f"(d[5]), "+f"(d[6]), "+f"(d[7]),
      "+f"(d[8]), "+f"(d[9]), "+f"(d[10]), "+f"(d[11])
    : "r"(a0), "r"(a1), "r"(a2), "r"(a3), "l"(descB), "r"(scaleD));
}
__device__ __forceinline__ void wgmma_rs_n64_z(float (&d)[32], uint32_t a0, uint32_t a1, uint32_t a2, uint32_t a3, uint64_t descB) {
  asm volatile("{\n.reg .pred p;\nsetp.ne.b32 p, %37, 0;\n"
    "wgmma.mma_async.sync.aligned.m64n64k16.f32.bf16.bf16 "
    "{%0, %1, %2, %3, %4, %5, %6, %7, %8, %9, %10, %11, %12, %13, %14, %15, %16, %17, %18, %19, %20, %21, %22, %23, %24, %25, %26, %27, %28, %29, %30, %31}, {%32, %33, %34, %35}, %36, p, 1, 1, 0;\n}\n"
    : "=f"(d[0]), "=f"(d[1]), "=f"(d[2]), "=f"(d[3]), "=f"(d[4]), "=f"(d[5]), "=f"(d[6]), "=f"(d[7]),
      "=f"(d[8]), "=f"(d[9]), "=f"(d[10]), "=f"(d[11]), "=f"(d[12]), "=f"(d[13]), "=f"(d[14]), "=f"(d[15]),
      "=f"(d[16]), "=f"(d[17]), "=f"(d[18]), "=f"(d[19]), "=f"(d[20]), "=f"(d[21]), "=f"(d[22]), "=f"(d[23]),
      "=f"(d[24]), "=f"(d[25]), "=f"(d[26]), "=f"(d[27]), "=f"(d[28]), "=f"(d[29]), "=f"(d[30]), "=f"(d[31])
    : "r"(a0), "r"(a1), "r"(a2), "r"(a3), "l"(descB), "n"(0));
}
__device__ __forceinline__ void wgmma_ss_n128_tb(float (&d)[64], uint64_t descA, uint64_t descB, int scaleD) {
  asm volatile("{\n.reg .pred p;\nsetp.ne.b32 p, %66, 0;\n"
    "wgmma.mma_async.sync.aligned.m64n128k16.f32.bf16.bf16 "
    "{%0, %1, %2, %3, %4, %5, %6, %7, %8, %9, %10, %11, %12, %13, %14, %15, %16, %17, %18, %19, %20, %21, %22, %23, %24, %25, %26, %27, %28, %29, %30, %31, %32, %33, %34, %35, %36, %37, %38, %39, %40, %41, %42, %43, %44, %45, %46, %47, %48, %49, %50, %51, %52, %53, %54, %55, %56, %57, %58, %59, %60, %61, %62, %63}, %64, %65, p, 1, 1, 0, 1;\n}\n"
    : "+f"(d[0]), "+f"(d[1]), "+f"(d[2]), "+f"(d[3]), "+f"(d[4]), "+f"(d[5]), "+f"(d[6]), "+f"(d[7]),
      "+f"(d[8]), "+f"(d[9]), "+f"(d[10]), "+f"(d[11]), "+f"(d[12]), "+f"(d[13]), "+f"(d[14]), "+f"(d[15]),
      "+f"(d[16]), "+f"(d[17]), "+f"(d[18]), "+f"(d[19]), "+f"(d[20]), "+f"(d[21]), "+f"(d[22]), "+f"(d[23]),
      "+f"(d[24]), "+f"(d[25]), "+f"(d[26]), "+f"(d[27]), "+f"(d[28]), "+f"(d[29]), "+f"(d[30]), "+f"(d[31]),
      "+f"(d[32]), "+f"(d[33]), "+f"(d[34]), "+f"(d[35]), "+f"(d[36]), "+f"(d[37]), "+f"(d[38]), "+f"(d[39]),
      "+f"(d[40]), "+f"(d[41]), "+f"(d[42]), "+f"(d[43]), "+f"(d[44]), "+f"(d[45]), "+f"(d[46]), "+f"(d[47]),
      "+f"(d[48]), "+f"(d[49]), "+f"(d[50]), "+f"(d[51]), "+f"(d[52]), "+f"(d[53]), "+f"(d[54]), "+f"(d[55]),
      "+f"(d[56]), "+f"(d[57]), "+f"(d[58]), "+f"(d[59]), "+f"(d[60]), "+f"(d[61]), "+f"(d[62]), "+f"(d[63])
    : "l"(descA), "l"(descB), "r"(scaleD));
}
__device__ __forceinline__ void wgmma_ss_n192_tb(float (&d)[96], uint64_t descA, uint64_t descB, int scaleD) {
  asm volatile("{\n.reg .pred p;\nsetp.ne.b32 p, %98, 0;\n"
    "wgmma.mma_async.sync.aligned.m64n192k16.f32.bf16.bf16 "
    "{%0, %1, %2, %3, %4, %5, %6, %7, %8, %9, %10, %11, %12, %13, %14, %15, %16, %17, %18, %19, %20, %21, %22, %23, %24, %25, %26, %27, %28, %29, %30, %31, %32, %33, %34, %35, %36, %37, %38, %39, %40, %41, %42, %43, %44, %45, %46, %47, %48, %49, %50, %51, %52, %53, %54, %55, %56, %57, %58, %59, %60, %61, %62, %63, %64, %65, %66, %67, %68, %69, %70, %71, %72, %73, %74, %75, %76, %77, %78, %79, %80, %81, %82, %83, %84, %85, %86, %87, %88, %89, %90, %91, %92, %93, %94, %95}, %96, %97, p, 1, 1, 0, 1;\n}\n"
    : "+f"(d[0]), "+f"(d[1]), "+f"(d[2]), "+f"(d[3]), "+f"(d[4]), "+f"(d[5]), "+f"(d[6]), "+f"(d[7]),
      "+f"(d[8]), "+f"(d[9]), "+f"(d[10]), "+f"(d[11]), "+f"(d[12]), "+f"(d[13]), "+f"(d[14]), "+f"(d[15]),
      "+f"(d[16]), "+f"(d[17]), "+f"(d[18]), "+f"(d[19]), "+f"(d[20]), "+f"(d[21]), "+f"(d[22]), "+f"(d[23]),
      "+f"(d[24]), "+f"(d[25]), "+f"(d[26]), "+f"(d[27]), "+f"(d[28]), "+f"(d[29]), "+f"(d[30]), "+f"(d[31]),
      "+f"(d[32]), "+f"(d[33]), "+f"(d[34]), "+f"(d[35]), "+f"(d[36]), "+f"(d[37]), "+f"(d[38]), "+f"(d[39]),
      "+f"(d[40]), "+f"(d[41]), "+f"(d[42]), "+f"(d[43]), "+f"(d[44]), "+f"(d[45]), "+f"(d[46]), "+f"(d[47]),
      "+f"(d[48]), "+f"(d[49]), "+f"(d[50]), "+f"(d[51]), "+f"(d[52]), "+f"(d[53]), "+f"(d[54]), "+f"(d[55]),
      "+f"(d[56]), "+f"(d[57]), "+f"(d[58]), "+f"(d[59]), "+f"(d[60]), "+f"(d[61]), "+f"(d[62]), "+f"(d[63]),
      "+f"(d[64]), "+f"(d[65]), "+f"(d[66]), "+f"(d[67]), "+f"(d[68]), "+f"(d[69]), "+f"(d[70]), "+f"(d[71]),
      "+f"(d[72]), "+f"(d[73]), "+f"(d[74]), "+f"(d[75]), "+f"(d[76]), "+f"(d[77]), "+f"(d[78]), "+f"(d[79]),
      "+f"(d[80]), "+f"(d[81]), "+f"(d[82]), "+f"(d[83]), "+f"(d[84]), "+f"(d[85]), "+f"(d[86]), "+f"(d[87]),
      "+f"(d[88]), "+f"(d[89]), "+f"(d[90]), "+f"(d[91]), "+f"(d[92]), "+f"(d[93]), "+f"(d[94]), "+f"(d[95])
    : "l"(descA), "l"(descB), "r"(scaleD));
}

__device__ __forceinline__ void ldsm4t(uint32_t (&b)[4], uint32_t addr) {
  asm volatile("ldmatrix.sync.aligned.m8n8.x4.trans.shared.b16 {%0,%1,%2,%3}, [%4];"
               : "=r"(b[0]), "=r"(b[1]), "=r"(b[2]), "=r"(b[3])
               : "r"(addr));
}
__device__ __forceinline__ void hmma(float (&c)[4], uint32_t a0, uint32_t a1, uint32_t a2, uint32_t a3, uint32_t b0, uint32_t b1) {
  asm("mma.sync.aligned.m16n8k16.row.col.f32.bf16.bf16.f32 {%0,%1,%2,%3}, {%4,%5,%6,%7}, {%8,%9}, {%0,%1,%2,%3};"
      : "+f"(c[0]), "+f"(c[1]), "+f"(c[2]), "+f"(c[3])
      : "r"(a0), "r"(a1), "r"(a2), "r"(a3), "r"(b0), "r"(b1));
}

__device__ __forceinline__ uint32_t movm(uint32_t a) {
  uint32_t d;
  asm volatile("movmatrix.sync.aligned.m8n8.trans.b16 %0, %1;" : "=r"(d) : "r"(a));
  return d;
}

#define K1_CPA 2
#define K1_PACE_NS 150
#define K1_WARM 0
constexpr int K1_STAGES = 4;
constexpr int K1_W_BYTES = 3 * 8192;
constexpr int K1_X_BYTES = 8 * 16384;
constexpr int K1_BAR_OFF = K1_X_BYTES + K1_STAGES * K1_W_BYTES;
constexpr int K1_SMEM = K1_BAR_OFF + 192 + 1024;
constexpr float QSCALE = 0.25f * 1.4426950408889634f;

__device__ __forceinline__ uint32_t phi2(uint32_t t2) {
  uint32_t a2, mask, r2, o2;
  asm("add.rn.bf16x2 %0, %1, %2;" : "=r"(a2) : "r"(t2), "r"(0x3F803F80u));
  const uint32_t e2 = pack_bf16(ex2f(bf_lo(t2) * 1.4426950408889634f), ex2f(bf_hi(t2) * 1.4426950408889634f));
  asm("set.gt.u32.bf16x2 %0, %1, %2;" : "=r"(mask) : "r"(t2), "r"(0u));
  r2 = (a2 & mask) | (e2 & ~mask);
  asm("add.rn.bf16x2 %0, %1, %2;" : "=r"(o2) : "r"(r2), "r"(0x35863586u));
  return o2;
}

#define K1_SLOT_KB(h) ((h) < 4 ? 2 * (h) : 2 * ((h) - 4) + 1)
struct EpiCtx {
  uint4* qf;
  uint32_t* kp;
  uint32_t* vp;
  uint32_t s_red_addr;
  float* red;
  int lane;
};

template <bool LINEAR, int HH, int PART>
__device__ __forceinline__ void epi_slice(const float (&acc)[96], const EpiCtx& c, uint32_t (&pk)[4], float& vmax, bool live) {
  const float* a = &acc[HH * 8];
  const float* k = &acc[32 + HH * 8];
  const float* v = &acc[64 + HH * 8];
  if (!LINEAR) {
    if (PART == 0) {
      uint32_t* kh = c.kp + HH * (KV_HEAD_BYTES / 4);
      if (live) {
        c.qf[HH * 32 * 128] = make_uint4(pack_bf16(a[0], a[1]), pack_bf16(a[2], a[3]), pack_bf16(a[4], a[5]), pack_bf16(a[6], a[7]));
        kh[0] = pack_bf16(k[0], k[1]);
        kh[64] = pack_bf16(k[2], k[3]);
        kh[32] = pack_bf16(k[4], k[5]);
        kh[96] = pack_bf16(k[6], k[7]);
      }
      float q0 = a[0] * a[0] + a[1] * a[1] + a[4] * a[4] + a[5] * a[5];
      float q1 = a[2] * a[2] + a[3] * a[3] + a[6] * a[6] + a[7] * a[7];
      float k0 = k[0] * k[0] + k[1] * k[1] + k[4] * k[4] + k[5] * k[5];
      float k1 = k[2] * k[2] + k[3] * k[3] + k[6] * k[6] + k[7] * k[7];
#pragma unroll
      for (int o = 1; o <= 2; o <<= 1) {
        q0 += __shfl_xor_sync(0xffffffffu, q0, o);
        q1 += __shfl_xor_sync(0xffffffffu, q1, o);
        k0 += __shfl_xor_sync(0xffffffffu, k0, o);
        k1 += __shfl_xor_sync(0xffffffffu, k1, o);
      }
      const uint32_t qm = __reduce_max_sync(0xffffffffu, max(__float_as_uint(q0) & 0x7FFFFFFFu, __float_as_uint(q1) & 0x7FFFFFFFu));
      const uint32_t km = __reduce_max_sync(0xffffffffu, max(__float_as_uint(k0) & 0x7FFFFFFFu, __float_as_uint(k1) & 0x7FFFFFFFu));
      asm volatile(
          "{\n.reg .pred p;\nsetp.ne.b32 p, %3, 0;\n"
          "@p red.shared.max.u32 [%0], %1;\n@p red.shared.max.u32 [%0+4], %2;\n}" ::"r"(c.s_red_addr + HH * 8),
          "r"(qm), "r"(km), "r"((c.lane == 0 && live) ? 1 : 0)
          : "memory");
    } else {
      uint32_t* vh = c.vp + HH * (KV_HEAD_BYTES / 4);
      if (live) {
        vh[0] = pack_bf16(v[0], v[1]);
        vh[96] = pack_bf16(v[2], v[3]);
        vh[32] = pack_bf16(v[4], v[5]);
        vh[128] = pack_bf16(v[6], v[7]);
        vh[64] = 0x3F803F80u;
        vh[160] = 0x3F803F80u;
      }
#pragma unroll
      for (int i = 0; i < 8; i++) asm("max.NaN.f32 %0, %0, %1;" : "+f"(vmax) : "f"(fabsf(v[i])));
    }
  } else {
    if (PART == 0) {
      const uint4 pq = make_uint4(phi2(pack_bf16(a[0], a[1])), phi2(pack_bf16(a[2], a[3])), phi2(pack_bf16(a[4], a[5])),
                                  phi2(pack_bf16(a[6], a[7])));
      if (live) c.qf[HH * 32 * 128] = pq;
      pk[0] = movm(phi2(pack_bf16(k[0], k[1])));
      pk[2] = movm(phi2(pack_bf16(k[2], k[3])));
      pk[1] = movm(phi2(pack_bf16(k[4], k[5])));
      pk[3] = movm(phi2(pack_bf16(k[6], k[7])));
    } else {
      const uint32_t b0 = movm(pack_bf16(v[0], v[1]));
      const uint32_t b1 = movm(pack_bf16(v[2], v[3]));
      const uint32_t b2 = movm(pack_bf16(v[4], v[5]));
      const uint32_t b3 = movm(pack_bf16(v[6], v[7]));
      float c0[4] = {0, 0, 0, 0}, c1[4] = {0, 0, 0, 0}, c2[4] = {0, 0, 0, 0};
      hmma(c0, pk[0], pk[1], pk[2], pk[3], b0, b1);
      hmma(c1, pk[0], pk[1], pk[2], pk[3], b2, b3);
      hmma(c2, pk[0], pk[1], pk[2], pk[3], 0x3F803F80u, 0x3F803F80u);
      float* slot = c.red + HH * 2 * 4096;
      if (live) {
#pragma unroll
        for (int i = 0; i < 4; i++) {
          slot[i * 32] = c0[i];
          slot[(4 + i) * 32] = c1[i];
          slot[(8 + i) * 32] = c2[i];
        }
      }
    }
  }
}

template <bool LINEAR>
__device__ __forceinline__ void qkv_consumer(uint32_t sbase, uint8_t* smem_gen, uint32_t* s_red, int cp, int rt) {
  const uint32_t bar_full = sbase + K1_BAR_OFF;
  const uint32_t bar_empty = bar_full + 8 * K1_STAGES;
  const int warp = threadIdx.x >> 5;
  const int wg = warp >> 2;
  const int lane = threadIdx.x & 31;
  float accN[96], accP[96];
  EpiCtx c;
  {
    const int row0 = rt * 128 + wg * 64 + (warp & 3) * 16;
    c.qf = g_qfrag + ((size_t)((LINEAR ? NH : 0) + cp * 8) * 32 + (rt * 2 + wg)) * 128 + (threadIdx.x & 127);
    uint32_t* img = reinterpret_cast<uint32_t*>(reinterpret_cast<uint8_t*>(g_kv) + (size_t)(cp * 8) * KV_HEAD_BYTES);
    c.kp = img + (row0 >> 3) * 64 + lane;
    c.vp = img + KV_K_BYTES / 4 + (row0 >> 3) * 96 + lane;
    c.s_red_addr = smem_u32(s_red);
    c.red = reinterpret_cast<float*>(smem_gen + wg * 8192) + (warp & 3) * 384 + lane;
    c.lane = lane;
  }
  uint32_t pk[4] = {0, 0, 0, 0};
  float vmax = 0.f;
#pragma unroll
  for (int i = 0; i < 96; i++) asm volatile("mov.f32 %0, 0f00000000;" : "=f"(accN[i]));
  int npass;
  asm volatile("mov.u32 %0, 2;" : "=r"(npass));
#pragma unroll 1
  for (int pass = K1_WARM ? 0 : 1; pass < npass; pass++) {
    const bool live = K1_WARM ? pass != 0 : true;
    if (live) {
#pragma unroll 1
      for (int kb = 0; kb < 8; kb++) {
        const int s = kb % K1_STAGES;
        if (kb < K1_CPA) {
          if (kb == 0) asm volatile("cp.async.wait_group %0;" ::"n"(K1_CPA > 0 ? K1_CPA - 1 : 0) : "memory");
          else if (kb == 1) asm volatile("cp.async.wait_group %0;" ::"n"(K1_CPA > 1 ? K1_CPA - 2 : 0) : "memory");
          else if (kb == 2) asm volatile("cp.async.wait_group %0;" ::"n"(K1_CPA > 2 ? K1_CPA - 3 : 0) : "memory");
          else asm volatile("cp.async.wait_group 0;" ::: "memory");
          fence_proxy_async();
          asm volatile("bar.sync 1, 256;" ::: "memory");
        }
        mbar_wait(bar_full + 8 * s, (kb / K1_STAGES) & 1);
        if (threadIdx.x == 0) PROF_T(0, 2 + (kb >> 1));
        const uint64_t dA = mkdesc(sbase + kb * 16384 + wg * 8192, 16, 1024, 1);
        const uint64_t dB = mkdesc(sbase + K1_X_BYTES + s * K1_W_BYTES, 8192, 1024, 1);
        wg_fence();
#pragma unroll
        for (int k = 0; k < 4; k++) wgmma_ss_n192_tb(accP, dA + k * 2, dB + k * 128, (kb | k) != 0);
        wg_commit();
        if (kb > 0) {
          wg_wait<1>();
          if ((threadIdx.x & 127) == 0) {
            const int sp = (kb - 1) % K1_STAGES;
            mbar_arrive_cluster(bar_empty + 8 * sp, 0);
            mbar_arrive_cluster(bar_empty + 8 * sp, 1);
          }
        }
      }
      wg_wait<0>();
      fence_regs(accP);
      if ((threadIdx.x & 127) == 0) {
        mbar_arrive_cluster(bar_empty + 8 * (7 % K1_STAGES), 0);
        mbar_arrive_cluster(bar_empty + 8 * (7 % K1_STAGES), 1);
      }
      if (threadIdx.x == 0) PROF_T(0, 6);
#define K1_T1_STEP(KB)                                                                           \
  {                                                                                              \
    constexpr int g = 8 + KB;                                                                    \
    constexpr int s = g % K1_STAGES;                                                             \
    mbar_wait(bar_full + 8 * s, (g / K1_STAGES) & 1);                                            \
    const uint64_t dA = mkdesc(sbase + KB * 16384 + wg * 8192, 16, 1024, 1);                     \
    const uint64_t dB = mkdesc(sbase + K1_X_BYTES + s * K1_W_BYTES, 8192, 1024, 1);              \
    wg_fence();                                                                                  \
    _Pragma("unroll") for (int k = 0; k < 4; k++) wgmma_ss_n192_tb(accN, dA + k * 2, dB + k * 128, (KB | k) != 0); \
    wg_commit();                                                                                 \
    epi_slice<LINEAR, KB / 2, KB & 1>(accP, c, pk, vmax, true);                                  \
    wg_wait<0>();                                                                                \
    if (KB + K1_STAGES < 8 && (threadIdx.x & 127) == 0) {                                        \
      mbar_arrive_cluster(bar_empty + 8 * s, 0);                                                 \
      mbar_arrive_cluster(bar_empty + 8 * s, 1);                                                 \
    }                                                                                            \
  }
      K1_T1_STEP(0) K1_T1_STEP(1) K1_T1_STEP(2) K1_T1_STEP(3) K1_T1_STEP(4) K1_T1_STEP(5) K1_T1_STEP(6) K1_T1_STEP(7)
#undef K1_T1_STEP
      fence_regs(accN);
      if (threadIdx.x == 0) PROF_T(0, 10);
      c.qf += 4 * 32 * 128;
      c.kp += 4 * (KV_HEAD_BYTES / 4);
      c.vp += 4 * (KV_HEAD_BYTES / 4);
      c.s_red_addr += 32;
      c.red += 4096;
    }
    float vm1 = 0.f;
    epi_slice<LINEAR, 0, 0>(accN, c, pk, vm1, live);
    epi_slice<LINEAR, 0, 1>(accN, c, pk, vm1, live);
    epi_slice<LINEAR, 1, 0>(accN, c, pk, vm1, live);
    epi_slice<LINEAR, 1, 1>(accN, c, pk, vm1, live);
    epi_slice<LINEAR, 2, 0>(accN, c, pk, vm1, live);
    epi_slice<LINEAR, 2, 1>(accN, c, pk, vm1, live);
    epi_slice<LINEAR, 3, 0>(accN, c, pk, vm1, live);
    epi_slice<LINEAR, 3, 1>(accN, c, pk, vm1, live);
    if (live) asm("max.NaN.f32 %0, %0, %1;" : "+f"(vmax) : "f"(vm1));
  }
  if (!LINEAR) {
    const uint32_t vm = __reduce_max_sync(0xffffffffu, __float_as_uint(vmax) & 0x7FFFFFFFu);
    if (lane == 0) atomicMax(&s_red[16], vm);
    asm volatile("bar.sync 1, 256;" ::: "memory");
    if (threadIdx.x < 8) {
      *reinterpret_cast<float4*>(&g_nrm[((cp * 8 + threadIdx.x) * 16 + rt) * 4]) =
          make_float4(__uint_as_float(s_red[threadIdx.x * 2]), __uint_as_float(s_red[threadIdx.x * 2 + 1]), __uint_as_float(s_red[16]), 0.f);
    }
  } else {
    asm volatile("bar.sync 1, 256;" ::: "memory");
    float* dst = g_kvpart + ((size_t)rt * NH + cp * 8) * 384 + threadIdx.x;
    const float* base = reinterpret_cast<const float*>(smem_gen);
#pragma unroll
    for (int i = 0; i < 12; i++) {
      const int h0 = (i / 3) * 2, r = i % 3;
      const bool second = r == 2 || (r == 1 && threadIdx.x >= 128);
      const int e = (int)threadIdx.x + r * 256 - (second ? 384 : 0);
      const float* src = base + (second ? K1_SLOT_KB(h0 + 1) : K1_SLOT_KB(h0)) * 4096 + e;
      float sum = 0.f;
#pragma unroll
      for (int w = 0; w < 8; w++) sum += src[(w >> 2) * 2048 + (w & 3) * 384];
      dst[i * 256] = sum;
    }
  }
}

__global__ void __launch_bounds__(384, 1)
qkv_gemm_kernel(const __grid_constant__ CUtensorMap mxA, const __grid_constant__ CUtensorMap mxB,
                const __grid_constant__ CUtensorMap mwA, const __grid_constant__ CUtensorMap mwB, const uint8_t* __restrict__ xA,
                const uint8_t* __restrict__ xB, const uint8_t* __restrict__ wA, const uint8_t* __restrict__ wB) {
  extern __shared__ uint8_t smem_raw[];
  const uint32_t sbase = (smem_u32(smem_raw) + 1023) & ~1023u;
  uint8_t* smem_gen = smem_raw + (sbase - smem_u32(smem_raw));
  const uint32_t bar_full = sbase + K1_BAR_OFF;
  const uint32_t bar_empty = bar_full + 8 * K1_STAGES;
  uint32_t* s_red = reinterpret_cast<uint32_t*>(smem_gen + K1_BAR_OFF + 64);

  const int rank = blockIdx.x & 1;
  const int pair = blockIdx.x >> 1;
  const int branch = pair >> 5;
  const int rp = (pair & 31) >> 2;
  const int cp = pair & 3;
  const int rt = rp * 2 + rank;
  const int warp = threadIdx.x >> 5;
  if (threadIdx.x == 0) { PROF_G(0, 30); PROF_T(0, 0); }
  const CUtensorMap* mx = branch ? &mxA : &mxB;
  const CUtensorMap* mw = branch ? &mwA : &mwB;

  if (threadIdx.x < 256) {
    const uint8_t* xg = (branch ? xA : xB) + (size_t)rt * 128 * 1024;
    const uint8_t* wg_ = (branch ? wA : wB) + cp * 256;
#pragma unroll
    for (int kb = 0; kb < K1_CPA; kb++) {
#pragma unroll
      for (int i = 0; i < 4; i++) {
        const int c = threadIdx.x + i * 256, r = c >> 3, ch = c & 7;
        asm volatile("cp.async.cg.shared.global [%0], [%1], 16;" ::"r"(sbase + kb * 16384 + r * 128 + ((ch ^ (r & 7)) << 4)),
                     "l"(xg + r * 1024 + kb * 128 + ch * 16)
                     : "memory");
      }
#pragma unroll
      for (int i = 0; i < 6; i++) {
        const int c = threadIdx.x + i * 256, p = c >> 9, r = (c >> 3) & 63, ch = c & 7;
        asm volatile("cp.async.cg.shared.global [%0], [%1], 16;" ::"r"(sbase + K1_X_BYTES + kb * K1_W_BYTES + p * 8192 + r * 128 + ((ch ^ (r & 7)) << 4)),
                     "l"(wg_ + (size_t)(kb * 64 + r) * 3072 + p * 1024 + ch * 16)
                     : "memory");
      }
      asm volatile("cp.async.commit_group;" ::: "memory");
    }
  }
  if (threadIdx.x == 256) {
    asm volatile("prefetch.tensormap [%0];" ::"l"(mx) : "memory");
    asm volatile("prefetch.tensormap [%0];" ::"l"(mw) : "memory");
    for (int i = 0; i < K1_STAGES; i++) {
      mbar_init(bar_full + 8 * i, 1);
      mbar_init(bar_empty + 8 * i, 4);
    }
    fence_barrier_init();
    fence_proxy_async();
    for (int kb = 0; kb < K1_STAGES; kb++) {
      if (kb < K1_CPA) mbar_arrive(bar_full + 8 * kb);
      else mbar_expect_tx(bar_full + 8 * kb, 16384 + K1_W_BYTES);
    }
    if (K1_CPA < K1_STAGES) tma_load_2d(sbase + K1_CPA * 16384, mx, K1_CPA * 64, rt * 128, bar_full + 8 * K1_CPA);
  }
  pdl_launch_dependents();
  if (threadIdx.x < 32) s_red[threadIdx.x] = 0;
  __syncthreads();
  cluster_sync_relaxed();
  if (threadIdx.x == 0) PROF_T(0, 1);

  if (warp >= 8) {
    asm volatile("setmaxnreg.dec.sync.aligned.u32 40;");
    if (threadIdx.x == 256) {
      for (int g = K1_CPA; g < 16; g++) {
        const int s = g % K1_STAGES;
        const int kb = g & 7;
        if (g >= K1_STAGES) {
          mbar_wait(bar_empty + 8 * s, ((g / K1_STAGES) - 1) & 1);
          mbar_expect_tx(bar_full + 8 * s, (g < 8 ? 16384 : 0) + K1_W_BYTES);
        }
        if (g > K1_CPA && g < 8) tma_load_2d(sbase + kb * 16384, mx, kb * 64, rt * 128, bar_full + 8 * s);
        if (K1_CPA == K1_STAGES && g == K1_CPA) tma_load_2d(sbase + kb * 16384, mx, kb * 64, rt * 128, bar_full + 8 * s);
        const int h0 = cp * 8 + (g >> 3) * 4;
        const uint32_t st = sbase + K1_X_BYTES + s * K1_W_BYTES + rank * 4096;
#pragma unroll
        for (int p = 0; p < 3; p++)
          tma_load_2d_mc(st + p * 8192, mw, p * 512 + h0 * 16, kb * 64 + rank * 32, bar_full + 8 * s, (uint16_t)3);
        if (K1_PACE_NS && g < K1_STAGES - 1) __nanosleep(K1_PACE_NS);
      }
    }
    __syncwarp();
    cluster_sync_relaxed();
  } else {
    asm volatile("setmaxnreg.inc.sync.aligned.u32 232;");
    if (branch == 0) qkv_consumer<false>(sbase, smem_gen, s_red, cp, rt);
    else qkv_consumer<true>(sbase, smem_gen, s_red, cp, rt);
    if (threadIdx.x == 0) PROF_T(0, 11);
    __syncwarp();
    cluster_sync_relaxed();
    if (threadIdx.x == 0) { PROF_T(0, 12); PROF_G(0, 31); }
  }
}

constexpr int K2_SMEM = KV_HEAD_BYTES + 1024 + 256;

#define ATT_NPOLY 19
#define ATT_CH 8
#define ATT_D 1
#define PRO_MODE 1
#define STAGGER 0
#define K2_G0_CPASYNC 0
#define STAG_MODE 0
#define CONST_SMID 0
#define ATT_STRUCT 1
#define ATT_PIN 0
#define ATT_GM 1
#define ATT_DEG 2
struct ExpC {
  uint32_t k3c00, kmask, seven, c3;
};
__device__ __forceinline__ uint32_t hfma2(uint32_t a, uint32_t b, uint32_t c) {
  uint32_t r;
  asm("fma.rn.f16x2 %0, %1, %2, %3;" : "=r"(r) : "r"(a), "r"(b), "r"(c));
  return r;
}
__device__ __forceinline__ uint32_t exp2_poly_pair(float t0, float t1, const ExpC& c) {
  uint32_t u;
  asm("prmt.b32 %0, %1, %2, 0x5410;" : "=r"(u) : "r"(__float_as_uint(t0)), "r"(__float_as_uint(t1)));
  uint32_t m;
  asm("lop3.b32 %0, %1, 0x03FF03FF, %2, 0xEA;" : "=r"(m) : "r"(u), "r"(c.k3c00));
  uint32_t p = hfma2(m, c.c3, 0xa385a385u);
  p = hfma2(p, m, 0x4ad64ad7u);
  uint32_t mu;
  asm("lop3.b32 %0, %1, 0xFC00FC00, %2, 0xEA;" : "=r"(mu) : "r"(u), "r"(c.kmask));
  uint32_t r;
  asm("{.reg .b32 t; shf.r.wrap.b32 t, %1, %2, 3; add.u32 %0, t, %3;}" : "=r"(r) : "r"(mu), "r"(c.seven), "r"(p));
  return r;
}
__device__ __forceinline__ float gadd(float x, float M, uint32_t g) {
  float r = x;
  asm("{.reg .pred p; setp.ne.b32 p, %2, -1; @p add.f32 %0, %0, %1;}" : "+f"(r) : "f"(M), "r"(g));
  return r;
}
__device__ __forceinline__ float gex2(float x, uint32_t g) {
  float r = x;
  asm("{.reg .pred p; setp.ne.b32 p, %1, -1; @p ex2.approx.ftz.f32 %0, %0;}" : "+f"(r) : "r"(g));
  return r;
}
#define ATT_PAT 0
__host__ __device__ constexpr bool is_poly(int i, int npoly) {
  return ATT_PAT == 0   ? ((i + 1) * npoly / 32) != (i * npoly / 32)
         : ATT_PAT == 1 ? ((32 - i) * npoly / 32) != ((31 - i) * npoly / 32)
         : ATT_PAT == 2 ? ((i & 7) >= 8 - (((i / 8 + 1) * 8) * npoly / 32 - ((i / 8) * 8) * npoly / 32))
                        : ((i & 7) < (((i / 8 + 1) * 8) * npoly / 32 - ((i / 8) * 8) * npoly / 32));
}
template <int NPOLY, int NPAIR, int CH, int D, bool G0 = false>
__device__ __forceinline__ void exp_tile(const float (&s)[2 * NPAIR], uint32_t (&p)[NPAIR], const ExpC& c, uint32_t g0 = 0) {
#pragma unroll
  for (int i = 0; i < NPAIR; i++) {
    const bool isPoly = is_poly(i, NPOLY);
    const int ch = i / CH;
    const bool gated = ch >= D || G0;
    int gi = (ch - D) * CH + CH - 1;
    if (ch >= D) {
      while (gi > (ch - D) * CH && !is_poly(gi, NPOLY)) gi--;
    }
    const uint32_t g = ch >= D ? p[gi] : g0;
    if (!isPoly) {
      if (gated && ATT_GM) p[i] = pack_bf16(gex2(s[2 * i], g), gex2(s[2 * i + 1], g));
      else p[i] = pack_bf16(ex2f(s[2 * i]), ex2f(s[2 * i + 1]));
    } else {
      if (gated) p[i] = exp2_poly_pair(gadd(s[2 * i], 12329.f, g), gadd(s[2 * i + 1], 12329.f, g), c);
      else p[i] = exp2_poly_pair(s[2 * i] + 12329.f, s[2 * i + 1] + 12329.f, c);
    }
  }
}

__device__ __forceinline__ void store_o(__nv_bfloat16* o, int row0, int head, int lane, const uint32_t (&r)[4]) {
  const int g = lane >> 2, t = lane & 3;
  uint32_t* p0 = reinterpret_cast<uint32_t*>(o + (size_t)(row0 + g) * DM + head * 16) + t;
  uint32_t* p1 = reinterpret_cast<uint32_t*>(o + (size_t)(row0 + g + 8) * DM + head * 16) + t;
  p0[0] = r[0];
  p1[0] = r[1];
  p0[4] = r[2];
  p1[4] = r[3];
}

template <int NPOLY, int LO, int HI, int CH>
__device__ __forceinline__ void exp_range(const float (&s)[32], uint32_t (&p)[16], const ExpC& c) {
#pragma unroll
  for (int i = LO; i < HI; i++) {
    const bool isPoly = is_poly(i, NPOLY);
    const int ch = (i - LO) / CH;
    const bool gated = ch >= 1;
    int gi = LO + (ch - 1) * CH + CH - 1;
    if (gated) {
      while (gi > LO + (ch - 1) * CH && !is_poly(gi, NPOLY)) gi--;
    }
    const uint32_t g = gated ? p[gi] : 0;
    if (!isPoly) {
      if (gated && ATT_GM) p[i] = pack_bf16(gex2(s[2 * i], g), gex2(s[2 * i + 1], g));
      else p[i] = pack_bf16(ex2f(s[2 * i]), ex2f(s[2 * i + 1]));
    } else {
      if (gated) p[i] = exp2_poly_pair(gadd(s[2 * i], 12329.f, g), gadd(s[2 * i + 1], 12329.f, g), c);
      else p[i] = exp2_poly_pair(s[2 * i] + 12329.f, s[2 * i + 1] + 12329.f, c);
    }
  }
}

__device__ __forceinline__ void kv_fetch_piece(uint32_t sbase, uint32_t bar, int piece) {
  const uint8_t* img = reinterpret_cast<const uint8_t*>(g_kv) + (size_t)(blockIdx.x >> 2) * KV_HEAD_BYTES;
  const int g = piece >> 1, isv = piece & 1;
  const int e0 = g == 0 ? 0 : (isv ? 256 : 320) + (g - 1) * 512;
  const int e1 = g == 3 ? 2048 : (isv ? 256 : 320) + g * 512;
  const int bytes = (e1 - e0) * (isv ? 48 : 32);
  const int off = isv ? KV_K_BYTES + e0 * 48 : e0 * 32;
  mbar_expect_tx(bar + 8 * g, bytes);
  bulk_load(sbase + off, img + off, bytes, bar + 8 * g);
}

__device__ __forceinline__ void safe_exp(float (&s)[32], uint32_t (&p)[16], float (&o)[12], float& m0, float& m1) {
#pragma unroll
  for (int i = 0; i < 16; i++) {
    const uint32_t r = pack_bf16(s[2 * i], s[2 * i + 1]);
    s[2 * i] = bf_lo(r) * QSCALE;
    s[2 * i + 1] = bf_hi(r) * QSCALE;
  }
  float x0 = s[0], x1 = s[2];
#pragma unroll
  for (int i = 0; i < 8; i++) {
    x0 = fmaxf(x0, fmaxf(s[4 * i], s[4 * i + 1]));
    x1 = fmaxf(x1, fmaxf(s[4 * i + 2], s[4 * i + 3]));
  }
  x0 = fmaxf(x0, __shfl_xor_sync(0xffffffffu, x0, 1));
  x1 = fmaxf(x1, __shfl_xor_sync(0xffffffffu, x1, 1));
  x0 = fmaxf(x0, __shfl_xor_sync(0xffffffffu, x0, 2));
  x1 = fmaxf(x1, __shfl_xor_sync(0xffffffffu, x1, 2));
  const float n0 = fmaxf(m0, x0), n1 = fmaxf(m1, x1);
  const float c0 = ex2f(m0 - n0), c1 = ex2f(m1 - n1);
  m0 = n0;
  m1 = n1;
#pragma unroll
  for (int i = 0; i < 3; i++) {
    o[4 * i] *= c0;
    o[4 * i + 1] *= c0;
    o[4 * i + 2] *= c1;
    o[4 * i + 3] *= c1;
  }
#pragma unroll
  for (int i = 0; i < 8; i++) {
    p[2 * i] = pack_bf16(ex2f(s[4 * i] - n0), ex2f(s[4 * i + 1] - n0));
    p[2 * i + 1] = pack_bf16(ex2f(s[4 * i + 2] - n1), ex2f(s[4 * i + 3] - n1));
  }
}

__device__ __forceinline__ void attn_step(float (&sx)[32], float (&sy)[32], float (&o)[12], const uint4& qf, uint64_t dK, uint64_t dV,
                                          const ExpC& ec) {
  uint32_t pa[16], pb[16];
  wg_fence();
  wgmma_rs_n64_z(sy, qf.x, qf.y, qf.z, qf.w, dK + 128);
  wg_commit();
  exp_tile<ATT_NPOLY, 16, ATT_CH, ATT_D>(sx, pa, ec);
  wg_fence();
  wgmma_rs_n24_tb(o, pa[12], pa[13], pa[14], pa[15], dV + 3 * 48, 1);
  wg_commit();
  wg_wait<1>();
  fence_regs(sy);
  exp_tile<ATT_NPOLY, 16, ATT_CH, ATT_D>(sy, pb, ec);
  wg_fence();
#pragma unroll
  for (int k = 0; k < 3; k++) wgmma_rs_n24_tb(o, pa[4 * k], pa[4 * k + 1], pa[4 * k + 2], pa[4 * k + 3], dV + k * 48, 1);
#pragma unroll
  for (int k = 0; k < 4; k++) wgmma_rs_n24_tb(o, pb[4 * k], pb[4 * k + 1], pb[4 * k + 2], pb[4 * k + 3], dV + (4 + k) * 48, 1);
  wgmma_rs_n64_z(sy, qf.x, qf.y, qf.z, qf.w, dK + 256);
  wg_commit();
  wg_wait<0>();
  fence_regs(sy);
}

template <bool SAFE>
__device__ __forceinline__ void attn_tile(uint64_t dK, uint64_t dV, uint32_t bar, uint4 qf, const ExpC& ec, uint32_t (&outp)[4]) {
  float o[12];
#pragma unroll
  for (int i = 0; i < 12; i++) asm volatile("mov.f32 %0, 0f00000000;" : "=f"(o[i]));
  if (!SAFE) {
    qf.x = pack_bf16(bf_lo(qf.x) * QSCALE, bf_hi(qf.x) * QSCALE);
    qf.y = pack_bf16(bf_lo(qf.y) * QSCALE, bf_hi(qf.y) * QSCALE);
    qf.z = pack_bf16(bf_lo(qf.z) * QSCALE, bf_hi(qf.z) * QSCALE);
    qf.w = pack_bf16(bf_lo(qf.w) * QSCALE, bf_hi(qf.w) * QSCALE);
    float s0[32], s1[32];
    wg_fence();
    wgmma_rs_n64_z(s0, qf.x, qf.y, qf.z, qf.w, dK);
    wg_commit();
    wg_wait<0>();
    fence_regs(s0);
#pragma unroll 1
    for (int p = 0; p < 8; p++) {
      if (p & 1) mbar_wait(bar + 8 * min((p + 1) >> 1, 3), 0);
      attn_step(s0, s1, o, qf, dK, dV, ec);
      attn_step(s1, s0, o, qf, dK + 256, dV + 384, ec);
      dK += 512;
      dV += 768;
    }
    wg_wait<0>();
  } else {
    float m0 = -INFINITY, m1 = -INFINITY;
#pragma unroll 1
    for (int j = 0; j < 32; j++) {
      if (j == 4) { mbar_wait(bar + 8, 0); mbar_wait(bar + 16, 0); mbar_wait(bar + 24, 0); }
      float s[32];
      uint32_t p[16];
      wg_fence();
      wgmma_rs_n64_z(s, qf.x, qf.y, qf.z, qf.w, dK);
      wg_commit();
      wg_wait<0>();
      fence_regs(s);
      safe_exp(s, p, o, m0, m1);
      wg_fence();
#pragma unroll
      for (int k = 0; k < 4; k++) wgmma_rs_n24_tb(o, p[4 * k], p[4 * k + 1], p[4 * k + 2], p[4 * k + 3], dV + k * 48, 1);
      wg_commit();
      wg_wait<0>();
      fence_regs(o);
      dK += 128;
      dV += 192;
    }
  }
  fence_regs(o);
  const float r0 = 1.0f / o[8], r1 = 1.0f / o[10];
  outp[0] = pack_bf16(o[0] * r0, o[1] * r0);
  outp[1] = pack_bf16(o[2] * r1, o[3] * r1);
  outp[2] = pack_bf16(o[4] * r0, o[5] * r0);
  outp[3] = pack_bf16(o[6] * r1, o[7] * r1);
}

__device__ __forceinline__ void linear_attn_cta(uint8_t* smem_raw, uint32_t sbase, const CUtensorMap* mo16, int cta) {
  const int warp = threadIdx.x >> 5, lane = threadIdx.x & 31;
  const int hg = warp & 1;
  const uint4* qp = g_qfrag + (size_t)(NH + cta * 8 + hg * 4) * 32 * 128 + lane;
  auto qaddr = [&](int i) {
    const int blk16 = i * 8 + (warp >> 1);
    return qp + (blk16 >> 2) * 128 + (blk16 & 3) * 32;
  };
  uint4 q[4];
#pragma unroll
  for (int h = 0; h < 4; h++) q[h] = qaddr(0)[h * 32 * 128];
  float* red = reinterpret_cast<float*>(smem_raw + (sbase - smem_u32(smem_raw)) + 131072);
  {
    const float* src = g_kvpart + (size_t)cta * 8 * 384;
    float sum[6];
#pragma unroll
    for (int i = 0; i < 6; i++) sum[i] = 0.f;
#pragma unroll
    for (int r = 0; r < 16; r++) {
#pragma unroll
      for (int i = 0; i < 6; i++) sum[i] += src[(size_t)r * NH * 384 + threadIdx.x + i * 512];
    }
#pragma unroll
    for (int i = 0; i < 6; i++) red[threadIdx.x + i * 512] = round_bf16(sum[i]);
  }
  __syncthreads();
  if (threadIdx.x == 0) PROF_T(1, 1);
  uint32_t bf[4][6];
  {
    const int g = lane >> 2, t = lane & 3;
#pragma unroll
    for (int h = 0; h < 4; h++) {
#pragma unroll
      for (int f = 0; f < 6; f++) {
        const int blk = f >> 1, half = f & 1;
        const int e = (blk == 2) ? 0 : g;
        const int d = 2 * t + 8 * half;
        const int base = (hg * 4 + h) * 384 + (blk * 4 + half * 2 + (e & 1)) * 32 + (e >> 1);
        bf[h][f] = pack_bf16(red[base + (d & 7) * 4], red[base + ((d + 1) & 7) * 4]);
      }
    }
  }
  if (threadIdx.x == 0) PROF_T(1, 2);
  const uint32_t stg = sbase + warp * 8192;
#pragma unroll 1
  for (int i = 0; i < 16; i++) {
    uint4 qc[4];
#pragma unroll
    for (int h = 0; h < 4; h++) qc[h] = q[h];
    if (i + 1 < 16) {
#pragma unroll
      for (int h = 0; h < 4; h++) q[h] = qaddr(i + 1)[h * 32 * 128];
    }
    const uint32_t buf = stg + (i & 3) * 2048;
    if (i >= 4) {
      if (lane == 0) asm volatile("cp.async.bulk.wait_group.read 3;" ::: "memory");
      __syncwarp();
    }
#pragma unroll
    for (int h = 0; h < 4; h++) {
      float n0[4] = {0, 0, 0, 0}, n1[4] = {0, 0, 0, 0}, dn[4] = {0, 0, 0, 0};
      hmma(n0, qc[h].x, qc[h].y, qc[h].z, qc[h].w, bf[h][0], bf[h][1]);
      hmma(n1, qc[h].x, qc[h].y, qc[h].z, qc[h].w, bf[h][2], bf[h][3]);
      hmma(dn, qc[h].x, qc[h].y, qc[h].z, qc[h].w, bf[h][4], bf[h][5]);
      const float d0 = __fdividef(1.0f, dn[0] + 1e-6f), d1 = __fdividef(1.0f, dn[2] + 1e-6f);
      const uint32_t r0 = pack_bf16(n0[0] * d0, n0[1] * d0);
      const uint32_t r1 = pack_bf16(n0[2] * d1, n0[3] * d1);
      const uint32_t r2 = pack_bf16(n1[0] * d0, n1[1] * d0);
      const uint32_t r3 = pack_bf16(n1[2] * d1, n1[3] * d1);
      const int row = lane & 15;
      const int chunk = h * 2 + (lane >> 4);
      const uint32_t addr = buf + row * 128 + ((chunk ^ (row & 7)) << 4);
      asm volatile("stmatrix.sync.aligned.m8n8.x4.shared.b16 [%0], {%1,%2,%3,%4};" ::"r"(addr), "r"(r0), "r"(r1), "r"(r2), "r"(r3)
                   : "memory");
    }
    fence_proxy_async();
    __syncwarp();
    if (lane == 0) {
      tma_store_2d(mo16, buf, cta * 128 + hg * 64, (i * 8 + (warp >> 1)) * 16);
      asm volatile("cp.async.bulk.commit_group;" ::: "memory");
    }
  }
  if (threadIdx.x == 0) PROF_T(1, 3);
  if (lane == 0) asm volatile("cp.async.bulk.wait_group 0;" ::: "memory");
}

__global__ void __launch_bounds__(512, 1)
attn_kernel(const __grid_constant__ CUtensorMap mo16, const uint8_t* __restrict__ woA, const uint8_t* __restrict__ woB) {
  extern __shared__ uint8_t smem_raw[];
  const uint32_t sbase = (smem_u32(smem_raw) + 1023) & ~1023u;
  const uint32_t bar = sbase + KV_HEAD_BYTES;
  if (threadIdx.x == 0) { PROF_G(1, 30); PROF_T(1, 0); }
  if (threadIdx.x == 0) {
    for (int i = 0; i < 4; i++) mbar_init(bar + 8 * i, 2);
    asm volatile("st.shared.v4.u32 [%0], {%1, %2, %3, %4};" ::"r"(bar + 64), "r"(0x3C003C00u), "r"(0x00070000u), "r"(7u),
                 "r"(ATT_DEG == 3 ? 0x2cfd2cfdu : 0x35623562u)
                 : "memory");
    fence_barrier_init();
    fence_proxy_async();
  }
  __syncthreads();
  pdl_launch_dependents();
  if (blockIdx.x >= 128 && threadIdx.x < 16) {
    const int i = (blockIdx.x - 128) * 16 + threadIdx.x;
    const uint8_t* p = (i < 32 ? woA : woB) + (size_t)(i & 31) * 16384;
    asm volatile("cp.async.bulk.prefetch.L2.global [%0], %1;" ::"l"(p), "r"(16384) : "memory");
  }
  if (blockIdx.x >= 128) {
    pdl_wait();
    linear_attn_cta(smem_raw, sbase, &mo16, blockIdx.x - 128);
    if (threadIdx.x == 0) { PROF_T(1, 5); PROF_G(1, 31); }
    return;
  }
  const int head = blockIdx.x >> 2, qb = blockIdx.x & 3;
  const int lane = threadIdx.x & 31;
  const int wg = __shfl_sync(0xffffffffu, threadIdx.x >> 7, 0), warp = __shfl_sync(0xffffffffu, (threadIdx.x >> 5) & 3, 0);
  ExpC ec;
  asm volatile("ld.volatile.shared.v4.u32 {%0, %1, %2, %3}, [%4];" : "=r"(ec.k3c00), "=r"(ec.kmask), "=r"(ec.seven), "=r"(ec.c3) : "r"(bar + 64));
  const uint64_t dK = mkdesc(sbase, 128, 256, 0);
  const uint64_t dV = mkdesc(sbase + KV_K_BYTES, 384, 128, 0);
  pdl_wait();
  if (threadIdx.x == 0) { PROF_T(1, 7); PROF_G(1, 29); }
  if (threadIdx.x == 0) {
#pragma unroll
    for (int piece = 0; piece < 8; piece++) kv_fetch_piece(sbase, bar, piece);
  }
  uint4 qnext = g_qfrag[(head * 32 + qb * 8 + wg * 2) * 128 + (threadIdx.x & 127)];
  bool safe_path;
  {
    float4 n = make_float4(0.f, 0.f, 0.f, 0.f);
    if (lane < 16) n = *reinterpret_cast<const float4*>(&g_nrm[(head * 16 + lane) * 4]);
    uint32_t qm = ((lane >> 2) == qb) ? __float_as_uint(n.x) : 0u;
    qm = __reduce_max_sync(0xffffffffu, qm);
    const uint32_t km = __reduce_max_sync(0xffffffffu, __float_as_uint(n.y));
    const uint32_t vm = __reduce_max_sync(0xffffffffu, __float_as_uint(n.z));
    const float b2 = __uint_as_float(qm) * (QSCALE * QSCALE) * __uint_as_float(km) * 1.02f;
    const float vmax = __uint_as_float(vm);
    const bool ok = (b2 <= 21.5f * 21.5f) && (vmax <= 1.0e24f) && (vmax >= 1.0e-18f || vmax == 0.f);
    safe_path = !ok;
  }
  mbar_wait(bar, 0);
#pragma unroll 1
  for (int t = 0; t < 2; t++) {
    const int tile64 = qb * 8 + wg * 2 + t;
    const uint4 qf = qnext;
    if (t == 0) qnext = g_qfrag[(head * 32 + tile64 + 1) * 128 + (threadIdx.x & 127)];
    uint32_t r[4];
    if (threadIdx.x == 0) PROF_T(1, 1 + t);
    if (!safe_path) attn_tile<false>(dK, dV, bar, qf, ec, r);
    else attn_tile<true>(dK, dV, bar, qf, ec, r);
    store_o(g_o + (size_t)S_LEN * DM, tile64 * 64 + warp * 16, head, lane, r);
  }
  if (threadIdx.x == 0) { PROF_T(1, 5); PROF_G(1, 31); }
}

#define K3_WPRE 2
constexpr int K3_STAGES = 5;
constexpr int K3_W_BYTES = 8 * 16384;
constexpr int K3_BAR_OFF = K3_W_BYTES + K3_STAGES * 16384;
constexpr int K3_SMEM = K3_BAR_OFF + 256 + 1024;

__global__ void __launch_bounds__(288, 1)
out_gemm_kernel(const __grid_constant__ CUtensorMap mo, const __grid_constant__ CUtensorMap mwA,
                const __grid_constant__ CUtensorMap mwB, const __grid_constant__ CUtensorMap mout) {
  extern __shared__ uint8_t smem_raw[];
  const uint32_t sbase = (smem_u32(smem_raw) + 1023) & ~1023u;
  const uint32_t bar_full = sbase + K3_BAR_OFF;
  const uint32_t bar_empty = bar_full + 8 * K3_STAGES;
  const uint32_t bar_w = bar_empty + 8 * K3_STAGES;
  const int branch = blockIdx.x >> 6;
  const int rt = (blockIdx.x & 63) >> 2;
  const int ct = blockIdx.x & 3;
  const int warp = threadIdx.x >> 5;
  if (threadIdx.x == 0) { PROF_G(2, 30); PROF_T(2, 0); }
  if (threadIdx.x == 256) {
    const CUtensorMap* mw = branch ? &mwB : &mwA;
    asm volatile("prefetch.tensormap [%0];" ::"l"(mw) : "memory");
    asm volatile("prefetch.tensormap [%0];" ::"l"(&mo) : "memory");
    asm volatile("prefetch.tensormap [%0];" ::"l"(&mout) : "memory");
    for (int i = 0; i < K3_STAGES; i++) {
      mbar_init(bar_full + 8 * i, 1);
      mbar_init(bar_empty + 8 * i, 2);
    }
    for (int i = 0; i < 8; i++) mbar_init(bar_w + 8 * i, 1);
    fence_barrier_init();
    fence_proxy_async();
    for (int kb = 0; kb < K3_WPRE; kb++) {
      mbar_expect_tx(bar_w + 8 * kb, 16384);
      tma_load_2d(sbase + kb * 16384, mw, ct * 128, kb * 64, bar_w + 8 * kb);
      tma_load_2d(sbase + kb * 16384 + 8192, mw, ct * 128 + 64, kb * 64, bar_w + 8 * kb);
    }
  }
  __syncthreads();
  if (warp == 8) {
    if ((threadIdx.x & 31) == 0) {
      const CUtensorMap* mw = branch ? &mwB : &mwA;
      pdl_wait();
      PROF_T(2, 1);
      for (int kb = 0; kb < 8; kb++) {
        const int s = kb % K3_STAGES;
        if (kb >= K3_STAGES) mbar_wait(bar_empty + 8 * s, ((kb / K3_STAGES) - 1) & 1);
        mbar_expect_tx(bar_full + 8 * s, 16384);
        tma_load_2d(sbase + K3_W_BYTES + s * 16384, &mo, kb * 64, branch * S_LEN + rt * 128, bar_full + 8 * s);
        const int kw = kb + K3_WPRE;
        if (kw < 8) {
          mbar_expect_tx(bar_w + 8 * kw, 16384);
          tma_load_2d(sbase + kw * 16384, mw, ct * 128, kw * 64, bar_w + 8 * kw);
          tma_load_2d(sbase + kw * 16384 + 8192, mw, ct * 128 + 64, kw * 64, bar_w + 8 * kw);
        }
      }
    }
  } else {
    const int wg = warp >> 2;
    float acc[64];
    for (int kb = 0; kb < 8; kb++) {
      const int s = kb % K3_STAGES;
      mbar_wait(bar_w + 8 * kb, 0);
      mbar_wait(bar_full + 8 * s, (kb / K3_STAGES) & 1);
      if (threadIdx.x == 0) PROF_T(2, 2 + kb);
      const uint64_t dA = mkdesc(sbase + K3_W_BYTES + s * 16384 + wg * 8192, 16, 1024, 1);
      const uint64_t dB = mkdesc(sbase + kb * 16384, 8192, 1024, 1);
      wg_fence();
#pragma unroll
      for (int k = 0; k < 4; k++) wgmma_ss_n128_tb(acc, dA + k * 2, dB + k * 128, (kb | k) != 0);
      wg_commit();
      if (kb > 0) {
        wg_wait<1>();
        if ((threadIdx.x & 127) == 0) mbar_arrive(bar_empty + 8 * ((kb - 1) % K3_STAGES));
      }
    }
    wg_wait<0>();
    fence_regs(acc);
    if (threadIdx.x == 0) PROF_T(2, 10);
    const uint32_t stg = sbase + K3_W_BYTES + wg * 8192;
    const int lane = threadIdx.x & 31;
    const int rloc = (warp & 3) * 16 + (lane & 15);
#pragma unroll
    for (int c16 = 0; c16 < 8; c16++) {
      const float* a = &acc[c16 * 8];
      const uint32_t r0 = pack_bf16(a[0], a[1]), r1 = pack_bf16(a[2], a[3]), r2 = pack_bf16(a[4], a[5]), r3 = pack_bf16(a[6], a[7]);
      const int chunk = (c16 & 3) * 2 + (lane >> 4);
      const uint32_t addr = stg + (c16 >> 2) * 16384 + rloc * 128 + ((chunk ^ (rloc & 7)) << 4);
      asm volatile("stmatrix.sync.aligned.m8n8.x4.shared.b16 [%0], {%1,%2,%3,%4};" ::"r"(addr), "r"(r0), "r"(r1), "r"(r2), "r"(r3)
                   : "memory");
    }
    fence_proxy_async();
    asm volatile("bar.sync %0, 128;" ::"r"(2 + wg) : "memory");
    if ((threadIdx.x & 127) == 0) {
      tma_store_2d(&mout, stg, branch * DM + ct * 128, rt * 128 + wg * 64);
      tma_store_2d(&mout, stg + 16384, branch * DM + ct * 128 + 64, rt * 128 + wg * 64);
      asm volatile("cp.async.bulk.commit_group;" ::: "memory");
      asm volatile("cp.async.bulk.wait_group.read 0;" ::: "memory");
      if (threadIdx.x == 0) { PROF_T(2, 12); PROF_G(2, 31); }
    }
  }
}

typedef CUresult (*EncodeFn)(CUtensorMap*, CUtensorMapDataType, cuuint32_t, void*, const cuuint64_t*, const cuuint64_t*,
                             const cuuint32_t*, const cuuint32_t*, CUtensorMapInterleave, CUtensorMapSwizzle,
                             CUtensorMapL2promotion, CUtensorMapFloatOOBfill);

void make_map(EncodeFn enc, CUtensorMap* m, const void* ptr, uint64_t inner, uint64_t outer, uint32_t box_inner, uint32_t box_outer) {
  cuuint64_t dims[2] = {inner, outer};
  cuuint64_t strides[1] = {inner * 2};
  cuuint32_t box[2] = {box_inner, box_outer};
  cuuint32_t es[2] = {1, 1};
  enc(m, CU_TENSOR_MAP_DATA_TYPE_BFLOAT16, 2, const_cast<void*>(ptr), dims, strides, box, es, CU_TENSOR_MAP_INTERLEAVE_NONE,
      CU_TENSOR_MAP_SWIZZLE_128B, CU_TENSOR_MAP_L2_PROMOTION_L2_256B, CU_TENSOR_MAP_FLOAT_OOB_FILL_NONE);
}

struct HostState {
  bool init;
  const void* key[7];
  CUtensorMap mxA, mxB, mwA, mwB, mo, mo16, mwoA, mwoB, mout;
};
HostState g_hs;

}

extern "C" void kernel_launch(void* const* d_in, const int* in_sizes, int n_in, void* d_out, int out_size) {
  (void)in_sizes; (void)n_in; (void)out_size;
  HostState& hs = g_hs;
  bool same = hs.init && hs.key[6] == d_out;
  for (int i = 0; i < 6 && same; i++) same = hs.key[i] == d_in[i];
  if (!same) {
    void* fn = nullptr;
    cudaDriverEntryPointQueryResult qr;
    cudaGetDriverEntryPoint("cuTensorMapEncodeTiled", &fn, cudaEnableDefault, &qr);
    EncodeFn enc = (EncodeFn)fn;
    void* go = nullptr;
    cudaGetSymbolAddress(&go, g_o);
    make_map(enc, &hs.mxA, d_in[0], 512, 2048, 64, 128);
    make_map(enc, &hs.mwA, d_in[1], 1536, 512, 64, 32);
    make_map(enc, &hs.mwoA, d_in[2], 512, 512, 64, 64);
    make_map(enc, &hs.mxB, d_in[3], 512, 2048, 64, 128);
    make_map(enc, &hs.mwB, d_in[4], 1536, 512, 64, 32);
    make_map(enc, &hs.mwoB, d_in[5], 512, 512, 64, 64);
    make_map(enc, &hs.mo, go, 512, 4096, 64, 128);
    make_map(enc, &hs.mo16, go, 512, 4096, 64, 16);
    make_map(enc, &hs.mout, d_out, 1024, 2048, 64, 64);
    cudaFuncSetAttribute(qkv_gemm_kernel, cudaFuncAttributeMaxDynamicSharedMemorySize, K1_SMEM);
    cudaFuncSetAttribute(attn_kernel, cudaFuncAttributeMaxDynamicSharedMemorySize, K2_SMEM);
    cudaFuncSetAttribute(out_gemm_kernel, cudaFuncAttributeMaxDynamicSharedMemorySize, K3_SMEM);
    for (int i = 0; i < 6; i++) hs.key[i] = d_in[i];
    hs.key[6] = d_out;
    hs.init = true;
  }
  cudaStream_t st = cudaStreamPerThread;
  {
    cudaLaunchConfig_t cfg = {};
    cfg.gridDim = dim3(128);
    cfg.blockDim = dim3(384);
    cfg.dynamicSmemBytes = K1_SMEM;
    cfg.stream = st;
    cudaLaunchAttribute at[1];
    at[0].id = cudaLaunchAttributeClusterDimension;
    at[0].val.clusterDim.x = 2;
    at[0].val.clusterDim.y = 1;
    at[0].val.clusterDim.z = 1;
    cfg.attrs = at;
    cfg.numAttrs = 1;
    cudaLaunchKernelEx(&cfg, qkv_gemm_kernel, hs.mxA, hs.mxB, hs.mwA, hs.mwB, (const uint8_t*)d_in[0], (const uint8_t*)d_in[3],
                       (const uint8_t*)d_in[1], (const uint8_t*)d_in[4]);
  }
  {
    cudaLaunchConfig_t cfg = {};
    cfg.gridDim = dim3(132);
    cfg.blockDim = dim3(512);
    cfg.dynamicSmemBytes = K2_SMEM;
    cfg.stream = st;
    cudaLaunchAttribute at[1];
    at[0].id = cudaLaunchAttributeProgrammaticStreamSerialization;
    at[0].val.programmaticStreamSerializationAllowed = 1;
    cfg.attrs = at;
    cfg.numAttrs = 1;
    cudaLaunchKernelEx(&cfg, attn_kernel, hs.mo16, (const uint8_t*)d_in[2], (const uint8_t*)d_in[5]);
    cfg.gridDim = dim3(128);
    cfg.blockDim = dim3(288);
    cfg.dynamicSmemBytes = K3_SMEM;
    cudaLaunchKernelEx(&cfg, out_gemm_kernel, hs.mo, hs.mwoA, hs.mwoB, hs.mout);
  }
}
```

```cpp
#include <cuda_runtime.h>
#include <cuda_bf16.h>
#include <cuda.h>
#include <stdint.h>

namespace {

constexpr int S_LEN = 2048;
constexpr int DM = 512;
constexpr int NH = 32;

constexpr int KV_K_BYTES = 65536;
constexpr int KV_HEAD_BYTES = KV_K_BYTES + 98304;
__device__ uint4 g_qfrag[2 * NH * 32 * 128];
__device__ uint4 g_kv[NH * KV_HEAD_BYTES / 16];
__device__ float g_kvpart[16 * NH * 384];
__device__ float g_nrm[NH * 16 * 4];
__device__ __nv_bfloat16 g_o[2 * S_LEN * DM];


__device__ __forceinline__ uint32_t smem_u32(const void* p) { return (uint32_t)__cvta_generic_to_shared(p); }
__device__ __forceinline__ void mbar_init(uint32_t bar, int cnt) {
  asm volatile("mbarrier.init.shared::cta.b64 [%0], %1;" ::"r"(bar), "r"(cnt) : "memory");
}
__device__ __forceinline__ void mbar_expect_tx(uint32_t bar, uint32_t bytes) {
  asm volatile("mbarrier.arrive.expect_tx.shared::cta.b64 _, [%0], %1;" ::"r"(bar), "r"(bytes) : "memory");
}
__device__ __forceinline__ void mbar_arrive(uint32_t bar) {
  asm volatile("mbarrier.arrive.shared::cta.b64 _, [%0];" ::"r"(bar) : "memory");
}
__device__ __forceinline__ void mbar_arrive_cluster(uint32_t bar, uint32_t cta) {
  asm volatile(
      "{\n.reg .b32 ra;\nmapa.shared::cluster.u32 ra, %0, %1;\n"
      "mbarrier.arrive.shared::cluster.b64 _, [ra];\n}" ::"r"(bar), "r"(cta) : "memory");
}
__device__ __forceinline__ void mbar_wait(uint32_t bar, uint32_t parity) {
  asm volatile(
      "{\n.reg .pred p;\n.reg .u32 n;\n"
      "mov.u32 n, 0;\n"
      "WAIT_LOOP:\n"
      "mbarrier.try_wait.parity.shared::cta.b64 p, [%0], %1, 0x10000;\n"
      "@p bra WAIT_DONE;\n"
      "add.u32 n, n, 1;\n"
      "setp.lt.u32 p, n, 100000;\n"
      "@p bra WAIT_LOOP;\n"
      "trap;\n"
      "WAIT_DONE:\n}" ::"r"(bar), "r"(parity) : "memory");
}
__device__ __forceinline__ void fence_barrier_init() {
  asm volatile("fence.mbarrier_init.release.cluster;" ::: "memory");
}
__device__ __forceinline__ void fence_proxy_async() { asm volatile("fence.proxy.async.shared::cta;" ::: "memory"); }
__device__ __forceinline__ void cluster_sync_relaxed() {
  asm volatile("barrier.cluster.arrive.relaxed.aligned;\nbarrier.cluster.wait.aligned;" ::: "memory");
}
__device__ __forceinline__ void tma_load_2d(uint32_t dst, const CUtensorMap* m, int x, int y, uint32_t bar) {
  asm volatile(
      "cp.async.bulk.tensor.2d.shared::cluster.global.mbarrier::complete_tx::bytes [%0], [%1, {%3, %4}], [%2];" ::"r"(dst),
      "l"(m), "r"(bar), "r"(x), "r"(y)
      : "memory");
}
__device__ __forceinline__ void tma_load_2d_mc(uint32_t dst, const CUtensorMap* m, int x, int y, uint32_t bar, uint16_t mask) {
  asm volatile(
      "cp.async.bulk.tensor.2d.shared::cluster.global.mbarrier::complete_tx::bytes.multicast::cluster [%0], [%1, {%3, %4}], "
      "[%2], %5;" ::"r"(dst),
      "l"(m), "r"(bar), "r"(x), "r"(y), "h"(mask)
      : "memory");
}
__device__ __forceinline__ void tma_store_2d(const CUtensorMap* m, uint32_t src, int x, int y) {
  asm volatile("cp.async.bulk.tensor.2d.global.shared::cta.bulk_group [%0, {%2, %3}], [%1];" ::"l"(m), "r"(src), "r"(x),
               "r"(y)
               : "memory");
}
__device__ __forceinline__ void bulk_load(uint32_t dst, const void* src, uint32_t bytes, uint32_t bar) {
  asm volatile("cp.async.bulk.shared::cluster.global.mbarrier::complete_tx::bytes [%0], [%1], %2, [%3];" ::"r"(dst),
               "l"(src), "r"(bytes), "r"(bar)
               : "memory");
}
__device__ __forceinline__ void bulk_store(void* dst, uint32_t src, uint32_t bytes) {
  asm volatile("cp.async.bulk.global.shared::cta.bulk_group [%0], [%1], %2;" ::"l"(dst), "r"(src), "r"(bytes) : "memory");
}
__device__ __forceinline__ void stsm4(uint32_t addr, uint32_t r0, uint32_t r1, uint32_t r2, uint32_t r3) {
  asm volatile("stmatrix.sync.aligned.m8n8.x4.shared.b16 [%0], {%1,%2,%3,%4};" ::"r"(addr), "r"(r0), "r"(r1), "r"(r2), "r"(r3) : "memory");
}
__device__ __forceinline__ void pdl_launch_dependents() { asm volatile("griddepcontrol.launch_dependents;" ::: "memory"); }
__device__ __forceinline__ void pdl_wait() { asm volatile("griddepcontrol.wait;" ::: "memory"); }
__device__ __forceinline__ void wg_fence() { asm volatile("wgmma.fence.sync.aligned;" ::: "memory"); }
__device__ __forceinline__ void wg_commit() { asm volatile("wgmma.commit_group.sync.aligned;" ::: "memory"); }
template <int N>
__device__ __forceinline__ void wg_wait() {
  asm volatile("wgmma.wait_group.sync.aligned %0;" ::"n"(N) : "memory");
}
template <int M>
__device__ __forceinline__ void fence_regs(float (&r)[M]) {
#pragma unroll
  for (int i = 0; i < M; i++) asm volatile("" : "+f"(r[i])::"memory");
}
__device__ __forceinline__ uint64_t mkdesc(uint32_t addr, uint32_t lbo, uint32_t sbo, uint32_t layout) {
  return (uint64_t)((addr & 0x3FFFF) >> 4) | ((uint64_t)(lbo >> 4) << 16) | ((uint64_t)(sbo >> 4) << 32) |
         ((uint64_t)layout << 62);
}
__device__ __forceinline__ uint32_t pack_bf16(float lo, float hi) {
  uint32_t r;
  asm("cvt.rn.bf16x2.f32 %0, %1, %2;" : "=r"(r) : "f"(hi), "f"(lo));
  return r;
}
__device__ __forceinline__ uint32_t pack_f16(float lo, float hi) {
  uint32_t r;
  asm("cvt.rn.f16x2.f32 %0, %1, %2;" : "=r"(r) : "f"(hi), "f"(lo));
  return r;
}
__device__ __forceinline__ float bf_lo(uint32_t v) { return __uint_as_float(v << 16); }
__device__ __forceinline__ float bf_hi(uint32_t v) { return __uint_as_float(v & 0xFFFF0000u); }
__device__ __forceinline__ float round_bf16(float x) { return bf_lo(pack_bf16(x, 0.f)); }
__device__ __forceinline__ float ex2f(float x) {
  float y;
  asm("ex2.approx.ftz.f32 %0, %1;" : "=f"(y) : "f"(x));
  return y;
}

__device__ __forceinline__ void wgmma_rs_n24_tb(float (&d)[12], uint32_t a0, uint32_t a1, uint32_t a2, uint32_t a3, uint64_t descB, int scaleD) {
  asm volatile("{\n.reg .pred p;\nsetp.ne.b32 p, %17, 0;\n"
    "wgmma.mma_async.sync.aligned.m64n24k16.f32.bf16.bf16 "
    "{%0, %1, %2, %3, %4, %5, %6, %7, %8, %9, %10, %11}, {%12, %13, %14, %15}, %16, p, 1, 1, 1;\n}\n"
    : "+f"(d[0]), "+f"(d[1]), "+f"(d[2]), "+f"(d[3]), "+f"(d[4]), "+f"(d[5]), "+f"(d[6]), "+f"(d[7]),
      "+f"(d[8]), "+f"(d[9]), "+f"(d[10]), "+f"(d[11])
    : "r"(a0), "r"(a1), "r"(a2), "r"(a3), "l"(descB), "r"(scaleD));
}
__device__ __forceinline__ void wgmma_rs_n24_tb_h(float (&d)[12], uint32_t a0, uint32_t a1, uint32_t a2, uint32_t a3, uint64_t descB, int scaleD) {
  asm volatile("{\n.reg .pred p;\nsetp.ne.b32 p, %17, 0;\n"
    "wgmma.mma_async.sync.aligned.m64n24k16.f32.f16.f16 "
    "{%0, %1, %2, %3, %4, %5, %6, %7, %8, %9, %10, %11}, {%12, %13, %14, %15}, %16, p, 1, 1, 1;\n}\n"
    : "+f"(d[0]), "+f"(d[1]), "+f"(d[2]), "+f"(d[3]), "+f"(d[4]), "+f"(d[5]), "+f"(d[6]), "+f"(d[7]),
      "+f"(d[8]), "+f"(d[9]), "+f"(d[10]), "+f"(d[11])
    : "r"(a0), "r"(a1), "r"(a2), "r"(a3), "l"(descB), "r"(scaleD));
}
__device__ __forceinline__ void wgmma_rs_n64_z(float (&d)[32], uint32_t a0, uint32_t a1, uint32_t a2, uint32_t a3, uint64_t descB) {
  asm volatile("{\n.reg .pred p;\nsetp.ne.b32 p, %37, 0;\n"
    "wgmma.mma_async.sync.aligned.m64n64k16.f32.bf16.bf16 "
    "{%0, %1, %2, %3, %4, %5, %6, %7, %8, %9, %10, %11, %12, %13, %14, %15, %16, %17, %18, %19, %20, %21, %22, %23, %24, %25, %26, %27, %28, %29, %30, %31}, {%32, %33, %34, %35}, %36, p, 1, 1, 0;\n}\n"
    : "=f"(d[0]), "=f"(d[1]), "=f"(d[2]), "=f"(d[3]), "=f"(d[4]), "=f"(d[5]), "=f"(d[6]), "=f"(d[7]),
      "=f"(d[8]), "=f"(d[9]), "=f"(d[10]), "=f"(d[11]), "=f"(d[12]), "=f"(d[13]), "=f"(d[14]), "=f"(d[15]),
      "=f"(d[16]), "=f"(d[17]), "=f"(d[18]), "=f"(d[19]), "=f"(d[20]), "=f"(d[21]), "=f"(d[22]), "=f"(d[23]),
      "=f"(d[24]), "=f"(d[25]), "=f"(d[26]), "=f"(d[27]), "=f"(d[28]), "=f"(d[29]), "=f"(d[30]), "=f"(d[31])
    : "r"(a0), "r"(a1), "r"(a2), "r"(a3), "l"(descB), "n"(0));
}
__device__ __forceinline__ void wgmma_ss_n128_tb(float (&d)[64], uint64_t descA, uint64_t descB, int scaleD) {
  asm volatile("{\n.reg .pred p;\nsetp.ne.b32 p, %66, 0;\n"
    "wgmma.mma_async.sync.aligned.m64n128k16.f32.bf16.bf16 "
    "{%0, %1, %2, %3, %4, %5, %6, %7, %8, %9, %10, %11, %12, %13, %14, %15, %16, %17, %18, %19, %20, %21, %22, %23, %24, %25, %26, %27, %28, %29, %30, %31, %32, %33, %34, %35, %36, %37, %38, %39, %40, %41, %42, %43, %44, %45, %46, %47, %48, %49, %50, %51, %52, %53, %54, %55, %56, %57, %58, %59, %60, %61, %62, %63}, %64, %65, p, 1, 1, 0, 1;\n}\n"
    : "+f"(d[0]), "+f"(d[1]), "+f"(d[2]), "+f"(d[3]), "+f"(d[4]), "+f"(d[5]), "+f"(d[6]), "+f"(d[7]),
      "+f"(d[8]), "+f"(d[9]), "+f"(d[10]), "+f"(d[11]), "+f"(d[12]), "+f"(d[13]), "+f"(d[14]), "+f"(d[15]),
      "+f"(d[16]), "+f"(d[17]), "+f"(d[18]), "+f"(d[19]), "+f"(d[20]), "+f"(d[21]), "+f"(d[22]), "+f"(d[23]),
      "+f"(d[24]), "+f"(d[25]), "+f"(d[26]), "+f"(d[27]), "+f"(d[28]), "+f"(d[29]), "+f"(d[30]), "+f"(d[31]),
      "+f"(d[32]), "+f"(d[33]), "+f"(d[34]), "+f"(d[35]), "+f"(d[36]), "+f"(d[37]), "+f"(d[38]), "+f"(d[39]),
      "+f"(d[40]), "+f"(d[41]), "+f"(d[42]), "+f"(d[43]), "+f"(d[44]), "+f"(d[45]), "+f"(d[46]), "+f"(d[47]),
      "+f"(d[48]), "+f"(d[49]), "+f"(d[50]), "+f"(d[51]), "+f"(d[52]), "+f"(d[53]), "+f"(d[54]), "+f"(d[55]),
      "+f"(d[56]), "+f"(d[57]), "+f"(d[58]), "+f"(d[59]), "+f"(d[60]), "+f"(d[61]), "+f"(d[62]), "+f"(d[63])
    : "l"(descA), "l"(descB), "r"(scaleD));
}
__device__ __forceinline__ void wgmma_ss_n192_tb(float (&d)[96], uint64_t descA, uint64_t descB, int scaleD) {
  asm volatile("{\n.reg .pred p;\nsetp.ne.b32 p, %98, 0;\n"
    "wgmma.mma_async.sync.aligned.m64n192k16.f32.bf16.bf16 "
    "{%0, %1, %2, %3, %4, %5, %6, %7, %8, %9, %10, %11, %12, %13, %14, %15, %16, %17, %18, %19, %20, %21, %22, %23, %24, %25, %26, %27, %28, %29, %30, %31, %32, %33, %34, %35, %36, %37, %38, %39, %40, %41, %42, %43, %44, %45, %46, %47, %48, %49, %50, %51, %52, %53, %54, %55, %56, %57, %58, %59, %60, %61, %62, %63, %64, %65, %66, %67, %68, %69, %70, %71, %72, %73, %74, %75, %76, %77, %78, %79, %80, %81, %82, %83, %84, %85, %86, %87, %88, %89, %90, %91, %92, %93, %94, %95}, %96, %97, p, 1, 1, 0, 1;\n}\n"
    : "+f"(d[0]), "+f"(d[1]), "+f"(d[2]), "+f"(d[3]), "+f"(d[4]), "+f"(d[5]), "+f"(d[6]), "+f"(d[7]),
      "+f"(d[8]), "+f"(d[9]), "+f"(d[10]), "+f"(d[11]), "+f"(d[12]), "+f"(d[13]), "+f"(d[14]), "+f"(d[15]),
      "+f"(d[16]), "+f"(d[17]), "+f"(d[18]), "+f"(d[19]), "+f"(d[20]), "+f"(d[21]), "+f"(d[22]), "+f"(d[23]),
      "+f"(d[24]), "+f"(d[25]), "+f"(d[26]), "+f"(d[27]), "+f"(d[28]), "+f"(d[29]), "+f"(d[30]), "+f"(d[31]),
      "+f"(d[32]), "+f"(d[33]), "+f"(d[34]), "+f"(d[35]), "+f"(d[36]), "+f"(d[37]), "+f"(d[38]), "+f"(d[39]),
      "+f"(d[40]), "+f"(d[41]), "+f"(d[42]), "+f"(d[43]), "+f"(d[44]), "+f"(d[45]), "+f"(d[46]), "+f"(d[47]),
      "+f"(d[48]), "+f"(d[49]), "+f"(d[50]), "+f"(d[51]), "+f"(d[52]), "+f"(d[53]), "+f"(d[54]), "+f"(d[55]),
      "+f"(d[56]), "+f"(d[57]), "+f"(d[58]), "+f"(d[59]), "+f"(d[60]), "+f"(d[61]), "+f"(d[62]), "+f"(d[63]),
      "+f"(d[64]), "+f"(d[65]), "+f"(d[66]), "+f"(d[67]), "+f"(d[68]), "+f"(d[69]), "+f"(d[70]), "+f"(d[71]),
      "+f"(d[72]), "+f"(d[73]), "+f"(d[74]), "+f"(d[75]), "+f"(d[76]), "+f"(d[77]), "+f"(d[78]), "+f"(d[79]),
      "+f"(d[80]), "+f"(d[81]), "+f"(d[82]), "+f"(d[83]), "+f"(d[84]), "+f"(d[85]), "+f"(d[86]), "+f"(d[87]),
      "+f"(d[88]), "+f"(d[89]), "+f"(d[90]), "+f"(d[91]), "+f"(d[92]), "+f"(d[93]), "+f"(d[94]), "+f"(d[95])
    : "l"(descA), "l"(descB), "r"(scaleD));
}

__device__ __forceinline__ void hmma(float (&c)[4], uint32_t a0, uint32_t a1, uint32_t a2, uint32_t a3, uint32_t b0, uint32_t b1) {
  asm("mma.sync.aligned.m16n8k16.row.col.f32.bf16.bf16.f32 {%0,%1,%2,%3}, {%4,%5,%6,%7}, {%8,%9}, {%0,%1,%2,%3};"
      : "+f"(c[0]), "+f"(c[1]), "+f"(c[2]), "+f"(c[3])
      : "r"(a0), "r"(a1), "r"(a2), "r"(a3), "r"(b0), "r"(b1));
}

__device__ __forceinline__ uint32_t movm(uint32_t a) {
  uint32_t d;
  asm volatile("movmatrix.sync.aligned.m8n8.trans.b16 %0, %1;" : "=r"(d) : "r"(a));
  return d;
}


constexpr int K1_STAGES = 4;
constexpr int K1_W_BYTES = 3 * 8192;
constexpr int K1_X_BYTES = 8 * 16384;
constexpr int K1_BAR_OFF = K1_X_BYTES + K1_STAGES * K1_W_BYTES;
constexpr int K1_SMEM = K1_BAR_OFF + 192 + 1024;
constexpr float QSCALE = 0.25f * 1.4426950408889634f;

__device__ __forceinline__ uint32_t phi2(uint32_t t2) {
  uint32_t a2, mask, r2, o2;
  asm("add.rn.bf16x2 %0, %1, %2;" : "=r"(a2) : "r"(t2), "r"(0x3F803F80u));
  const uint32_t e2 = pack_bf16(ex2f(bf_lo(t2) * 1.4426950408889634f), ex2f(bf_hi(t2) * 1.4426950408889634f));
  asm("set.gt.u32.bf16x2 %0, %1, %2;" : "=r"(mask) : "r"(t2), "r"(0u));
  r2 = (a2 & mask) | (e2 & ~mask);
  asm("add.rn.bf16x2 %0, %1, %2;" : "=r"(o2) : "r"(r2), "r"(0x35863586u));
  return o2;
}

#define K1_SLOT_KB(h) ((h) < 4 ? 2 * (h) : 2 * ((h) - 4) + 1)
struct EpiCtx {
  uint4* qf;
  uint8_t* img;
  int voff;
  uint32_t stg;
  uint32_t s_red_addr;
  float* red;
  int lane, wg;
};

struct EpiState {
  float nrm[16];
  uint32_t vb[4];
  uint32_t pk[16];
  uint32_t vt[8];
};

template <bool LINEAR, int S>
__device__ __forceinline__ void epi_slice(const float (&acc)[96], const EpiCtx& c, EpiState& st) {
  if constexpr (!LINEAR) {
    const int w = (threadIdx.x >> 5) & 3;
    if constexpr (S == 0) {
#pragma unroll
      for (int i = 0; i < 8; i++) {
        const float* a = &acc[i * 8];
        st.nrm[2 * i] = a[0] * a[0] + a[1] * a[1] + a[4] * a[4] + a[5] * a[5];
        st.nrm[2 * i + 1] = a[2] * a[2] + a[3] * a[3] + a[6] * a[6] + a[7] * a[7];
      }
#pragma unroll
      for (int h = 0; h < 4; h++) {
        uint32_t m = 0;
#pragma unroll
        for (int i = 0; i < 8; i++) m = max(m, __float_as_uint(acc[64 + h * 8 + i]) & 0x7FFFFFFFu);
        st.vb[h] = m;
      }
#pragma unroll
      for (int h = 0; h < 4; h++) st.vb[h] = __reduce_max_sync(0xffffffffu, st.vb[h]);
    } else if constexpr (S <= 4) {
      constexpr int h = S - 1;
      const float* a = &acc[h * 8];
      const float* k = &acc[32 + h * 8];
      const float* v = &acc[64 + h * 8];
      const uint32_t base = c.stg + h * 16384;
      const int mi = c.lane >> 3, r = c.lane & 7;
      asm volatile("st.shared.v4.u32 [%0], {%1, %2, %3, %4};" ::"r"(base + 5120 + (threadIdx.x & 127) * 16), "r"(pack_bf16(a[0], a[1])),
                   "r"(pack_bf16(a[2], a[3])), "r"(pack_bf16(a[4], a[5])), "r"(pack_bf16(a[6], a[7]))
                   : "memory");
      stsm4(base + (w * 2 + (mi & 1)) * 256 + (mi >> 1) * 128 + r * 16, pack_bf16(k[0], k[1]), pack_bf16(k[2], k[3]), pack_bf16(k[4], k[5]),
            pack_bf16(k[6], k[7]));
      const uint32_t vaddr = base + 2048 + (w * 2 + (mi & 1)) * 384 + (mi >> 1) * 128 + r * 16;
      const uint32_t oaddr = base + 2048 + w * 768 + 256 + c.lane * 4;
      uint32_t one;
      if (st.vb[h] <= 0x476A6000u   && (st.vb[h] >= 0x3A800000u   || st.vb[h] == 0)) {
        stsm4(vaddr, pack_f16(v[0], v[1]), pack_f16(v[2], v[3]), pack_f16(v[4], v[5]), pack_f16(v[6], v[7]));
        one = 0x3C003C00u;
      } else {
        stsm4(vaddr, pack_bf16(v[0], v[1]), pack_bf16(v[2], v[3]), pack_bf16(v[4], v[5]), pack_bf16(v[6], v[7]));
        one = 0x3F803F80u;
        if (c.lane == 0) asm volatile("red.shared.max.u32 [%0], 1;" ::"r"(c.s_red_addr + h * 16 + 12) : "memory");
      }
      asm volatile("st.shared.u32 [%0], %1;\nst.shared.u32 [%0+384], %1;" ::"r"(oaddr), "r"(one) : "memory");
    } else if constexpr (S == 5) {
      fence_proxy_async();
      asm volatile("bar.sync %0, 128;" ::"r"(2 + c.wg) : "memory");
      if (c.lane == 0) {
        uint8_t* img = c.img + (size_t)w * KV_HEAD_BYTES;
        const uint32_t base = c.stg + w * 16384;
        bulk_store(img, base, 2048);
        bulk_store(img + c.voff, base + 2048, 3072);
        bulk_store(c.qf - (threadIdx.x & 127) + w * 32 * 128, base + 5120, 2048);
        asm volatile("cp.async.bulk.commit_group;" ::: "memory");
      }
    } else if constexpr (S == 6) {
#pragma unroll
      for (int o = 1; o <= 2; o <<= 1) {
#pragma unroll
        for (int i = 0; i < 16; i++) st.nrm[i] += __shfl_xor_sync(0xffffffffu, st.nrm[i], o);
      }
    } else {
      uint32_t m[8];
#pragma unroll
      for (int i = 0; i < 8; i++)
        m[i] = __reduce_max_sync(0xffffffffu, max(__float_as_uint(st.nrm[2 * i]) & 0x7FFFFFFFu, __float_as_uint(st.nrm[2 * i + 1]) & 0x7FFFFFFFu));
#pragma unroll
      for (int h = 0; h < 4; h++) {
        asm volatile(
            "{\n.reg .pred p;\nsetp.ne.b32 p, %4, 0;\n"
            "@p red.shared.max.u32 [%0], %2;\n@p red.shared.max.u32 [%1], %3;\n}" ::"r"(c.s_red_addr + h * 16 + c.wg * 4),
            "r"(c.s_red_addr + h * 16 + 8), "r"(m[h]), "r"(m[4 + h]), "r"(c.lane == 0 ? 1 : 0)
            : "memory");
      }
    }
  } else {
    if constexpr (S == 0) {
#pragma unroll
      for (int h = 0; h < 4; h++) {
        const float* a = &acc[h * 8];
        c.qf[h * 32 * 128] = make_uint4(pack_bf16(a[0], a[1]), pack_bf16(a[2], a[3]), pack_bf16(a[4], a[5]), pack_bf16(a[6], a[7]));
      }
    } else if constexpr (S == 1 || S == 2) {
#pragma unroll
      for (int i = (S - 1) * 8; i < S * 8; i++) st.pk[i] = phi2(pack_bf16(acc[32 + 2 * i], acc[32 + 2 * i + 1]));
    } else if constexpr (S == 3) {
#pragma unroll
      for (int h = 0; h < 4; h++) {
        const uint32_t a0 = movm(st.pk[4 * h]), a2 = movm(st.pk[4 * h + 1]), a1 = movm(st.pk[4 * h + 2]), a3 = movm(st.pk[4 * h + 3]);
        st.pk[4 * h] = a0;
        st.pk[4 * h + 1] = a1;
        st.pk[4 * h + 2] = a2;
        st.pk[4 * h + 3] = a3;
      }
    } else if constexpr (S == 4 || S == 6) {
#pragma unroll
      for (int i = 0; i < 8; i++) st.vt[i] = movm(pack_bf16(acc[64 + (S - 4) * 8 + 2 * i], acc[64 + (S - 4) * 8 + 2 * i + 1]));
    } else {
#pragma unroll
      for (int j = 0; j < 2; j++) {
        const int h = (S - 5) + j;
        float c0[4] = {0, 0, 0, 0}, c1[4] = {0, 0, 0, 0}, c2[4] = {0, 0, 0, 0};
        hmma(c0, st.pk[4 * h], st.pk[4 * h + 1], st.pk[4 * h + 2], st.pk[4 * h + 3], st.vt[4 * j], st.vt[4 * j + 1]);
        hmma(c1, st.pk[4 * h], st.pk[4 * h + 1], st.pk[4 * h + 2], st.pk[4 * h + 3], st.vt[4 * j + 2], st.vt[4 * j + 3]);
        hmma(c2, st.pk[4 * h], st.pk[4 * h + 1], st.pk[4 * h + 2], st.pk[4 * h + 3], 0x3F803F80u, 0x3F803F80u);
        float* slot = c.red + h * 2 * 4096;
#pragma unroll
        for (int i = 0; i < 4; i++) {
          slot[i * 32] = c0[i];
          slot[(4 + i) * 32] = c1[i];
          slot[(8 + i) * 32] = c2[i];
        }
      }
    }
  }
}

template <bool LINEAR>
__device__ __forceinline__ void qkv_consumer(uint32_t sbase, uint8_t* smem_gen, uint32_t* s_red, int cp, int rt) {
  const uint32_t bar_full = sbase + K1_BAR_OFF;
  const uint32_t bar_empty = bar_full + 8 * K1_STAGES;
  const int warp = threadIdx.x >> 5;
  const int wg = warp >> 2;
  const int lane = threadIdx.x & 31;
  float acc0[96], acc1[96];
  EpiCtx c;
  {
    c.qf = g_qfrag + ((size_t)((LINEAR ? NH : 0) + cp * 8) * 32 + (rt * 2 + wg)) * 128 + (threadIdx.x & 127);
    const int grp0 = (rt * 128 + wg * 64) >> 3;
    c.img = reinterpret_cast<uint8_t*>(g_kv) + (size_t)(cp * 8) * KV_HEAD_BYTES + grp0 * 256;
    c.voff = KV_K_BYTES + grp0 * 128;
    c.stg = sbase + wg * 8192;
    c.s_red_addr = smem_u32(s_red);
    c.red = reinterpret_cast<float*>(smem_gen + wg * 8192) + (warp & 3) * 384 + lane;
    c.lane = lane;
    c.wg = wg;
  }
  EpiState es;
#pragma unroll 1
  for (int kb = 0; kb < 8; kb++) {
    const int s = kb % K1_STAGES;
    mbar_wait(bar_full + 8 * s, (kb / K1_STAGES) & 1);
    const uint64_t dA = mkdesc(sbase + kb * 16384 + wg * 8192, 16, 1024, 1);
    const uint64_t dB = mkdesc(sbase + K1_X_BYTES + s * K1_W_BYTES, 8192, 1024, 1);
    wg_fence();
#pragma unroll
    for (int k = 0; k < 4; k++) wgmma_ss_n192_tb(acc0, dA + k * 2, dB + k * 128, (kb | k) != 0);
    wg_commit();
    if (kb > 0) {
      wg_wait<1>();
      if ((threadIdx.x & 127) == 0) {
        const int sp = (kb - 1) % K1_STAGES;
        mbar_arrive_cluster(bar_empty + 8 * sp, 0);
        mbar_arrive_cluster(bar_empty + 8 * sp, 1);
      }
    }
  }
  wg_wait<0>();
  fence_regs(acc0);
  if ((threadIdx.x & 127) == 0) {
    mbar_arrive_cluster(bar_empty + 8 * (7 % K1_STAGES), 0);
    mbar_arrive_cluster(bar_empty + 8 * (7 % K1_STAGES), 1);
  }
#define K1_T1_ISSUE(KB)                                                                                            \
  {                                                                                                                \
    constexpr int g = 8 + (KB);                                                                                    \
    constexpr int s = g % K1_STAGES;                                                                               \
    mbar_wait(bar_full + 8 * s, (g / K1_STAGES) & 1);                                                              \
    const uint64_t dA = mkdesc(sbase + (KB) * 16384 + wg * 8192, 16, 1024, 1);                                     \
    const uint64_t dB = mkdesc(sbase + K1_X_BYTES + s * K1_W_BYTES, 8192, 1024, 1);                                \
    wg_fence();                                                                                                    \
    _Pragma("unroll") for (int k = 0; k < 4; k++) wgmma_ss_n192_tb(acc1, dA + k * 2, dB + k * 128, ((KB) | k) != 0); \
    wg_commit();                                                                                                   \
  }
#define K1_T1_STEP(KB)                                                                                             \
  {                                                                                                                \
    if (KB + 1 < 8) K1_T1_ISSUE((KB + 1) & 7)                                                                      \
    epi_slice<LINEAR, KB>(acc0, c, es);                                                          \
    if (KB + 1 < 8) wg_wait<1>();                                                                                  \
    else wg_wait<0>();                                                                                             \
    if (KB + K1_STAGES < 8 && (threadIdx.x & 127) == 0) {                                                          \
      mbar_arrive_cluster(bar_empty + 8 * ((8 + KB) % K1_STAGES), 0);                                              \
      mbar_arrive_cluster(bar_empty + 8 * ((8 + KB) % K1_STAGES), 1);                                              \
    }                                                                                                              \
  }
  K1_T1_ISSUE(0)
  K1_T1_STEP(0) K1_T1_STEP(1) K1_T1_STEP(2) K1_T1_STEP(3) K1_T1_STEP(4) K1_T1_STEP(5) K1_T1_STEP(6) K1_T1_STEP(7)
#undef K1_T1_STEP
#undef K1_T1_ISSUE
  fence_regs(acc1);
  c.qf += 4 * 32 * 128;
  c.img += 4 * (size_t)KV_HEAD_BYTES;
  c.stg += 4 * 16384;
  c.s_red_addr += 64;
  c.red += 4096;
  epi_slice<LINEAR, 0>(acc1, c, es);
  epi_slice<LINEAR, 1>(acc1, c, es);
  epi_slice<LINEAR, 2>(acc1, c, es);
  epi_slice<LINEAR, 3>(acc1, c, es);
  epi_slice<LINEAR, 4>(acc1, c, es);
  epi_slice<LINEAR, 5>(acc1, c, es);
  epi_slice<LINEAR, 6>(acc1, c, es);
  epi_slice<LINEAR, 7>(acc1, c, es);
  if (!LINEAR) {
    if (lane == 0) asm volatile("cp.async.bulk.wait_group.read 0;" ::: "memory");
    asm volatile("bar.sync 1, 256;" ::: "memory");
    if (threadIdx.x < 8) {
      *reinterpret_cast<uint4*>(&g_nrm[((cp * 8 + threadIdx.x) * 16 + rt) * 4]) =
          make_uint4(s_red[threadIdx.x * 4], s_red[threadIdx.x * 4 + 1], s_red[threadIdx.x * 4 + 2], s_red[threadIdx.x * 4 + 3]);
    }
  } else {
    asm volatile("bar.sync 1, 256;" ::: "memory");
    float* dst = g_kvpart + ((size_t)rt * NH + cp * 8) * 384 + threadIdx.x;
    const float* base = reinterpret_cast<const float*>(smem_gen);
#pragma unroll
    for (int i = 0; i < 12; i++) {
      const int h0 = (i / 3) * 2, r = i % 3;
      const bool second = r == 2 || (r == 1 && threadIdx.x >= 128);
      const int e = (int)threadIdx.x + r * 256 - (second ? 384 : 0);
      const float* src = base + (second ? K1_SLOT_KB(h0 + 1) : K1_SLOT_KB(h0)) * 4096 + e;
      float sum = 0.f;
#pragma unroll
      for (int w = 0; w < 8; w++) sum += src[(w >> 2) * 2048 + (w & 3) * 384];
      dst[i * 256] = sum;
    }
  }
}

__global__ void __launch_bounds__(384, 1)
qkv_gemm_kernel(const __grid_constant__ CUtensorMap mxA, const __grid_constant__ CUtensorMap mxB,
                const __grid_constant__ CUtensorMap mwA, const __grid_constant__ CUtensorMap mwB) {
  extern __shared__ uint8_t smem_raw[];
  const uint32_t sbase = (smem_u32(smem_raw) + 1023) & ~1023u;
  uint8_t* smem_gen = smem_raw + (sbase - smem_u32(smem_raw));
  const uint32_t bar_full = sbase + K1_BAR_OFF;
  const uint32_t bar_empty = bar_full + 8 * K1_STAGES;
  uint32_t* s_red = reinterpret_cast<uint32_t*>(smem_gen + K1_BAR_OFF + 64);

  const int rank = blockIdx.x & 1;
  const int pair = blockIdx.x >> 1;
  const int branch = pair >> 5;
  const int rp = (pair & 31) >> 2;
  const int cp = pair & 3;
  const int rt = rp * 2 + rank;
  const int warp = threadIdx.x >> 5;
  const CUtensorMap* mx = branch ? &mxA : &mxB;
  const CUtensorMap* mw = branch ? &mwA : &mwB;

  if (threadIdx.x == 256) {
    asm volatile("prefetch.tensormap [%0];" ::"l"(mx) : "memory");
    asm volatile("prefetch.tensormap [%0];" ::"l"(mw) : "memory");
    for (int i = 0; i < K1_STAGES; i++) {
      mbar_init(bar_full + 8 * i, 1);
      mbar_init(bar_empty + 8 * i, 4);
    }
    fence_barrier_init();
    fence_proxy_async();
    for (int kb = 0; kb < K1_STAGES; kb++) mbar_expect_tx(bar_full + 8 * kb, 16384 + K1_W_BYTES);
    tma_load_2d(sbase, mx, 0, rt * 128, bar_full);
  }
  pdl_launch_dependents();
  if (threadIdx.x < 32) s_red[threadIdx.x] = 0;
  __syncthreads();
  cluster_sync_relaxed();

  if (warp >= 8) {
    asm volatile("setmaxnreg.dec.sync.aligned.u32 40;");
    if (threadIdx.x == 256) {
      for (int g = 0; g < 16; g++) {
        const int s = g % K1_STAGES;
        const int kb = g & 7;
        if (g >= K1_STAGES) {
          mbar_wait(bar_empty + 8 * s, ((g / K1_STAGES) - 1) & 1);
          mbar_expect_tx(bar_full + 8 * s, (g < 8 ? 16384 : 0) + K1_W_BYTES);
        }
        if (g > 0 && g < 8) tma_load_2d(sbase + kb * 16384, mx, kb * 64, rt * 128, bar_full + 8 * s);
        const int h0 = cp * 8 + (g >> 3) * 4;
        const uint32_t st = sbase + K1_X_BYTES + s * K1_W_BYTES + rank * 4096;
#pragma unroll
        for (int p = 0; p < 3; p++)
          tma_load_2d_mc(st + p * 8192, mw, p * 512 + h0 * 16, kb * 64 + rank * 32, bar_full + 8 * s, (uint16_t)3);
      }
    }
    __syncwarp();
    cluster_sync_relaxed();
  } else {
    asm volatile("setmaxnreg.inc.sync.aligned.u32 232;");
    if (branch == 0) qkv_consumer<false>(sbase, smem_gen, s_red, cp, rt);
    else qkv_consumer<true>(sbase, smem_gen, s_red, cp, rt);
    __syncwarp();
    cluster_sync_relaxed();
  }
}

constexpr int K2_SMEM = KV_HEAD_BYTES + 1024 + 256;

constexpr int ATT_MASK_A = 0x5b5b;
constexpr int ATT_MASK_B = 0xd56a;
constexpr int ATT_CH = 8;

struct ExpC {
  uint32_t k3c00, c2;
};
__device__ __forceinline__ uint32_t hfma2(uint32_t a, uint32_t b, uint32_t c) {
  uint32_t r;
  asm("fma.rn.f16x2 %0, %1, %2, %3;" : "=r"(r) : "r"(a), "r"(b), "r"(c));
  return r;
}
__device__ __forceinline__ uint32_t exp2_poly_pair(float t0, float t1, const ExpC& c) {
  uint32_t u, m, r;
  asm("prmt.b32 %0, %1, %2, 0x5410;" : "=r"(u) : "r"(__float_as_uint(t0)), "r"(__float_as_uint(t1)));
  asm("lop3.b32 %0, %1, 0x03FF03FF, %2, 0xEA;" : "=r"(m) : "r"(u), "r"(c.k3c00));
  uint32_t p = hfma2(m, c.c2, 0xa39da39du);
  p = hfma2(p, m, 0x39713971u);
  asm("lop3.b32 %0, %1, %2, 0xFC00FC00, 0xE4;" : "=r"(r) : "r"(u), "r"(p));
  return r;
}
__device__ __forceinline__ float gadd(float x, float M, uint32_t g) {
  float r = x;
  asm("{.reg .pred p; setp.ne.b32 p, %2, -1; @p add.f32 %0, %0, %1;}" : "+f"(r) : "f"(M), "r"(g));
  return r;
}
__device__ __forceinline__ float gex2(float x, uint32_t g) {
  float r = x;
  asm("{.reg .pred p; setp.ne.b32 p, %1, -1; @p ex2.approx.ftz.f32 %0, %0;}" : "+f"(r) : "r"(g));
  return r;
}
__host__ __device__ constexpr bool is_poly(int i, int mask) { return (mask >> i) & 1; }
template <int MASK>
__device__ __forceinline__ void exp_tile(const float (&s)[32], uint32_t (&p)[16], const ExpC& c) {
#pragma unroll
  for (int i = 0; i < 16; i++) {
    const bool gated = i >= ATT_CH;
    int gi = ATT_CH - 1;
    while (gi > 0 && !is_poly(gi, MASK)) gi--;
    if (!is_poly(i, MASK)) {
      if (gated) p[i] = pack_f16(gex2(s[2 * i], p[gi]), gex2(s[2 * i + 1], p[gi]));
      else p[i] = pack_f16(ex2f(s[2 * i]), ex2f(s[2 * i + 1]));
    } else {
      if (gated) p[i] = exp2_poly_pair(gadd(s[2 * i], 12303.f, p[gi]), gadd(s[2 * i + 1], 12303.f, p[gi]), c);
      else p[i] = exp2_poly_pair(s[2 * i] + 12303.f, s[2 * i + 1] + 12303.f, c);
    }
  }
}

__device__ __forceinline__ void store_o(__nv_bfloat16* o, int row0, int head, int lane, const uint32_t (&r)[4]) {
  const int g = lane >> 2, t = lane & 3;
  uint32_t* p0 = reinterpret_cast<uint32_t*>(o + (size_t)(row0 + g) * DM + head * 16) + t;
  uint32_t* p1 = reinterpret_cast<uint32_t*>(o + (size_t)(row0 + g + 8) * DM + head * 16) + t;
  p0[0] = r[0];
  p1[0] = r[1];
  p0[4] = r[2];
  p1[4] = r[3];
}

__device__ __forceinline__ void kv_fetch_piece(uint32_t sbase, uint32_t bar, int piece) {
  const uint8_t* img = reinterpret_cast<const uint8_t*>(g_kv) + (size_t)(blockIdx.x >> 2) * KV_HEAD_BYTES;
  const int g = piece >> 1, isv = piece & 1;
  const int e0 = g == 0 ? 0 : (isv ? 256 : 320) + (g - 1) * 512;
  const int e1 = g == 3 ? 2048 : (isv ? 256 : 320) + g * 512;
  const int bytes = (e1 - e0) * (isv ? 48 : 32);
  const int off = isv ? KV_K_BYTES + e0 * 48 : e0 * 32;
  mbar_expect_tx(bar + 8 * g, bytes);
  bulk_load(sbase + off, img + off, bytes, bar + 8 * g);
}

__device__ __forceinline__ void safe_exp(float (&s)[32], float (&e)[32], float (&o)[12], float& m0, float& m1) {
#pragma unroll
  for (int i = 0; i < 16; i++) {
    const uint32_t r = pack_bf16(s[2 * i], s[2 * i + 1]);
    s[2 * i] = bf_lo(r) * QSCALE;
    s[2 * i + 1] = bf_hi(r) * QSCALE;
  }
  float x0 = s[0], x1 = s[2];
#pragma unroll
  for (int i = 0; i < 8; i++) {
    x0 = fmaxf(x0, fmaxf(s[4 * i], s[4 * i + 1]));
    x1 = fmaxf(x1, fmaxf(s[4 * i + 2], s[4 * i + 3]));
  }
  x0 = fmaxf(x0, __shfl_xor_sync(0xffffffffu, x0, 1));
  x1 = fmaxf(x1, __shfl_xor_sync(0xffffffffu, x1, 1));
  x0 = fmaxf(x0, __shfl_xor_sync(0xffffffffu, x0, 2));
  x1 = fmaxf(x1, __shfl_xor_sync(0xffffffffu, x1, 2));
  const float n0 = fmaxf(m0, x0), n1 = fmaxf(m1, x1);
  const float c0 = ex2f(m0 - n0), c1 = ex2f(m1 - n1);
  m0 = n0;
  m1 = n1;
#pragma unroll
  for (int i = 0; i < 3; i++) {
    o[4 * i] *= c0;
    o[4 * i + 1] *= c0;
    o[4 * i + 2] *= c1;
    o[4 * i + 3] *= c1;
  }
#pragma unroll
  for (int i = 0; i < 8; i++) {
    e[4 * i] = ex2f(s[4 * i] - n0);
    e[4 * i + 1] = ex2f(s[4 * i + 1] - n0);
    e[4 * i + 2] = ex2f(s[4 * i + 2] - n1);
    e[4 * i + 3] = ex2f(s[4 * i + 3] - n1);
  }
}

template <int MASK>
__device__ __forceinline__ void wide_exp(const float (&s)[32], uint32_t (&p)[16], const ExpC& c, float sh) {
  const float msh = 12303.f - sh;
#pragma unroll
  for (int i = 0; i < 16; i++) {
    if (!is_poly(i, MASK)) p[i] = pack_f16(ex2f(s[2 * i] - sh), ex2f(s[2 * i + 1] - sh));
    else p[i] = exp2_poly_pair(fmaxf(s[2 * i] + msh, 12288.f), fmaxf(s[2 * i + 1] + msh, 12288.f), c);
  }
}
template <bool WIDE>
__device__ __forceinline__ void attn_step(float (&sx)[32], float (&sy)[32], float (&o)[12], const uint4& qf, uint64_t dK, uint64_t dV,
                                          const ExpC& ec, float sh) {
  uint32_t pa[16], pb[16];
  if (WIDE) {
    const float dn = ex2f(-sh);
#pragma unroll
    for (int i = 0; i < 12; i++) o[i] *= dn;
  }
  wg_fence();
  wgmma_rs_n64_z(sy, qf.x, qf.y, qf.z, qf.w, dK + 128);
  wg_commit();
  if (WIDE) wide_exp<ATT_MASK_A>(sx, pa, ec, sh);
  else exp_tile<ATT_MASK_A>(sx, pa, ec);
  wg_fence();
  wgmma_rs_n24_tb_h(o, pa[12], pa[13], pa[14], pa[15], dV + 3 * 48, 1);
  wg_commit();
  wg_wait<1>();
  fence_regs(sy);
  if (WIDE) wide_exp<ATT_MASK_B>(sy, pb, ec, sh);
  else exp_tile<ATT_MASK_B>(sy, pb, ec);
  wg_fence();
#pragma unroll
  for (int k = 0; k < 3; k++) wgmma_rs_n24_tb_h(o, pa[4 * k], pa[4 * k + 1], pa[4 * k + 2], pa[4 * k + 3], dV + k * 48, 1);
#pragma unroll
  for (int k = 0; k < 4; k++) wgmma_rs_n24_tb_h(o, pb[4 * k], pb[4 * k + 1], pb[4 * k + 2], pb[4 * k + 3], dV + (4 + k) * 48, 1);
  wgmma_rs_n64_z(sy, qf.x, qf.y, qf.z, qf.w, dK + 256);
  wg_commit();
  wg_wait<0>();
  fence_regs(sy);
  if (WIDE) {
    fence_regs(o);
    const float up = ex2f(sh);
#pragma unroll
    for (int i = 0; i < 12; i++) o[i] *= up;
  }
}

template <int MODE>
__device__ __forceinline__ void attn_tile(uint64_t dK, uint64_t dV, uint32_t bar, uint32_t vsm, uint4 qf, const ExpC& ec, uint32_t wide,
                                          float shv, uint32_t (&outp)[4], float& lmin) {
  float o[12];
#pragma unroll
  for (int i = 0; i < 12; i++) asm volatile("mov.f32 %0, 0f00000000;" : "=f"(o[i]));
  if (MODE < 2) {
    qf.x = pack_bf16(bf_lo(qf.x) * QSCALE, bf_hi(qf.x) * QSCALE);
    qf.y = pack_bf16(bf_lo(qf.y) * QSCALE, bf_hi(qf.y) * QSCALE);
    qf.z = pack_bf16(bf_lo(qf.z) * QSCALE, bf_hi(qf.z) * QSCALE);
    qf.w = pack_bf16(bf_lo(qf.w) * QSCALE, bf_hi(qf.w) * QSCALE);
    float s0[32], s1[32];
    wg_fence();
    wgmma_rs_n64_z(s0, qf.x, qf.y, qf.z, qf.w, dK);
    wg_commit();
    wg_wait<0>();
    fence_regs(s0);
    int p = 0;
#pragma unroll 1
    while (true) {
      const int pw = (MODE == 1 && wide) ? (__ffs(wide) - 1) >> 1 : 8;
#pragma unroll 1
      for (; p < pw; p++) {
        if (p & 1) mbar_wait(bar + 8 * min((p + 1) >> 1, 3), 0);
        attn_step<false>(s0, s1, o, qf, dK, dV, ec, 0.f);
        attn_step<false>(s1, s0, o, qf, dK + 256, dV + 384, ec, 0.f);
        dK += 512;
        dV += 768;
      }
      if (MODE != 1 || p >= 8) break;
      if (p & 1) mbar_wait(bar + 8 * min((p + 1) >> 1, 3), 0);
      const float sh = fmaxf(__shfl_sync(0xffffffffu, shv, 2 * p), __shfl_sync(0xffffffffu, shv, 2 * p + 1));
      attn_step<true>(s0, s1, o, qf, dK, dV, ec, sh);
      attn_step<true>(s1, s0, o, qf, dK + 256, dV + 384, ec, sh);
      wide &= ~(3u << (2 * p));
      p++;
      dK += 512;
      dV += 768;
    }
  } else {
    float m0 = -INFINITY, m1 = -INFINITY;
#pragma unroll 1
    for (int j = 0; j < 32; j++) {
      if (j == 4) { mbar_wait(bar + 8, 0); mbar_wait(bar + 16, 0); mbar_wait(bar + 24, 0); }
      float s[32], e[32];
      wg_fence();
      wgmma_rs_n64_z(s, qf.x, qf.y, qf.z, qf.w, dK);
      wg_commit();
      wg_wait<0>();
      fence_regs(s);
      safe_exp(s, e, o, m0, m1);
#pragma unroll
      for (int k = 0; k < 4; k++) {
        uint32_t one;
        asm volatile("ld.shared.u32 %0, [%1];" : "=r"(one) : "r"(vsm + (j * 4 + k) * 768 + 256));
        const float* ek = &e[8 * k];
        if (__shfl_sync(0xffffffffu, one, 0) == 0x3C003C00u) {
          const uint32_t p0 = pack_f16(ek[0], ek[1]), p1 = pack_f16(ek[2], ek[3]), p2 = pack_f16(ek[4], ek[5]), p3 = pack_f16(ek[6], ek[7]);
          wg_fence();
          wgmma_rs_n24_tb_h(o, p0, p1, p2, p3, dV + k * 48, 1);
          wg_commit();
          wg_wait<0>();
        } else {
          const uint32_t p0 = pack_bf16(ek[0], ek[1]), p1 = pack_bf16(ek[2], ek[3]), p2 = pack_bf16(ek[4], ek[5]), p3 = pack_bf16(ek[6], ek[7]);
          wg_fence();
          wgmma_rs_n24_tb(o, p0, p1, p2, p3, dV + k * 48, 1);
          wg_commit();
          wg_wait<0>();
        }
        fence_regs(o);
      }
      dK += 128;
      dV += 192;
    }
  }
  fence_regs(o);
  lmin = fminf(o[8], o[10]);
  if (!(o[8] == o[8] && o[10] == o[10])) lmin = 0.f;
  const float r0 = 1.0f / o[8], r1 = 1.0f / o[10];
  outp[0] = pack_bf16(o[0] * r0, o[1] * r0);
  outp[1] = pack_bf16(o[2] * r1, o[3] * r1);
  outp[2] = pack_bf16(o[4] * r0, o[5] * r0);
  outp[3] = pack_bf16(o[6] * r1, o[7] * r1);
}

__device__ __forceinline__ void linear_attn_cta(uint8_t* smem_raw, uint32_t sbase, const CUtensorMap* mo16, int cta) {
  const int warp = threadIdx.x >> 5, lane = threadIdx.x & 31;
  const int hg = warp & 1;
  const uint4* qp = g_qfrag + (size_t)(NH + cta * 8 + hg * 4) * 32 * 128 + lane;
  auto qaddr = [&](int i) {
    const int blk16 = i * 8 + (warp >> 1);
    return qp + (blk16 >> 2) * 128 + (blk16 & 3) * 32;
  };
  uint4 q[2][4];
#pragma unroll
  for (int h = 0; h < 4; h++) {
    q[0][h] = qaddr(0)[h * 32 * 128];
    q[1][h] = qaddr(1)[h * 32 * 128];
  }
  float* red = reinterpret_cast<float*>(smem_raw + (sbase - smem_u32(smem_raw)) + 131072);
  {
    const float* src = g_kvpart + (size_t)cta * 8 * 384;
    float sum[6];
#pragma unroll
    for (int i = 0; i < 6; i++) sum[i] = 0.f;
#pragma unroll
    for (int r = 0; r < 16; r++) {
#pragma unroll
      for (int i = 0; i < 6; i++) sum[i] += src[(size_t)r * NH * 384 + threadIdx.x + i * 512];
    }
#pragma unroll
    for (int i = 0; i < 6; i++) red[threadIdx.x + i * 512] = round_bf16(sum[i]);
  }
  __syncthreads();
  uint32_t bf[4][6];
  {
    const int g = lane >> 2, t = lane & 3;
#pragma unroll
    for (int h = 0; h < 4; h++) {
#pragma unroll
      for (int f = 0; f < 6; f++) {
        const int blk = f >> 1, half = f & 1;
        const int e = (blk == 2) ? 0 : g;
        const int d = 2 * t + 8 * half;
        const int base = (hg * 4 + h) * 384 + (blk * 4 + half * 2 + (e & 1)) * 32 + (e >> 1);
        bf[h][f] = pack_bf16(red[base + (d & 7) * 4], red[base + ((d + 1) & 7) * 4]);
      }
    }
  }
  const uint32_t stg = sbase + warp * 8192;
#pragma unroll 2
  for (int i = 0; i < 16; i++) {
    uint4 qc[4];
#pragma unroll
    for (int h = 0; h < 4; h++) qc[h] = make_uint4(phi2(q[i & 1][h].x), phi2(q[i & 1][h].y), phi2(q[i & 1][h].z), phi2(q[i & 1][h].w));
    if (i + 2 < 16) {
#pragma unroll
      for (int h = 0; h < 4; h++) q[i & 1][h] = qaddr(i + 2)[h * 32 * 128];
    }
    const uint32_t buf = stg + (i & 3) * 2048;
    if (i >= 4) {
      if (lane == 0) asm volatile("cp.async.bulk.wait_group.read 3;" ::: "memory");
      __syncwarp();
    }
#pragma unroll
    for (int h = 0; h < 4; h++) {
      float n0[4] = {0, 0, 0, 0}, n1[4] = {0, 0, 0, 0}, dn[4] = {0, 0, 0, 0};
      hmma(n0, qc[h].x, qc[h].y, qc[h].z, qc[h].w, bf[h][0], bf[h][1]);
      hmma(n1, qc[h].x, qc[h].y, qc[h].z, qc[h].w, bf[h][2], bf[h][3]);
      hmma(dn, qc[h].x, qc[h].y, qc[h].z, qc[h].w, bf[h][4], bf[h][5]);
      const float d0 = __fdividef(1.0f, dn[0] + 1e-6f), d1 = __fdividef(1.0f, dn[2] + 1e-6f);
      const uint32_t r0 = pack_bf16(n0[0] * d0, n0[1] * d0);
      const uint32_t r1 = pack_bf16(n0[2] * d1, n0[3] * d1);
      const uint32_t r2 = pack_bf16(n1[0] * d0, n1[1] * d0);
      const uint32_t r3 = pack_bf16(n1[2] * d1, n1[3] * d1);
      const int row = lane & 15;
      const int chunk = h * 2 + (lane >> 4);
      const uint32_t addr = buf + row * 128 + ((chunk ^ (row & 7)) << 4);
      asm volatile("stmatrix.sync.aligned.m8n8.x4.shared.b16 [%0], {%1,%2,%3,%4};" ::"r"(addr), "r"(r0), "r"(r1), "r"(r2), "r"(r3)
                   : "memory");
    }
    fence_proxy_async();
    __syncwarp();
    if (lane == 0) {
      tma_store_2d(mo16, buf, cta * 128 + hg * 64, (i * 8 + (warp >> 1)) * 16);
      asm volatile("cp.async.bulk.commit_group;" ::: "memory");
    }
  }
  if (lane == 0) asm volatile("cp.async.bulk.wait_group 0;" ::: "memory");
}

__global__ void __launch_bounds__(512, 1)
attn_kernel(const __grid_constant__ CUtensorMap mo16, const uint8_t* __restrict__ woA, const uint8_t* __restrict__ woB) {
  extern __shared__ uint8_t smem_raw[];
  const uint32_t sbase = (smem_u32(smem_raw) + 1023) & ~1023u;
  const uint32_t bar = sbase + KV_HEAD_BYTES;
  if (threadIdx.x == 0) {
    for (int i = 0; i < 4; i++) mbar_init(bar + 8 * i, 2);
    asm volatile("st.shared.v2.u32 [%0], {%1, %2};" ::"r"(bar + 64), "r"(0x3C003C00u), "r"(0x35623562u) : "memory");
    fence_barrier_init();
    fence_proxy_async();
  }
  __syncthreads();
  pdl_launch_dependents();
  if (blockIdx.x >= 128 && threadIdx.x < 16) {
    const int i = (blockIdx.x - 128) * 16 + threadIdx.x;
    const uint8_t* p = (i < 32 ? woA : woB) + (size_t)(i & 31) * 16384;
    asm volatile("cp.async.bulk.prefetch.L2.global [%0], %1;" ::"l"(p), "r"(16384) : "memory");
  }
  if (blockIdx.x >= 128) {
    pdl_wait();
    linear_attn_cta(smem_raw, sbase, &mo16, blockIdx.x - 128);
    return;
  }
  const int head = blockIdx.x >> 2, qb = blockIdx.x & 3;
  const int lane = threadIdx.x & 31;
  const int wg = __shfl_sync(0xffffffffu, threadIdx.x >> 7, 0), warp = __shfl_sync(0xffffffffu, (threadIdx.x >> 5) & 3, 0);
  ExpC ec;
  asm volatile("ld.volatile.shared.v2.u32 {%0, %1}, [%2];" : "=r"(ec.k3c00), "=r"(ec.c2) : "r"(bar + 64));
  const uint64_t dK = mkdesc(sbase, 128, 256, 0);
  const uint64_t dV = mkdesc(sbase + KV_K_BYTES, 384, 128, 0);
  pdl_wait();
  if (threadIdx.x == 0) {
#pragma unroll
    for (int piece = 0; piece < 8; piece++) kv_fetch_piece(sbase, bar, piece);
  }
  uint4 qnext = g_qfrag[(head * 32 + qb * 8 + wg * 2) * 128 + (threadIdx.x & 127)];
  uint4 nrm = make_uint4(0, 0, 0, 0);
  if (lane < 16) nrm = *reinterpret_cast<const uint4*>(&g_nrm[(head * 16 + lane) * 4]);
  const uint32_t km_all = __reduce_max_sync(0xffffffffu, nrm.z);
  const bool v_is_f16 = __reduce_max_sync(0xffffffffu, nrm.w) == 0;
  mbar_wait(bar, 0);
#pragma unroll 1
  for (int t = 0; t < 2; t++) {
    const int tile64 = qb * 8 + wg * 2 + t;
    const uint4 qf = qnext;
    if (t == 0) qnext = g_qfrag[(head * 32 + tile64 + 1) * 128 + (threadIdx.x & 127)];
    const uint32_t qm = __reduce_max_sync(0xffffffffu, lane == (tile64 >> 1) ? (t ? nrm.y : nrm.x) : 0u);
    const float qs = __uint_as_float(qm) * (QSCALE * QSCALE * 1.025f);
    const bool safe_path = !(v_is_f16 && qs * __uint_as_float(km_all) <= 21.5f * 21.5f);
    const float b2 = qs * __uint_as_float(nrm.z);
    const uint32_t wide = __reduce_or_sync(0xffffffffu, b2 > 15.9f * 15.9f ? 1u << lane : 0u);
    const bool verify = qs * __uint_as_float(km_all) > 14.0f * 14.0f;
    uint32_t r[4];
    bool exact = safe_path;
    float lmin;
    if (!safe_path) {
      float shmax = 0.f;
      if (wide == 0) {
        attn_tile<0>(dK, dV, bar, 0, qf, ec, 0, 0.f, r, lmin);
      } else {
        float b;
        asm("sqrt.approx.f32 %0, %1;" : "=f"(b) : "f"(b2));
        const float shv = ceilf(b * 1.0001f - 15.9f);
        attn_tile<1>(dK, dV, bar, 0, qf, ec, wide, shv, r, lmin);
        shmax = __uint_as_float(__reduce_max_sync(0xffffffffu, __float_as_uint(fmaxf(shv, 0.f))));
      }
      if (verify) {
        uint32_t redo;
        asm volatile(
            "{\n.reg .pred p, q;\nsetp.lt.f32 q, %1, %2;\n"
            "barrier.cta.red.or.pred p, %3, 128, q;\nselp.b32 %0, 1, 0, p;\n}"
            : "=r"(redo)
            : "f"(lmin), "f"(ex2f(shmax + 8.f)), "r"(1 + wg)
            : "memory");
        exact = __reduce_max_sync(0xffffffffu, redo) != 0;
      }
    }
    if (exact) attn_tile<2>(dK, dV, bar, sbase + KV_K_BYTES, qf, ec, 0, 0.f, r, lmin);
    store_o(g_o + (size_t)S_LEN * DM, tile64 * 64 + warp * 16, head, lane, r);
  }
}

constexpr int K3_WPRE = 1;
constexpr int K3_STAGES = 4;
constexpr int K3_W_BYTES = 8 * 16384;
constexpr int K3_BAR_OFF = K3_W_BYTES + K3_STAGES * 16384;
constexpr int K3_SMEM = K3_BAR_OFF + 256 + 1024;

__global__ void __launch_bounds__(288, 1)
out_gemm_kernel(const __grid_constant__ CUtensorMap mo, const __grid_constant__ CUtensorMap mwA,
                const __grid_constant__ CUtensorMap mwB, const __grid_constant__ CUtensorMap mout) {
  extern __shared__ uint8_t smem_raw[];
  const uint32_t sbase = (smem_u32(smem_raw) + 1023) & ~1023u;
  const uint32_t bar_full = sbase + K3_BAR_OFF;
  const uint32_t bar_empty = bar_full + 8 * K3_STAGES;
  const uint32_t bar_w = bar_empty + 8 * K3_STAGES;
  const int branch = blockIdx.x >> 6;
  const int rt = (blockIdx.x & 63) >> 2;
  const int ct = blockIdx.x & 3;
  const int warp = threadIdx.x >> 5;
  if (threadIdx.x == 256) {
    const CUtensorMap* mw = branch ? &mwB : &mwA;
    asm volatile("prefetch.tensormap [%0];" ::"l"(mw) : "memory");
    asm volatile("prefetch.tensormap [%0];" ::"l"(&mo) : "memory");
    asm volatile("prefetch.tensormap [%0];" ::"l"(&mout) : "memory");
    for (int i = 0; i < K3_STAGES; i++) {
      mbar_init(bar_full + 8 * i, 1);
      mbar_init(bar_empty + 8 * i, 2);
    }
    for (int i = 0; i < 8; i++) mbar_init(bar_w + 8 * i, 1);
    fence_barrier_init();
    fence_proxy_async();
    for (int kb = 0; kb < K3_WPRE; kb++) {
      mbar_expect_tx(bar_w + 8 * kb, 16384);
      tma_load_2d(sbase + kb * 16384, mw, ct * 128, kb * 64, bar_w + 8 * kb);
      tma_load_2d(sbase + kb * 16384 + 8192, mw, ct * 128 + 64, kb * 64, bar_w + 8 * kb);
    }
  }
  __syncthreads();
  if (warp == 8) {
    if ((threadIdx.x & 31) == 0) {
      const CUtensorMap* mw = branch ? &mwB : &mwA;
      pdl_wait();
      for (int kb = 0; kb < 8; kb++) {
        const int s = kb % K3_STAGES;
        if (kb >= K3_STAGES) mbar_wait(bar_empty + 8 * s, ((kb / K3_STAGES) - 1) & 1);
        mbar_expect_tx(bar_full + 8 * s, 16384);
        tma_load_2d(sbase + K3_W_BYTES + s * 16384, &mo, kb * 64, branch * S_LEN + rt * 128, bar_full + 8 * s);
        const int kw = kb + K3_WPRE;
        if (kw < 8) {
          mbar_expect_tx(bar_w + 8 * kw, 16384);
          tma_load_2d(sbase + kw * 16384, mw, ct * 128, kw * 64, bar_w + 8 * kw);
          tma_load_2d(sbase + kw * 16384 + 8192, mw, ct * 128 + 64, kw * 64, bar_w + 8 * kw);
        }
      }
    }
  } else {
    const int wg = warp >> 2;
    float acc[64];
    for (int kb = 0; kb < 8; kb++) {
      const int s = kb % K3_STAGES;
      mbar_wait(bar_w + 8 * kb, 0);
      mbar_wait(bar_full + 8 * s, (kb / K3_STAGES) & 1);
      const uint64_t dA = mkdesc(sbase + K3_W_BYTES + s * 16384 + wg * 8192, 16, 1024, 1);
      const uint64_t dB = mkdesc(sbase + kb * 16384, 8192, 1024, 1);
      wg_fence();
#pragma unroll
      for (int k = 0; k < 4; k++) wgmma_ss_n128_tb(acc, dA + k * 2, dB + k * 128, (kb | k) != 0);
      wg_commit();
      if (kb > 0) {
        wg_wait<1>();
        if ((threadIdx.x & 127) == 0) mbar_arrive(bar_empty + 8 * ((kb - 1) % K3_STAGES));
      }
    }
    wg_wait<0>();
    fence_regs(acc);
    const uint32_t stg = sbase + K3_W_BYTES + wg * 8192;
    const int lane = threadIdx.x & 31;
    const int rloc = (warp & 3) * 16 + (lane & 15);
#pragma unroll
    for (int c16 = 0; c16 < 8; c16++) {
      const float* a = &acc[c16 * 8];
      const uint32_t r0 = pack_bf16(a[0], a[1]), r1 = pack_bf16(a[2], a[3]), r2 = pack_bf16(a[4], a[5]), r3 = pack_bf16(a[6], a[7]);
      const int chunk = (c16 & 3) * 2 + (lane >> 4);
      const uint32_t addr = stg + (c16 >> 2) * 16384 + rloc * 128 + ((chunk ^ (rloc & 7)) << 4);
      asm volatile("stmatrix.sync.aligned.m8n8.x4.shared.b16 [%0], {%1,%2,%3,%4};" ::"r"(addr), "r"(r0), "r"(r1), "r"(r2), "r"(r3)
                   : "memory");
    }
    fence_proxy_async();
    asm volatile("bar.sync %0, 128;" ::"r"(2 + wg) : "memory");
    if ((threadIdx.x & 127) == 0) {
      tma_store_2d(&mout, stg, branch * DM + ct * 128, rt * 128 + wg * 64);
      tma_store_2d(&mout, stg + 16384, branch * DM + ct * 128 + 64, rt * 128 + wg * 64);
      asm volatile("cp.async.bulk.commit_group;" ::: "memory");
      asm volatile("cp.async.bulk.wait_group.read 0;" ::: "memory");
    }
  }
}

typedef CUresult (*EncodeFn)(CUtensorMap*, CUtensorMapDataType, cuuint32_t, void*, const cuuint64_t*, const cuuint64_t*,
                             const cuuint32_t*, const cuuint32_t*, CUtensorMapInterleave, CUtensorMapSwizzle,
                             CUtensorMapL2promotion, CUtensorMapFloatOOBfill);

void make_map(EncodeFn enc, CUtensorMap* m, const void* ptr, uint64_t inner, uint64_t outer, uint32_t box_inner, uint32_t box_outer) {
  cuuint64_t dims[2] = {inner, outer};
  cuuint64_t strides[1] = {inner * 2};
  cuuint32_t box[2] = {box_inner, box_outer};
  cuuint32_t es[2] = {1, 1};
  enc(m, CU_TENSOR_MAP_DATA_TYPE_BFLOAT16, 2, const_cast<void*>(ptr), dims, strides, box, es, CU_TENSOR_MAP_INTERLEAVE_NONE,
      CU_TENSOR_MAP_SWIZZLE_128B, CU_TENSOR_MAP_L2_PROMOTION_L2_128B, CU_TENSOR_MAP_FLOAT_OOB_FILL_NONE);
}

struct HostState {
  bool init;
  const void* key[7];
  CUtensorMap mxA, mxB, mwA, mwB, mo, mo16, mwoA, mwoB, mout;
};
HostState g_hs;

}

extern "C" void kernel_launch(void* const* d_in, const int* in_sizes, int n_in, void* d_out, int out_size) {
  (void)in_sizes; (void)n_in; (void)out_size;
  HostState& hs = g_hs;
  bool same = hs.init && hs.key[6] == d_out;
  for (int i = 0; i < 6 && same; i++) same = hs.key[i] == d_in[i];
  if (!same) {
    void* fn = nullptr;
    cudaDriverEntryPointQueryResult qr;
    cudaGetDriverEntryPoint("cuTensorMapEncodeTiled", &fn, cudaEnableDefault, &qr);
    EncodeFn enc = (EncodeFn)fn;
    void* go = nullptr;
    cudaGetSymbolAddress(&go, g_o);
    make_map(enc, &hs.mxA, d_in[0], 512, 2048, 64, 128);
    make_map(enc, &hs.mwA, d_in[1], 1536, 512, 64, 32);
    make_map(enc, &hs.mwoA, d_in[2], 512, 512, 64, 64);
    make_map(enc, &hs.mxB, d_in[3], 512, 2048, 64, 128);
    make_map(enc, &hs.mwB, d_in[4], 1536, 512, 64, 32);
    make_map(enc, &hs.mwoB, d_in[5], 512, 512, 64, 64);
    make_map(enc, &hs.mo, go, 512, 4096, 64, 128);
    make_map(enc, &hs.mo16, go, 512, 4096, 64, 16);
    make_map(enc, &hs.mout, d_out, 1024, 2048, 64, 64);
    cudaFuncSetAttribute(qkv_gemm_kernel, cudaFuncAttributeMaxDynamicSharedMemorySize, K1_SMEM);
    cudaFuncSetAttribute(attn_kernel, cudaFuncAttributeMaxDynamicSharedMemorySize, K2_SMEM);
    cudaFuncSetAttribute(out_gemm_kernel, cudaFuncAttributeMaxDynamicSharedMemorySize, K3_SMEM);
    for (int i = 0; i < 6; i++) hs.key[i] = d_in[i];
    hs.key[6] = d_out;
    hs.init = true;
  }
  cudaStream_t st = cudaStreamPerThread;
  {
    cudaLaunchConfig_t cfg = {};
    cfg.gridDim = dim3(128);
    cfg.blockDim = dim3(384);
    cfg.dynamicSmemBytes = K1_SMEM;
    cfg.stream = st;
    cudaLaunchAttribute at[1];
    at[0].id = cudaLaunchAttributeClusterDimension;
    at[0].val.clusterDim.x = 2;
    at[0].val.clusterDim.y = 1;
    at[0].val.clusterDim.z = 1;
    cfg.attrs = at;
    cfg.numAttrs = 1;
    cudaLaunchKernelEx(&cfg, qkv_gemm_kernel, hs.mxA, hs.mxB, hs.mwA, hs.mwB);
  }
  {
    cudaLaunchConfig_t cfg = {};
    cfg.gridDim = dim3(132);
    cfg.blockDim = dim3(512);
    cfg.dynamicSmemBytes = K2_SMEM;
    cfg.stream = st;
    cudaLaunchAttribute at[1];
    at[0].id = cudaLaunchAttributeProgrammaticStreamSerialization;
    at[0].val.programmaticStreamSerializationAllowed = 1;
    cfg.attrs = at;
    cfg.numAttrs = 1;
    cudaLaunchKernelEx(&cfg, attn_kernel, hs.mo16, (const uint8_t*)d_in[2], (const uint8_t*)d_in[5]);
    cfg.gridDim = dim3(128);
    cfg.blockDim = dim3(288);
    cfg.dynamicSmemBytes = K3_SMEM;
    cudaLaunchKernelEx(&cfg, out_gemm_kernel, hs.mo, hs.mwoA, hs.mwoB, hs.mout);
  }
}
```
